```python
import torch

def _softmax(x, axis=-1):
    return torch.softmax(x, dim=axis)
def _gelu(x):
    return torch.nn.functional.gelu(x, approximate="tanh")
def _silu(x):
    return torch.nn.functional.silu(x)
def _sigmoid(x):
    return torch.sigmoid(x)
def _layernorm(x, axis=-1, eps=1e-5):
    m = x.mean(dim=axis, keepdim=True)
    v = x.var(dim=axis, keepdim=True, unbiased=False)
    return (x - m) / torch.sqrt(v + eps)
def _scatter_add(tgt, idx, src, axis=0):
    return tgt.clone().index_add_(axis, idx, src)
def _segment_sum(src, seg, n):
    out = torch.zeros((n,) + src.shape[1:], dtype=src.dtype)
    return out.index_add_(0, seg, src)
def _pad(x, pw):
    flat = tuple(v for pair in reversed(pw) for v in pair)
    return torch.nn.functional.pad(x, flat)

kernel_name = 'concat_heads__ssm_conv_h3__grouped_kv_mqa__prompt'

def setup_inputs():

    _w = (lambda a: (lambda t: t.to(torch.bfloat16) if t.is_floating_point() else t)(torch.as_tensor(a)))
    def _A_setup():
        B, S, D = 1, 2048, 512
        ks = 4
        return {
            "q": _w((lambda *s: torch.randn(*s, dtype=torch.bfloat16) * 0.05)(B, S, D)),
            "k": _w((lambda *s: torch.randn(*s, dtype=torch.bfloat16) * 0.2)(B, S, D)),
            "v": _w((lambda *s: torch.randn(*s, dtype=torch.bfloat16) * 0.2)(B, S, D)),
            "shift_k": _w((lambda *s: torch.randn(*s, dtype=torch.bfloat16) * 0.2)(D, ks) * 0.5),
            "ssm_k": _w((lambda *s: torch.randn(*s, dtype=torch.bfloat16) * 0.4)(D, S) * (1.0 / S ** 0.5)),
            "ssm_D": _w((lambda *s: torch.randn(*s, dtype=torch.bfloat16) * 0.2)(D)),
        }
    _A_in = _A_setup()

    def _B_setup():
        B, S, D, H = 1, 2048, 512, 32
        Dh = D // H
        return {
            "x": _w((lambda *s: torch.randn(*s, dtype=torch.bfloat16) * 0.05)(B, S, D)),
            "wq": _w((lambda *s: torch.randn(*s, dtype=torch.bfloat16) * 0.8)(D, H * Dh)),
            "wk": _w((lambda *s: torch.randn(*s, dtype=torch.bfloat16) * 0.8)(D, Dh)),
            "wv": _w((lambda *s: torch.randn(*s, dtype=torch.bfloat16) * 0.05)(D, Dh)),
            "wo": _w((lambda *s: torch.randn(*s, dtype=torch.bfloat16) * 0.05)(H * Dh, D)),
        }
    _B_in = _B_setup()

    return {
        "A_q": _A_in["q"],
        "A_k": _A_in["k"],
        "A_v": _A_in["v"],
        "A_shift_k": _A_in["shift_k"],
        "A_ssm_k": _A_in["ssm_k"],
        "A_ssm_D": _A_in["ssm_D"],
        "B_x": _B_in["x"],
        "B_wq": _B_in["wq"],
        "B_wk": _B_in["wk"],
        "B_wv": _B_in["wv"],
        "B_wo": _B_in["wo"],
    }

def reference(A_q, A_k, A_v, A_shift_k, A_ssm_k, A_ssm_D, B_x, B_wq, B_wk, B_wv, B_wo):
    def _A_ref(q, k, v, shift_k, ssm_k, ssm_D):
        B, S, D = q.shape
        ks = shift_k.shape[-1]
        k_pad = _pad(k, ((0, 0), (ks - 1, 0), (0, 0)))
        k_shift = torch.zeros_like(k)
        for t in range(ks):
            k_shift = k_shift + k_pad[:, t:t + S, :] * shift_k[:, ks - 1 - t][None, None, :]
        kv = k_shift * v
        L = 2 * S
        kv_pad = _pad(kv, ((0, 0), (0, S), (0, 0)))
        kf_pad = _pad(ssm_k, ((0, 0), (0, S)))
        kv_f = (lambda x, axes=(-2,-1): torch.fft.rfft2(x.float(), dim=axes))(kv_pad[:, None, :, :], axes=(1, 2))
        kf_f = (lambda x, axes=(-2,-1): torch.fft.rfft2(x.float(), dim=axes))(kf_pad[:, None, :], axes=(1, 2))
        kf_f = (lambda x, *d: x.permute(*d))(kf_f, 1, 2, 0)
        y_f = kv_f * kf_f[None, :, :, :]
        y = (lambda x, s, axes=(-2,-1): torch.fft.irfft2(x, s=s, dim=axes).to(torch.bfloat16))(y_f, (1, L), axes=(1, 2))[:, 0, :S, :]
        y = y + kv * ssm_D[None, None, :]
        return q * y

    def _B_ref(x, wq, wk, wv, wo):
        B, S, D = x.shape
        H = 32
        Dh = D // H
        q = (lambda x, *d: x.permute(*d))((x @ wq).reshape(B, S, H, Dh), 0, 2, 1, 3)
        k = x @ wk
        v = x @ wv
        scores = torch.einsum("bhqd,bkd->bhqk", q, k) * (Dh ** -0.5)
        p = _softmax(scores, axis=-1)
        o = torch.einsum("bhqk,bkd->bhqd", p, v)
        return (lambda x, *d: x.permute(*d))(o, 0, 2, 1, 3).reshape(B, S, H * Dh) @ wo

    a = _A_ref(A_q, A_k, A_v, A_shift_k, A_ssm_k, A_ssm_D)
    b = _B_ref(B_x, B_wq, B_wk, B_wv, B_wo)
    return torch.concatenate([a, b], axis=-1)
```

```cpp
#include <cuda_runtime.h>
#include <cuda_bf16.h>
#include <cuda_fp16.h>
#include <cuda.h>
#include <stdint.h>

namespace {

constexpr int S_LEN = 2048;
constexpr int NCTA = 128;
constexpr int NTHREADS = 640;

constexpr uint32_t OFF_K = 0;
constexpr uint32_t OFF_V = 65536;
constexpr uint32_t OFF_VONES = OFF_V + 32768;
constexpr uint32_t OFF_X = 132096;
constexpr uint32_t OFF_C = 197632;
constexpr uint32_t C_KVC = OFF_C;
constexpr uint32_t C_H0 = OFF_C + 16384;
constexpr uint32_t C_H1 = C_H0 + 4608;
constexpr uint32_t C_Z = C_H1 + 4608;
constexpr uint32_t OFF_BAR = C_Z + 8448;
constexpr uint32_t SMEM_TOTAL = 232448;

enum {
    B_WKV = 0, B_X16 = 1, B_Q = 2, B_QEMPTY = 10, B_QDONE = 14, B_KV = 15, B_WO = 23, B_O = 31, B_ATT = 39, B_H = 40, B_COUNT = 42
};
constexpr uint32_t OFF_MISC = OFF_BAR + 8 * B_COUNT;

__device__ __align__(1024) uint8_t g_kimg[65536];
__device__ __align__(1024) uint8_t g_vimg[65792];
__device__ __align__(1024) __nv_bfloat16 g_vraw[S_LEN * 16];
__device__ __align__(1024) __nv_bfloat16 g_o[S_LEN * 512];
__device__ float2 g_stats[NCTA];
__device__ unsigned int g_kv_count;
__device__ unsigned int g_o_count[32];
__device__ unsigned int g_done;
#define TSTAMP(i) do {} while (0)

__device__ __forceinline__ void wg_fence() { asm volatile("wgmma.fence.sync.aligned;" ::: "memory"); }
__device__ __forceinline__ void wg_commit() { asm volatile("wgmma.commit_group.sync.aligned;" ::: "memory"); }
template <int N> __device__ __forceinline__ void wg_wait() { asm volatile("wgmma.wait_group.sync.aligned %0;" ::"n"(N) : "memory"); }
template <int N> __device__ __forceinline__ void fence_regs(float* r) {
#pragma unroll
    for (int i = 0; i < N; i++) asm volatile("" : "+f"(r[i])::"memory");
}
template <int N> __device__ __forceinline__ void fence_uregs(uint32_t* r) {
#pragma unroll
    for (int i = 0; i < N; i++) asm volatile("" : "+r"(r[i])::"memory");
}
__device__ __forceinline__ uint64_t make_desc(uint32_t saddr, uint32_t lbo, uint32_t sbo, uint32_t swz) {
    return (uint64_t)((saddr & 0x3FFFF) >> 4) | ((uint64_t)(lbo >> 4) << 16) | ((uint64_t)(sbo >> 4) << 32) | ((uint64_t)swz << 62);
}
__device__ __forceinline__ void mbar_init(uint32_t bar, uint32_t count) {
    asm volatile("mbarrier.init.shared::cta.b64 [%0], %1;" ::"r"(bar), "r"(count) : "memory");
}
__device__ __forceinline__ void mbar_expect_tx(uint32_t bar, uint32_t bytes) {
    asm volatile("mbarrier.arrive.expect_tx.shared::cta.b64 _, [%0], %1;" ::"r"(bar), "r"(bytes) : "memory");
}
__device__ __forceinline__ void mbar_arrive(uint32_t bar) {
    asm volatile("mbarrier.arrive.shared::cta.b64 _, [%0];" ::"r"(bar) : "memory");
}
__device__ __forceinline__ bool mbar_try(uint32_t bar, uint32_t parity) {
    uint32_t ok;
    asm volatile("{\n.reg .pred p;\nmbarrier.try_wait.parity.shared::cta.b64 p, [%1], %2;\nselp.u32 %0, 1, 0, p;\n}\n"
                 : "=r"(ok) : "r"(bar), "r"(parity) : "memory");
    return ok != 0;
}
__device__ __forceinline__ void mbar_wait(uint32_t bar, uint32_t parity) {
    uint32_t spins = 0;
    while (!mbar_try(bar, parity)) {
        if (++spins > (1u << 24)) __trap();
    }
}
__device__ __forceinline__ void tma2d(uint32_t dst, const CUtensorMap* tm, int c0, int c1, uint32_t bar) {
    asm volatile("cp.async.bulk.tensor.2d.shared::cluster.global.mbarrier::complete_tx::bytes [%0], [%1, {%3, %4}], [%2];"
                 ::"r"(dst), "l"((uint64_t)tm), "r"(bar), "r"(c0), "r"(c1) : "memory");
}
__device__ __forceinline__ void bulk_g2s(uint32_t dst, const void* src, uint32_t bytes, uint32_t bar) {
    asm volatile("cp.async.bulk.shared::cluster.global.mbarrier::complete_tx::bytes [%0], [%1], %2, [%3];"
                 ::"r"(dst), "l"(src), "r"(bytes), "r"(bar) : "memory");
}
__device__ __forceinline__ void fence_async_all() { asm volatile("fence.proxy.async;" ::: "memory"); }
__device__ __forceinline__ void fence_async_smem() { asm volatile("fence.proxy.async.shared::cta;" ::: "memory"); }
__device__ __forceinline__ void named_bar(int id, int n) { asm volatile("bar.sync %0, %1;" ::"r"(id), "r"(n) : "memory"); }
__device__ __forceinline__ bool named_bar_and(int id, int n, bool pred) {
    uint32_t r;
    asm volatile("{\n.reg .pred p, q;\nsetp.ne.u32 p, %3, 0;\nbarrier.cta.red.and.pred q, %1, %2, p;\nselp.u32 %0, 1, 0, q;\n}\n"
                 : "=r"(r) : "r"(id), "r"(n), "r"((uint32_t)pred) : "memory");
    return r != 0;
}
__device__ __forceinline__ unsigned int ld_acquire(const unsigned int* p) {
    unsigned int v;
    asm volatile("ld.acquire.gpu.global.u32 %0, [%1];" : "=r"(v) : "l"(p) : "memory");
    return v;
}
__device__ __forceinline__ void red_release_add(unsigned int* p, unsigned int v) {
    asm volatile("red.release.gpu.global.add.u32 [%0], %1;" ::"l"(p), "r"(v) : "memory");
}
__device__ __forceinline__ void poll_counter(const unsigned int* p, unsigned int target) {
    uint32_t spins = 0;
    while (ld_acquire(p) < target) {
        if (++spins > (1u << 22)) __trap();
    }
}
__device__ __forceinline__ float ex2f(float x) { float y; asm("ex2.approx.ftz.f32 %0, %1;" : "=f"(y) : "f"(x)); return y; }
__device__ __forceinline__ uint32_t pack_f16(float lo, float hi) { uint32_t r; asm("cvt.rn.f16x2.f32 %0, %1, %2;" : "=r"(r) : "f"(hi), "f"(lo)); return r; }
__device__ __forceinline__ uint32_t pack_bf16(float lo, float hi) { uint32_t r; asm("cvt.rn.bf16x2.f32 %0, %1, %2;" : "=r"(r) : "f"(hi), "f"(lo)); return r; }
__device__ __forceinline__ float bf_lo(uint32_t v) { return __uint_as_float(v << 16); }
__device__ __forceinline__ float bf_hi(uint32_t v) { return __uint_as_float(v & 0xFFFF0000u); }
__device__ __forceinline__ uint32_t hfma2(uint32_t a, uint32_t b, uint32_t c) { uint32_t r; asm("fma.rn.f16x2 %0, %1, %2, %3;" : "=r"(r) : "r"(a), "r"(b), "r"(c)); return r; }
__device__ __forceinline__ uint32_t bmul2(uint32_t a, uint32_t b) { uint32_t r; asm("mul.rn.bf16x2 %0, %1, %2;" : "=r"(r) : "r"(a), "r"(b)); return r; }
__device__ __forceinline__ uint32_t badd2(uint32_t a, uint32_t b) { uint32_t r; asm("add.rn.bf16x2 %0, %1, %2;" : "=r"(r) : "r"(a), "r"(b)); return r; }
template <int LUT> __device__ __forceinline__ uint32_t lop3(uint32_t a, uint32_t b, uint32_t c) {
    uint32_t r; asm("lop3.b32 %0, %1, %2, %3, %4;" : "=r"(r) : "r"(a), "r"(b), "r"(c), "n"(LUT)); return r;
}
__device__ __forceinline__ uint32_t lds32(uint32_t a) { uint32_t v; asm volatile("ld.shared.u32 %0, [%1];" : "=r"(v) : "r"(a)); return v; }
__device__ __forceinline__ float ldsf(uint32_t a) { float v; asm volatile("ld.shared.f32 %0, [%1];" : "=f"(v) : "r"(a)); return v; }
__device__ __forceinline__ uint32_t lds16(uint32_t a) { uint16_t v; asm volatile("ld.shared.u16 %0, [%1];" : "=h"(v) : "r"(a)); return v; }
__device__ __forceinline__ uint4 lds128(uint32_t a) { uint4 v; asm volatile("ld.shared.v4.u32 {%0,%1,%2,%3}, [%4];" : "=r"(v.x), "=r"(v.y), "=r"(v.z), "=r"(v.w) : "r"(a)); return v; }
__device__ __forceinline__ void sts32(uint32_t a, uint32_t v) { asm volatile("st.shared.u32 [%0], %1;" ::"r"(a), "r"(v) : "memory"); }
__device__ __forceinline__ void sts16(uint32_t a, uint32_t v) { asm volatile("st.shared.u16 [%0], %1;" ::"r"(a), "h"((uint16_t)v) : "memory"); }
__device__ __forceinline__ void sts64f(uint32_t a, float x, float y) { asm volatile("st.shared.v2.f32 [%0], {%1,%2};" ::"r"(a), "f"(x), "f"(y) : "memory"); }
__device__ __forceinline__ void sts128(uint32_t a, uint32_t x, uint32_t y, uint32_t z, uint32_t w) {
    asm volatile("st.shared.v4.u32 [%0], {%1,%2,%3,%4};" ::"r"(a), "r"(x), "r"(y), "r"(z), "r"(w) : "memory");
}

__device__ __forceinline__ void wg_ss_n32_tb(float* d, uint64_t descA, uint64_t descB) {
    asm volatile("wgmma.mma_async.sync.aligned.m64n32k16.f32.bf16.bf16 {%0,%1,%2,%3,%4,%5,%6,%7,%8,%9,%10,%11,%12,%13,%14,%15}, %16, %17, 1, 1, 1, 0, 1;\n"
        : "+f"(d[0]), "+f"(d[1]), "+f"(d[2]), "+f"(d[3]), "+f"(d[4]), "+f"(d[5]), "+f"(d[6]), "+f"(d[7]), "+f"(d[8]), "+f"(d[9]), "+f"(d[10]), "+f"(d[11]), "+f"(d[12]), "+f"(d[13]), "+f"(d[14]), "+f"(d[15])
        : "l"(descA), "l"(descB));
}
__device__ __forceinline__ void wg_qk_n64(float* d, const uint32_t* a, uint64_t desc) {
    asm volatile("wgmma.mma_async.sync.aligned.m64n64k16.f32.bf16.bf16 {%0,%1,%2,%3,%4,%5,%6,%7,%8,%9,%10,%11,%12,%13,%14,%15,%16,%17,%18,%19,%20,%21,%22,%23,%24,%25,%26,%27,%28,%29,%30,%31}, {%32,%33,%34,%35}, %36, 0, 1, 1, 0;\n"
        : "+f"(d[0]), "+f"(d[1]), "+f"(d[2]), "+f"(d[3]), "+f"(d[4]), "+f"(d[5]), "+f"(d[6]), "+f"(d[7]), "+f"(d[8]), "+f"(d[9]), "+f"(d[10]), "+f"(d[11]), "+f"(d[12]), "+f"(d[13]), "+f"(d[14]), "+f"(d[15]), "+f"(d[16]), "+f"(d[17]), "+f"(d[18]), "+f"(d[19]), "+f"(d[20]), "+f"(d[21]), "+f"(d[22]), "+f"(d[23]), "+f"(d[24]), "+f"(d[25]), "+f"(d[26]), "+f"(d[27]), "+f"(d[28]), "+f"(d[29]), "+f"(d[30]), "+f"(d[31])
        : "r"(a[0]), "r"(a[1]), "r"(a[2]), "r"(a[3]), "l"(desc));
}
__device__ __forceinline__ void wg_pv_n24(float* d, const uint32_t* a, uint64_t desc) {
    asm volatile("wgmma.mma_async.sync.aligned.m64n24k16.f32.f16.f16 {%0,%1,%2,%3,%4,%5,%6,%7,%8,%9,%10,%11}, {%12,%13,%14,%15}, %16, 1, 1, 1, 1;\n"
        : "+f"(d[0]), "+f"(d[1]), "+f"(d[2]), "+f"(d[3]), "+f"(d[4]), "+f"(d[5]), "+f"(d[6]), "+f"(d[7]), "+f"(d[8]), "+f"(d[9]), "+f"(d[10]), "+f"(d[11])
        : "r"(a[0]), "r"(a[1]), "r"(a[2]), "r"(a[3]), "l"(desc));
}
__device__ __forceinline__ void wg_cv_n8(float* d, const uint32_t* a, uint64_t desc) {
    asm volatile("wgmma.mma_async.sync.aligned.m64n8k16.f32.bf16.bf16 {%0,%1,%2,%3}, {%4,%5,%6,%7}, %8, 1, 1, 1, 0;\n"
        : "+f"(d[0]), "+f"(d[1]), "+f"(d[2]), "+f"(d[3])
        : "r"(a[0]), "r"(a[1]), "r"(a[2]), "r"(a[3]), "l"(desc));
}
__device__ __forceinline__ void wg_cv_n16(float* d, const uint32_t* a, uint64_t desc) {
    asm volatile("wgmma.mma_async.sync.aligned.m64n16k16.f32.bf16.bf16 {%0,%1,%2,%3,%4,%5,%6,%7}, {%8,%9,%10,%11}, %12, 1, 1, 1, 0;\n"
        : "+f"(d[0]), "+f"(d[1]), "+f"(d[2]), "+f"(d[3]), "+f"(d[4]), "+f"(d[5]), "+f"(d[6]), "+f"(d[7])
        : "r"(a[0]), "r"(a[1]), "r"(a[2]), "r"(a[3]), "l"(desc));
}
__device__ __forceinline__ void wg_cv_n24(float* d, const uint32_t* a, uint64_t desc) {
    asm volatile("wgmma.mma_async.sync.aligned.m64n24k16.f32.bf16.bf16 {%0,%1,%2,%3,%4,%5,%6,%7,%8,%9,%10,%11}, {%12,%13,%14,%15}, %16, 1, 1, 1, 0;\n"
        : "+f"(d[0]), "+f"(d[1]), "+f"(d[2]), "+f"(d[3]), "+f"(d[4]), "+f"(d[5]), "+f"(d[6]), "+f"(d[7]), "+f"(d[8]), "+f"(d[9]), "+f"(d[10]), "+f"(d[11])
        : "r"(a[0]), "r"(a[1]), "r"(a[2]), "r"(a[3]), "l"(desc));
}
__device__ __forceinline__ void wg_cv_n32(float* d, const uint32_t* a, uint64_t desc) {
    asm volatile("wgmma.mma_async.sync.aligned.m64n32k16.f32.bf16.bf16 {%0,%1,%2,%3,%4,%5,%6,%7,%8,%9,%10,%11,%12,%13,%14,%15}, {%16,%17,%18,%19}, %20, 1, 1, 1, 0;\n"
        : "+f"(d[0]), "+f"(d[1]), "+f"(d[2]), "+f"(d[3]), "+f"(d[4]), "+f"(d[5]), "+f"(d[6]), "+f"(d[7]), "+f"(d[8]), "+f"(d[9]), "+f"(d[10]), "+f"(d[11]), "+f"(d[12]), "+f"(d[13]), "+f"(d[14]), "+f"(d[15])
        : "r"(a[0]), "r"(a[1]), "r"(a[2]), "r"(a[3]), "l"(desc));
}
__device__ __forceinline__ void wg_cv_n40(float* d, const uint32_t* a, uint64_t desc) {
    asm volatile("wgmma.mma_async.sync.aligned.m64n40k16.f32.bf16.bf16 {%0,%1,%2,%3,%4,%5,%6,%7,%8,%9,%10,%11,%12,%13,%14,%15,%16,%17,%18,%19}, {%20,%21,%22,%23}, %24, 1, 1, 1, 0;\n"
        : "+f"(d[0]), "+f"(d[1]), "+f"(d[2]), "+f"(d[3]), "+f"(d[4]), "+f"(d[5]), "+f"(d[6]), "+f"(d[7]), "+f"(d[8]), "+f"(d[9]), "+f"(d[10]), "+f"(d[11]), "+f"(d[12]), "+f"(d[13]), "+f"(d[14]), "+f"(d[15]), "+f"(d[16]), "+f"(d[17]), "+f"(d[18]), "+f"(d[19])
        : "r"(a[0]), "r"(a[1]), "r"(a[2]), "r"(a[3]), "l"(desc));
}
__device__ __forceinline__ void wg_cv_n48(float* d, const uint32_t* a, uint64_t desc) {
    asm volatile("wgmma.mma_async.sync.aligned.m64n48k16.f32.bf16.bf16 {%0,%1,%2,%3,%4,%5,%6,%7,%8,%9,%10,%11,%12,%13,%14,%15,%16,%17,%18,%19,%20,%21,%22,%23}, {%24,%25,%26,%27}, %28, 1, 1, 1, 0;\n"
        : "+f"(d[0]), "+f"(d[1]), "+f"(d[2]), "+f"(d[3]), "+f"(d[4]), "+f"(d[5]), "+f"(d[6]), "+f"(d[7]), "+f"(d[8]), "+f"(d[9]), "+f"(d[10]), "+f"(d[11]), "+f"(d[12]), "+f"(d[13]), "+f"(d[14]), "+f"(d[15]), "+f"(d[16]), "+f"(d[17]), "+f"(d[18]), "+f"(d[19]), "+f"(d[20]), "+f"(d[21]), "+f"(d[22]), "+f"(d[23])
        : "r"(a[0]), "r"(a[1]), "r"(a[2]), "r"(a[3]), "l"(desc));
}
__device__ __forceinline__ void wg_cv_n56(float* d, const uint32_t* a, uint64_t desc) {
    asm volatile("wgmma.mma_async.sync.aligned.m64n56k16.f32.bf16.bf16 {%0,%1,%2,%3,%4,%5,%6,%7,%8,%9,%10,%11,%12,%13,%14,%15,%16,%17,%18,%19,%20,%21,%22,%23,%24,%25,%26,%27}, {%28,%29,%30,%31}, %32, 1, 1, 1, 0;\n"
        : "+f"(d[0]), "+f"(d[1]), "+f"(d[2]), "+f"(d[3]), "+f"(d[4]), "+f"(d[5]), "+f"(d[6]), "+f"(d[7]), "+f"(d[8]), "+f"(d[9]), "+f"(d[10]), "+f"(d[11]), "+f"(d[12]), "+f"(d[13]), "+f"(d[14]), "+f"(d[15]), "+f"(d[16]), "+f"(d[17]), "+f"(d[18]), "+f"(d[19]), "+f"(d[20]), "+f"(d[21]), "+f"(d[22]), "+f"(d[23]), "+f"(d[24]), "+f"(d[25]), "+f"(d[26]), "+f"(d[27])
        : "r"(a[0]), "r"(a[1]), "r"(a[2]), "r"(a[3]), "l"(desc));
}
__device__ __forceinline__ void wg_cv_n64(float* d, const uint32_t* a, uint64_t desc) {
    asm volatile("wgmma.mma_async.sync.aligned.m64n64k16.f32.bf16.bf16 {%0,%1,%2,%3,%4,%5,%6,%7,%8,%9,%10,%11,%12,%13,%14,%15,%16,%17,%18,%19,%20,%21,%22,%23,%24,%25,%26,%27,%28,%29,%30,%31}, {%32,%33,%34,%35}, %36, 1, 1, 1, 0;\n"
        : "+f"(d[0]), "+f"(d[1]), "+f"(d[2]), "+f"(d[3]), "+f"(d[4]), "+f"(d[5]), "+f"(d[6]), "+f"(d[7]), "+f"(d[8]), "+f"(d[9]), "+f"(d[10]), "+f"(d[11]), "+f"(d[12]), "+f"(d[13]), "+f"(d[14]), "+f"(d[15]), "+f"(d[16]), "+f"(d[17]), "+f"(d[18]), "+f"(d[19]), "+f"(d[20]), "+f"(d[21]), "+f"(d[22]), "+f"(d[23]), "+f"(d[24]), "+f"(d[25]), "+f"(d[26]), "+f"(d[27]), "+f"(d[28]), "+f"(d[29]), "+f"(d[30]), "+f"(d[31])
        : "r"(a[0]), "r"(a[1]), "r"(a[2]), "r"(a[3]), "l"(desc));
}

template <int N> __device__ __forceinline__ void wg_cv(float* d, const uint32_t* a, uint64_t desc);
template <> __device__ __forceinline__ void wg_cv<8>(float* d, const uint32_t* a, uint64_t s) { wg_cv_n8(d, a, s); }
template <> __device__ __forceinline__ void wg_cv<16>(float* d, const uint32_t* a, uint64_t s) { wg_cv_n16(d, a, s); }
template <> __device__ __forceinline__ void wg_cv<24>(float* d, const uint32_t* a, uint64_t s) { wg_cv_n24(d, a, s); }
template <> __device__ __forceinline__ void wg_cv<32>(float* d, const uint32_t* a, uint64_t s) { wg_cv_n32(d, a, s); }
template <> __device__ __forceinline__ void wg_cv<40>(float* d, const uint32_t* a, uint64_t s) { wg_cv_n40(d, a, s); }
template <> __device__ __forceinline__ void wg_cv<48>(float* d, const uint32_t* a, uint64_t s) { wg_cv_n48(d, a, s); }
template <> __device__ __forceinline__ void wg_cv<56>(float* d, const uint32_t* a, uint64_t s) { wg_cv_n56(d, a, s); }
template <> __device__ __forceinline__ void wg_cv<64>(float* d, const uint32_t* a, uint64_t s) { wg_cv_n64(d, a, s); }

constexpr uint32_t POLYMASK = 0xB5B5u;
__device__ __forceinline__ void softmax_fast(const float* s, uint32_t* p, uint32_t mlo) {
    const uint32_t C3 = 0x2cfb2cfbu, C2 = 0x9fec9fecu, C1 = 0x37a837a8u, C0 = 0x37383738u;
#pragma unroll
    for (int i = 0; i < 16; i++) {
        const float s0 = s[2 * i], s1 = s[2 * i + 1];
        if ((POLYMASK >> i) & 1) {
            const float t0 = s0 + 12303.0f, t1 = s1 + 12303.0f;
            const uint32_t T = __byte_perm(__float_as_uint(t0), __float_as_uint(t1), 0x5410);
            const uint32_t U = lop3<0xEA>(T, mlo, 0x3C003C00u);
            uint32_t h = hfma2(U, C3, C2);
            h = hfma2(h, U, C1);
            h = hfma2(h, U, C0);
            p[i] = lop3<0xE4>(h, T, 0x03FF03FFu);
        } else {
            p[i] = pack_f16(ex2f(s0), ex2f(s1));
        }
    }
}

__device__ __forceinline__ void gemm_chunk(float* acc, uint32_t a_addr, uint32_t b_addr) {
    const uint64_t da = make_desc(a_addr, 16, 1024, 1);
    const uint64_t db = make_desc(b_addr, 8192, 1024, 1);
#pragma unroll
    for (int ks = 0; ks < 4; ks++) wg_ss_n32_tb(acc, da + ks * 2, db + ks * 128);
}

struct Params {
    const __nv_bfloat16 *aq, *ak, *av, *shift_k, *ssm_D;
    __nv_bfloat16* out;
};

template <int NQ>
__device__ __forceinline__ void conv_group(float* D, uint32_t zaddr, uint64_t hdesc) {
    uint32_t a[2][8];
    float* Dn = D + (64 - NQ) / 2;
#pragma unroll
    for (int hq = 0; hq < 2; hq++) {
#pragma unroll
        for (int u = 0; u < 2; u++) {
            const int qi = hq * 2 + u;
            const uint32_t z = zaddr + qi * 256;
            a[u][0] = lds32(z);       a[u][1] = lds32(z + 32); a[u][2] = lds32(z - 32); a[u][3] = lds32(z);
            a[u][4] = lds32(z - 64);  a[u][5] = lds32(z - 32); a[u][6] = lds32(z - 96); a[u][7] = lds32(z - 64);
        }
        fence_uregs<8>(a[0]); fence_uregs<8>(a[1]);
        wg_fence();
#pragma unroll
        for (int u = 0; u < 2; u++) {
            const int qi = hq * 2 + u;
            wg_cv<NQ>(Dn, &a[u][0], hdesc - qi * 8);
            wg_cv<NQ>(Dn, &a[u][4], hdesc - qi * 8 + 2);
        }
        wg_commit();
        wg_wait<0>();
        fence_regs<NQ / 2>(Dn);
    }
}

__global__ void __launch_bounds__(NTHREADS, 1)
fused_kernel(const __grid_constant__ CUtensorMap tm_x, const __grid_constant__ CUtensorMap tm_wq,
             const __grid_constant__ CUtensorMap tm_wo, const __grid_constant__ CUtensorMap tm_wk,
             const __grid_constant__ CUtensorMap tm_wv, const __grid_constant__ CUtensorMap tm_o,
             const __grid_constant__ CUtensorMap tm_h, const Params prm) {
    extern __shared__ __align__(1024) uint8_t smem_raw[];
    const uint32_t sb = (uint32_t)__cvta_generic_to_shared(smem_raw);
    const int warp_id = __shfl_sync(0xffffffffu, threadIdx.x >> 5, 0);
    const int lane = threadIdx.x & 31;
    const int g = lane >> 2, t = lane & 3;
    const int b = blockIdx.x, pb = b >> 2, hg = b & 3;
    auto bar = [&](int i) { return sb + OFF_BAR + 8 * i; };

    if (threadIdx.x == 0) {
        TSTAMP(0);
        mbar_init(bar(B_WKV), 1); mbar_init(bar(B_X16), 1);
        for (int j = 0; j < 8; j++) { mbar_init(bar(B_Q + j), 1); mbar_init(bar(B_KV + j), j == 0 ? 2 : 1); mbar_init(bar(B_WO + j), 1); mbar_init(bar(B_O + j), 1); }
        for (int j = 0; j < 4; j++) mbar_init(bar(B_QEMPTY + j), 4);
        mbar_init(bar(B_QDONE), 4); mbar_init(bar(B_ATT), 4);
        mbar_init(bar(B_H), 1); mbar_init(bar(B_H + 1), 1);
        asm volatile("fence.mbarrier_init.release.cluster;" ::: "memory");
    }
    __syncthreads();

    if (warp_id < 16) {
        const int w = warp_id >> 2, wq = warp_id & 3;
        float acc[16];
#pragma unroll
        for (int i = 0; i < 16; i++) acc[i] = 0.f;
        fence_regs<16>(acc);
        const uint32_t bcol = (w >> 1) * 8192 + (w & 1) * 64;
        mbar_wait(bar(B_X16), 0);
#pragma unroll 1
        for (int j = 0; j < 8; j++) {
            mbar_wait(bar(B_Q + j), 0);
            wg_fence();
            gemm_chunk(acc, sb + OFF_X + j * 8192, sb + OFF_V + (j & 3) * 16384 + bcol);
            wg_commit();
            wg_wait<0>();
            if (j < 4 && (threadIdx.x & 127) == 0) mbar_arrive(bar(B_QEMPTY + j));
        }
        fence_regs<16>(acc);
        if ((threadIdx.x & 127) == 0) { mbar_arrive(bar(B_QDONE)); if (w == 0) TSTAMP(1); }
        uint32_t qa[2][4];
        float qn[2][2];
        {
            const float c = 0.25f * 1.4426950408889634f;
#pragma unroll
            for (int hh = 0; hh < 2; hh++) {
                float n0 = 0.f, n1 = 0.f;
#pragma unroll
                for (int i = 0; i < 4; i++) {
                    const uint32_t qb = pack_bf16(acc[8 * hh + 2 * i], acc[8 * hh + 2 * i + 1]);
                    const uint32_t qs = pack_bf16(bf_lo(qb) * c, bf_hi(qb) * c);
                    qa[hh][i] = qs;
                    const float e = bf_lo(qs) * bf_lo(qs) + bf_hi(qs) * bf_hi(qs);
                    if (i & 1) n1 += e; else n0 += e;
                }
                n0 += __shfl_xor_sync(0xffffffffu, n0, 1); n0 += __shfl_xor_sync(0xffffffffu, n0, 2);
                n1 += __shfl_xor_sync(0xffffffffu, n1, 1); n1 += __shfl_xor_sync(0xffffffffu, n1, 2);
                qn[hh][0] = n0; qn[hh][1] = n1;
            }
        }
        uint32_t mlo = 0x03FF03FFu; asm volatile("" : "+r"(mlo));
        const uint64_t kdesc0 = make_desc(sb + OFF_K, 128, 256, 0);
        const uint64_t vdesc0 = make_desc(sb + OFF_VONES - 256, 128, 256, 0);
        constexpr uint64_t VSTEP = ((uint64_t)16 << 32) - 16;
        mbar_wait(bar(B_KV + 0), 0);
        if ((threadIdx.x & 127) == 0 && w == 0) TSTAMP(2);
        const float kmax2 = ldsf(sb + OFF_MISC);
        const float vscale = ldsf(sb + OFF_MISC + 4);
#pragma unroll 1
        for (int hh = 0; hh < 2; hh++) {
            uint32_t a[4];
#pragma unroll
            for (int i = 0; i < 4; i++) a[i] = hh ? qa[1][i] : qa[0][i];
            const float nmax = hh ? fmaxf(qn[1][0], qn[1][1]) : fmaxf(qn[0][0], qn[0][1]);
            const bool fast = named_bar_and(1 + w, 128, nmax * kmax2 <= 193.0f);
            float S[32], O[12];
#pragma unroll
            for (int i = 0; i < 12; i++) O[i] = 0.f;
#pragma unroll
            for (int i = 0; i < 32; i++) S[i] = 0.f;
            fence_regs<12>(O); fence_regs<32>(S);
            wg_fence();
            wg_qk_n64(S, a, kdesc0);
            wg_commit();
            wg_wait<0>();
            uint64_t kd = kdesc0 + 128, vd = vdesc0;
            if (fast) {
                uint32_t P[16];
#pragma unroll 1
                for (int c = 0; c < 8; c++) {
                    if (c < 7) mbar_wait(bar(B_KV + c + 1), 0);
#pragma unroll 1
                    for (int j = 0; j < 4; j++) {
                        fence_regs<32>(S);
                        softmax_fast(S, P, mlo);
                        fence_regs<32>(S);
                        wg_fence();
                        wg_qk_n64(S, a, kd);
#pragma unroll
                        for (int i = 0; i < 4; i++) wg_pv_n24(O, &P[4 * i], vd + i * VSTEP);
                        wg_commit();
                        wg_wait<0>();
                        kd += 128; vd += 4 * VSTEP;
                    }
                }
            } else {
                uint32_t P[16];
                float m0 = -INFINITY, m1 = -INFINITY;
#pragma unroll 1
                for (int c = 0; c < 8; c++) {
                    if (c < 7) mbar_wait(bar(B_KV + c + 1), 0);
#pragma unroll 1
                    for (int j = 0; j < 4; j++) {
                        fence_regs<32>(S); fence_regs<12>(O);
                        float x0 = m0, x1 = m1;
#pragma unroll
                        for (int i = 0; i < 8; i++) {
                            x0 = fmaxf(x0, fmaxf(S[4 * i], S[4 * i + 1]));
                            x1 = fmaxf(x1, fmaxf(S[4 * i + 2], S[4 * i + 3]));
                        }
                        x0 = fmaxf(x0, __shfl_xor_sync(0xffffffffu, x0, 1)); x0 = fmaxf(x0, __shfl_xor_sync(0xffffffffu, x0, 2));
                        x1 = fmaxf(x1, __shfl_xor_sync(0xffffffffu, x1, 1)); x1 = fmaxf(x1, __shfl_xor_sync(0xffffffffu, x1, 2));
                        const float r0 = ex2f(m0 - x0), r1 = ex2f(m1 - x1);
                        m0 = x0; m1 = x1;
#pragma unroll
                        for (int i = 0; i < 3; i++) { O[4 * i] *= r0; O[4 * i + 1] *= r0; O[4 * i + 2] *= r1; O[4 * i + 3] *= r1; }
#pragma unroll
                        for (int i = 0; i < 8; i++) {
                            P[2 * i] = pack_f16(ex2f(S[4 * i] - m0), ex2f(S[4 * i + 1] - m0));
                            P[2 * i + 1] = pack_f16(ex2f(S[4 * i + 2] - m1), ex2f(S[4 * i + 3] - m1));
                        }
                        fence_regs<32>(S); fence_regs<12>(O);
                        wg_fence();
                        wg_qk_n64(S, a, kd);
#pragma unroll
                        for (int i = 0; i < 4; i++) wg_pv_n24(O, &P[4 * i], vd + i * VSTEP);
                        wg_commit();
                        wg_wait<0>();
                        kd += 128; vd += 4 * VSTEP;
                    }
                }
            }
            fence_regs<12>(O);
            const float i0 = __fdividef(vscale, O[4]), i1 = __fdividef(vscale, O[6]);
            const int row = pb * 64 + wq * 16 + g;
            uint32_t* o0 = (uint32_t*)(g_o + (size_t)row * 512 + (hg * 8 + 2 * w + hh) * 16) + t;
            uint32_t* o1 = o0 + 8 * 256;
            o0[0] = pack_bf16(O[0] * i0, O[1] * i0);
            o0[4] = pack_bf16(O[8] * i0, O[9] * i0);
            o1[0] = pack_bf16(O[2] * i1, O[3] * i1);
            o1[4] = pack_bf16(O[10] * i1, O[11] * i1);
            if ((threadIdx.x & 127) == 0 && w == 0) TSTAMP(3 + hh);
        }
        __threadfence();
        fence_async_all();
        named_bar(1 + w, 128);
        if ((threadIdx.x & 127) == 0) {
            red_release_add(&g_o_count[pb], 1);
            mbar_arrive(bar(B_ATT));
        }
        if (threadIdx.x == 0) {
            mbar_wait(bar(B_ATT), 0);
            for (int j = 4; j < 8; j++) {
                mbar_expect_tx(bar(B_WO + j), 16384);
                tma2d(sb + OFF_K + (j - 4) * 16384, &tm_wo, hg * 128, 64 * j, bar(B_WO + j));
                tma2d(sb + OFF_K + (j - 4) * 16384 + 8192, &tm_wo, hg * 128 + 64, 64 * j, bar(B_WO + j));
            }
            poll_counter(&g_o_count[pb], 16);
            TSTAMP(18);
            fence_async_all();
            for (int j = 0; j < 8; j++) {
                mbar_expect_tx(bar(B_O + j), 8192);
                tma2d(sb + OFF_V + j * 8192, &tm_o, 64 * j, pb * 64, bar(B_O + j));
            }
            __threadfence();
            if (atomicAdd(&g_done, 1) == NCTA - 1) {
                g_kv_count = 0;
                for (int i = 0; i < 32; i++) g_o_count[i] = 0;
                g_done = 0;
                __threadfence();
            }
        }
        __syncwarp();
#pragma unroll
        for (int i = 0; i < 16; i++) acc[i] = 0.f;
        fence_regs<16>(acc);
#pragma unroll 1
        for (int j = 0; j < 8; j++) {
            mbar_wait(bar(B_WO + j), 0);
            mbar_wait(bar(B_O + j), 0);
            wg_fence();
            gemm_chunk(acc, sb + OFF_V + j * 8192, sb + (j < 4 ? OFF_X + j * 16384 : OFF_K + (j - 4) * 16384) + bcol);
            wg_commit();
        }
        wg_wait<0>();
        fence_regs<16>(acc);
        {
            const int row = pb * 64 + wq * 16 + g;
            uint32_t* d0 = (uint32_t*)(prm.out + (size_t)row * 1024 + 512 + hg * 128 + w * 32) + t;
            uint32_t* d1 = d0 + 8 * 512;
#pragma unroll
            for (int i = 0; i < 4; i++) {
                d0[4 * i] = pack_bf16(acc[4 * i], acc[4 * i + 1]);
                d1[4 * i] = pack_bf16(acc[4 * i + 2], acc[4 * i + 3]);
            }
        }
        if ((threadIdx.x & 127) == 0 && w == 0) TSTAMP(5);
    } else {
        const int wa = warp_id - 16, tau = threadIdx.x - 512;
        if (threadIdx.x == 512) {
            mbar_expect_tx(bar(B_WKV), 32768);
            tma2d(sb + OFF_C, &tm_wk, 0, 0, bar(B_WKV));
            tma2d(sb + OFF_C + 8192, &tm_wk, 0, 256, bar(B_WKV));
            tma2d(sb + OFF_C + 16384, &tm_wv, 0, 0, bar(B_WKV));
            tma2d(sb + OFF_C + 24576, &tm_wv, 0, 256, bar(B_WKV));
            mbar_expect_tx(bar(B_X16), 16384);
            for (int j = 0; j < 8; j++) tma2d(sb + OFF_X + j * 8192 + hg * 2048, &tm_x, 64 * j, pb * 64 + hg * 16, bar(B_X16));
            for (int j = 0; j < 8; j++) {
                mbar_expect_tx(bar(B_Q + j), 3 * 2048 + 16384);
                for (int r = 1; r < 4; r++) {
                    const int rg = (hg + r) & 3;
                    tma2d(sb + OFF_X + j * 8192 + rg * 2048, &tm_x, 64 * j, pb * 64 + rg * 16, bar(B_Q + j));
                }
                if (j < 4) {
                    tma2d(sb + OFF_V + j * 16384, &tm_wq, hg * 128, 64 * j, bar(B_Q + j));
                    tma2d(sb + OFF_V + j * 16384 + 8192, &tm_wq, hg * 128 + 64, 64 * j, bar(B_Q + j));
                }
            }
        }
        __syncwarp();
        {
            float acc[16];
#pragma unroll
            for (int i = 0; i < 16; i++) acc[i] = 0.f;
            fence_regs<16>(acc);
            mbar_wait(bar(B_WKV), 0);
            mbar_wait(bar(B_X16), 0);
            wg_fence();
#pragma unroll
            for (int j = 0; j < 8; j++) {
                const uint64_t da = make_desc(sb + OFF_X + j * 8192, 16, 1024, 1);
                const uint64_t db = make_desc(sb + OFF_C + j * 2048, 16384, 256, 3);
#pragma unroll
                for (int ks = 0; ks < 4; ks++) wg_ss_n32_tb(acc, da + ks * 2, db + ks * 32);
            }
            wg_commit();
            wg_wait<0>();
            fence_regs<16>(acc);
            if (wa == hg) {
                uint32_t kk[4], vv[4];
#pragma unroll
                for (int i = 0; i < 4; i++) { kk[i] = pack_bf16(acc[2 * i], acc[2 * i + 1]); vv[i] = pack_bf16(acc[8 + 2 * i], acc[8 + 2 * i + 1]); }
                uint32_t* kp = (uint32_t*)(g_kimg + (8 * pb + 2 * hg) * 256 + g * 16 + 4 * t);
                kp[0] = kk[0]; kp[64] = kk[1]; kp[32] = kk[2]; kp[96] = kk[3];
                const int s = 4 * pb + hg;
                uint32_t* vlo = (uint32_t*)(g_vimg + (127 - s) * 256 + g * 16 + 4 * t);
                uint32_t* vhi = (uint32_t*)(g_vimg + 32768 + 256 + s * 256 + g * 16 + 4 * t);
                vlo[0] = pack_f16(bf_lo(vv[0]), bf_hi(vv[0])); vlo[32] = pack_f16(bf_lo(vv[1]), bf_hi(vv[1]));
                vhi[0] = pack_f16(bf_lo(vv[2]), bf_hi(vv[2])); vhi[32] = pack_f16(bf_lo(vv[3]), bf_hi(vv[3]));
                uint32_t* vr = (uint32_t*)(g_vraw + (size_t)(64 * pb + 16 * hg + g) * 16) + t;
                vr[0] = vv[0]; vr[64] = vv[1]; vr[4] = vv[2]; vr[68] = vv[3];
                float n0 = bf_lo(kk[0]) * bf_lo(kk[0]) + bf_hi(kk[0]) * bf_hi(kk[0]) + bf_lo(kk[2]) * bf_lo(kk[2]) + bf_hi(kk[2]) * bf_hi(kk[2]);
                float n1 = bf_lo(kk[1]) * bf_lo(kk[1]) + bf_hi(kk[1]) * bf_hi(kk[1]) + bf_lo(kk[3]) * bf_lo(kk[3]) + bf_hi(kk[3]) * bf_hi(kk[3]);
                n0 += __shfl_xor_sync(0xffffffffu, n0, 1); n0 += __shfl_xor_sync(0xffffffffu, n0, 2);
                n1 += __shfl_xor_sync(0xffffffffu, n1, 1); n1 += __shfl_xor_sync(0xffffffffu, n1, 2);
                float km = fmaxf(n0, n1), vm = 0.f;
#pragma unroll
                for (int i = 0; i < 4; i++) vm = fmaxf(vm, fmaxf(fabsf(bf_lo(vv[i])), fabsf(bf_hi(vv[i]))));
#pragma unroll
                for (int o = 4; o < 32; o <<= 1) km = fmaxf(km, __shfl_xor_sync(0xffffffffu, km, o));
#pragma unroll
                for (int o = 1; o < 32; o <<= 1) vm = fmaxf(vm, __shfl_xor_sync(0xffffffffu, vm, o));
                if (lane == 0) g_stats[b] = make_float2(km, vm);
                __threadfence();
                fence_async_all();
                __syncwarp();
                if (lane == 0) { red_release_add(&g_kv_count, 1); TSTAMP(8); }
            }
        }
        const int c0 = 4 * b;
        named_bar(5, 128);
        if (wa == 0) {
            if (lane == 0) {
                for (int j = 4; j < 8; j++) {
                    mbar_wait(bar(B_QEMPTY + j - 4), 0);
                    tma2d(sb + OFF_V + (j - 4) * 16384, &tm_wq, hg * 128, 64 * j, bar(B_Q + j));
                    tma2d(sb + OFF_V + (j - 4) * 16384 + 8192, &tm_wq, hg * 128 + 64, 64 * j, bar(B_Q + j));
                }
                poll_counter(&g_kv_count, NCTA);
                TSTAMP(16);
            }
            __syncwarp();
            float km = 0.f, vm = 0.f;
#pragma unroll
            for (int i = 0; i < 4; i++) { const float2 st = __ldcg(&g_stats[lane + 32 * i]); km = fmaxf(km, st.x); vm = fmaxf(vm, st.y); }
#pragma unroll
            for (int o = 1; o < 32; o <<= 1) { km = fmaxf(km, __shfl_xor_sync(0xffffffffu, km, o)); vm = fmaxf(vm, __shfl_xor_sync(0xffffffffu, vm, o)); }
            const bool vdirect = (vm <= 32768.f && vm >= 9.765625e-4f) || vm == 0.f;
            float vs = 1.f;
            if (!vdirect && vm < INFINITY) {
                int e = (int)((__float_as_uint(vm) >> 23) & 0xFF) - 127;
                e = max(-100, min(100, e));
                vs = __uint_as_float((uint32_t)(127 + e - 13) << 23);
            }
            if (lane == 0) {
                asm volatile("st.shared.f32 [%0], %1;" ::"r"(sb + OFF_MISC), "f"(km) : "memory");
                asm volatile("st.shared.f32 [%0], %1;" ::"r"(sb + OFF_MISC + 4), "f"(vs) : "memory");
                fence_async_all();
                for (int c = 0; c < 8; c++) {
                    mbar_expect_tx(bar(B_KV + c), vdirect ? 16384 : 8192);
                    bulk_g2s(sb + OFF_K + c * 8192, g_kimg + c * 8192, 8192, bar(B_KV + c));
                }
                mbar_wait(bar(B_QDONE), 0);
                TSTAMP(17);
            }
            __syncwarp();
            sts32(sb + OFF_VONES + lane * 8, 0x3C003C00u);
            sts32(sb + OFF_VONES + lane * 8 + 4, 0x3C003C00u);
            if (vdirect) {
                if (lane == 0) {
                    for (int c = 0; c < 8; c++) {
                        bulk_g2s(sb + OFF_V + (112 - 16 * c) * 256, g_vimg + (112 - 16 * c) * 256, 4096, bar(B_KV + c));
                        bulk_g2s(sb + OFF_VONES + 256 + c * 4096, g_vimg + 32768 + 256 + c * 4096, 4096, bar(B_KV + c));
                    }
                }
            } else {
                const float inv = 1.f / vs;
                for (int idx = lane; idx < S_LEN * 8; idx += 32) {
                    const int key = idx >> 3, dp = idx & 7;
                    const uint32_t v = __ldcg((const uint32_t*)g_vraw + idx);
                    const uint32_t h = pack_f16(bf_lo(v) * inv, bf_hi(v) * inv);
                    const int st = key >> 4, hf = (key >> 3) & 1;
                    const uint32_t base = (dp < 4) ? (OFF_V + (127 - st) * 256) : (OFF_VONES + 256 + st * 256);
                    sts32(sb + base + hf * 128 + (key & 7) * 16 + (dp & 3) * 4, h);
                }
            }
            fence_async_smem();
            __syncwarp();
            if (lane == 0) {
                mbar_arrive(bar(B_KV + 0));
                for (int j = 0; j < 4; j++) {
                    mbar_expect_tx(bar(B_WO + j), 16384);
                    tma2d(sb + OFF_X + j * 16384, &tm_wo, hg * 128, 64 * j, bar(B_WO + j));
                    tma2d(sb + OFF_X + j * 16384 + 8192, &tm_wo, hg * 128 + 64, 64 * j, bar(B_WO + j));
                }
            }
            __syncwarp();
        }
        if (tau == 32) {
            mbar_expect_tx(bar(B_H), 4096);
            tma2d(sb + C_H0 + 512, &tm_h, 0, c0 * 64, bar(B_H));
            mbar_expect_tx(bar(B_H + 1), 4096);
            tma2d(sb + C_H1 + 512, &tm_h, 0, (c0 + 1) * 64, bar(B_H + 1));
        }
        sts32(sb + C_H0 + tau * 4, 0u);
        sts32(sb + C_H1 + tau * 4, 0u);
        {
            uint32_t wA[4], wB[4];
            {
                const uint4 s0 = *(const uint4*)(prm.shift_k + c0 * 4);
                const uint4 s1 = *(const uint4*)(prm.shift_k + c0 * 4 + 8);
                wA[0] = __byte_perm(s0.x, s0.z, 0x5410); wA[1] = __byte_perm(s0.x, s0.z, 0x7632);
                wA[2] = __byte_perm(s0.y, s0.w, 0x5410); wA[3] = __byte_perm(s0.y, s0.w, 0x7632);
                wB[0] = __byte_perm(s1.x, s1.z, 0x5410); wB[1] = __byte_perm(s1.x, s1.z, 0x7632);
                wB[2] = __byte_perm(s1.y, s1.w, 0x5410); wB[3] = __byte_perm(s1.y, s1.w, 0x7632);
            }
            const int s0 = tau * 16;
            const uint2* kp = (const uint2*)(prm.ak + c0);
            const uint2* vp = (const uint2*)(prm.av + c0);
#pragma unroll
            for (int half = 0; half < 2; half++) {
                uint2 kr[11], vr[8];
#pragma unroll
                for (int i = 0; i < 11; i++) {
                    const int s = s0 + half * 8 + i - 3;
                    kr[i] = s >= 0 ? __ldg(kp + (size_t)s * 128) : make_uint2(0u, 0u);
                }
#pragma unroll
                for (int i = 0; i < 8; i++) vr[i] = __ldg(vp + (size_t)(s0 + half * 8 + i) * 128);
                uint32_t xa[8], xb[8];
#pragma unroll
                for (int i = 0; i < 8; i++) {
                    uint32_t ua = bmul2(kr[i].x, wA[3]), ub = bmul2(kr[i].y, wB[3]);
                    ua = badd2(ua, bmul2(kr[i + 1].x, wA[2])); ub = badd2(ub, bmul2(kr[i + 1].y, wB[2]));
                    ua = badd2(ua, bmul2(kr[i + 2].x, wA[1])); ub = badd2(ub, bmul2(kr[i + 2].y, wB[1]));
                    ua = badd2(ua, bmul2(kr[i + 3].x, wA[0])); ub = badd2(ub, bmul2(kr[i + 3].y, wB[0]));
                    xa[i] = bmul2(ua, vr[i].x); xb[i] = bmul2(ub, vr[i].y);
                }
                const uint32_t dst = sb + C_KVC + (s0 + half * 8) * 2;
                sts128(dst,        __byte_perm(xa[0], xa[1], 0x5410), __byte_perm(xa[2], xa[3], 0x5410), __byte_perm(xa[4], xa[5], 0x5410), __byte_perm(xa[6], xa[7], 0x5410));
                sts128(dst + 4096, __byte_perm(xa[0], xa[1], 0x7632), __byte_perm(xa[2], xa[3], 0x7632), __byte_perm(xa[4], xa[5], 0x7632), __byte_perm(xa[6], xa[7], 0x7632));
                sts128(dst + 8192, __byte_perm(xb[0], xb[1], 0x5410), __byte_perm(xb[2], xb[3], 0x5410), __byte_perm(xb[4], xb[5], 0x5410), __byte_perm(xb[6], xb[7], 0x5410));
                sts128(dst + 12288, __byte_perm(xb[0], xb[1], 0x7632), __byte_perm(xb[2], xb[3], 0x7632), __byte_perm(xb[4], xb[5], 0x7632), __byte_perm(xb[6], xb[7], 0x7632));
            }
        }
        fence_async_smem();
        named_bar(5, 128);
        if (tau == 0) TSTAMP(9);
#pragma unroll 1
        for (int ch = 0; ch < 4; ch++) {
            {
                const uint32_t src = sb + C_KVC + ch * 4096 + tau * 32;
                const uint4 u0 = lds128(src), u1 = lds128(src + 16);
                const uint32_t prev = tau > 0 ? lds32(src - 4) : 0u;
                const uint32_t zd = sb + C_Z + (32 + tau * 16) * 4;
                sts128(zd,      __byte_perm(u0.x, prev, 0x7610), __byte_perm(u0.x, u0.x, 0x1032), __byte_perm(u0.y, u0.x, 0x7610), __byte_perm(u0.y, u0.y, 0x1032));
                sts128(zd + 16, __byte_perm(u0.z, u0.y, 0x7610), __byte_perm(u0.z, u0.z, 0x1032), __byte_perm(u0.w, u0.z, 0x7610), __byte_perm(u0.w, u0.w, 0x1032));
                sts128(zd + 32, __byte_perm(u1.x, u0.w, 0x7610), __byte_perm(u1.x, u1.x, 0x1032), __byte_perm(u1.y, u1.x, 0x7610), __byte_perm(u1.y, u1.y, 0x1032));
                sts128(zd + 48, __byte_perm(u1.z, u1.y, 0x7610), __byte_perm(u1.z, u1.z, 0x1032), __byte_perm(u1.w, u1.z, 0x7610), __byte_perm(u1.w, u1.w, 0x1032));
                if (tau < 32) sts32(sb + C_Z + tau * 4, 0u);
            }
            named_bar(5, 128);
            mbar_wait(bar(B_H + (ch & 1)), (ch >> 1) & 1);
            float D[32];
#pragma unroll
            for (int i = 0; i < 32; i++) D[i] = 0.f;
            fence_regs<32>(D);
            const uint32_t z0 = sb + C_Z + (32 + 32 * (wa >> 1) + 16 * (wa & 1) + g - 2 * t) * 4;
            const uint64_t hd = make_desc(sb + ((ch & 1) ? C_H1 : C_H0) + 512, 16, 512, 2);
            conv_group<64>(D, z0 + 0 * 1024, hd);
            conv_group<56>(D, z0 + 1 * 1024, hd);
            conv_group<48>(D, z0 + 2 * 1024, hd);
            conv_group<40>(D, z0 + 3 * 1024, hd);
            conv_group<32>(D, z0 + 4 * 1024, hd);
            conv_group<24>(D, z0 + 5 * 1024, hd);
            conv_group<16>(D, z0 + 6 * 1024, hd);
            conv_group<8>(D, z0 + 7 * 1024, hd);
            if (tau == 0 && ch < 2) {
                mbar_expect_tx(bar(B_H + (ch & 1)), 4096);
                tma2d(sb + ((ch & 1) ? C_H1 : C_H0) + 512, &tm_h, 0, (c0 + ch + 2) * 64, bar(B_H + (ch & 1)));
            }
            if (wa >= 2) {
#pragma unroll
                for (int jn = 0; jn < 8; jn++) {
#pragma unroll
                    for (int r = 0; r < 2; r++) {
                        const int bb = 16 * (wa & 1) + g + 8 * r;
                        const int n = 8 * jn + 2 * t;
                        sts64f(sb + C_Z + (bb * 64 + (n ^ ((bb & 3) << 3))) * 4, D[4 * jn + 2 * r], D[4 * jn + 2 * r + 1]);
                    }
                }
            }
            named_bar(5, 128);
            if (wa < 2) {
                const float dsc = __bfloat162float(prm.ssm_D[c0 + ch]);
#pragma unroll
                for (int jn = 0; jn < 8; jn++) {
#pragma unroll
                    for (int r = 0; r < 2; r++) {
                        const int bb = 16 * wa + g + 8 * r;
#pragma unroll
                        for (int e = 0; e < 2; e++) {
                            const int m = 8 * jn + 2 * t + e;
                            float y = D[4 * jn + 2 * r + e];
                            if (m > 0) y += ldsf(sb + C_Z + (bb * 64 + ((m - 1) ^ ((bb & 3) << 3))) * 4);
                            const uint32_t addr = sb + C_KVC + ch * 4096 + (32 * m + bb) * 2;
                            const float kv = __uint_as_float(lds16(addr) << 16);
                            const float yb = __bfloat162float(__float2bfloat16_rn(y));
                            const float kd = __bfloat162float(__float2bfloat16_rn(kv * dsc));
                            sts16(addr, (uint32_t)__bfloat16_as_ushort(__float2bfloat16_rn(yb + kd)));
                        }
                    }
                }
            }
            named_bar(5, 128);
            if (tau == 0) TSTAMP(10 + ch);
        }
        {
            const int s0 = tau * 16;
            const uint2* qp = (const uint2*)(prm.aq + c0);
            uint2* op = (uint2*)(prm.out + c0);
#pragma unroll
            for (int half = 0; half < 2; half++) {
                uint2 qr[8];
#pragma unroll
                for (int i = 0; i < 8; i++) qr[i] = __ldg(qp + (size_t)(s0 + half * 8 + i) * 128);
                const uint32_t src = sb + C_KVC + (s0 + half * 8) * 2;
                const uint4 z0 = lds128(src), z1 = lds128(src + 4096), z2 = lds128(src + 8192), z3 = lds128(src + 12288);
                const uint32_t a0[4] = {z0.x, z0.y, z0.z, z0.w}, a1[4] = {z1.x, z1.y, z1.z, z1.w};
                const uint32_t a2[4] = {z2.x, z2.y, z2.z, z2.w}, a3[4] = {z3.x, z3.y, z3.z, z3.w};
#pragma unroll
                for (int i = 0; i < 4; i++) {
                    const uint32_t e01 = __byte_perm(a0[i], a1[i], 0x5410), o01 = __byte_perm(a0[i], a1[i], 0x7632);
                    const uint32_t e23 = __byte_perm(a2[i], a3[i], 0x5410), o23 = __byte_perm(a2[i], a3[i], 0x7632);
                    op[(size_t)(s0 + half * 8 + 2 * i) * 256] = make_uint2(bmul2(qr[2 * i].x, e01), bmul2(qr[2 * i].y, e23));
                    op[(size_t)(s0 + half * 8 + 2 * i + 1) * 256] = make_uint2(bmul2(qr[2 * i + 1].x, o01), bmul2(qr[2 * i + 1].y, o23));
                }
            }
        }
        if (tau == 0) TSTAMP(14);
    }
}

typedef CUresult (*EncodeFn)(CUtensorMap*, CUtensorMapDataType, cuuint32_t, void*, const cuuint64_t*, const cuuint64_t*,
                             const cuuint32_t*, const cuuint32_t*, CUtensorMapInterleave, CUtensorMapSwizzle,
                             CUtensorMapL2promotion, CUtensorMapFloatOOBfill);

void make_map(EncodeFn fn, CUtensorMap* tm, const void* ptr, uint64_t cols, uint64_t rows, uint32_t bcols, uint32_t brows, CUtensorMapSwizzle swz) {
    cuuint64_t dims[2] = {cols, rows};
    cuuint64_t strides[1] = {cols * 2};
    cuuint32_t box[2] = {bcols, brows};
    cuuint32_t es[2] = {1, 1};
    fn(tm, CU_TENSOR_MAP_DATA_TYPE_BFLOAT16, 2, const_cast<void*>(ptr), dims, strides, box, es, CU_TENSOR_MAP_INTERLEAVE_NONE, swz,
       CU_TENSOR_MAP_L2_PROMOTION_L2_128B, CU_TENSOR_MAP_FLOAT_OOB_FILL_NONE);
}

}

extern "C" void kernel_launch(void* const* d_in, const int* in_sizes, int n_in, void* d_out, int out_size) {
    (void)in_sizes; (void)n_in; (void)out_size;
    static EncodeFn encode = nullptr;
    static void* o_ptr = nullptr;
    if (!encode) {
        cudaDriverEntryPointQueryResult qres;
        void* fn = nullptr;
        cudaGetDriverEntryPoint("cuTensorMapEncodeTiled", &fn, cudaEnableDefault, &qres);
        encode = (EncodeFn)fn;
        cudaGetSymbolAddress(&o_ptr, g_o);
        cudaFuncSetAttribute(fused_kernel, cudaFuncAttributeMaxDynamicSharedMemorySize, SMEM_TOTAL);
    }
    CUtensorMap tm_x, tm_wq, tm_wo, tm_wk, tm_wv, tm_o, tm_h;
    make_map(encode, &tm_x, d_in[6], 512, 2048, 64, 16, CU_TENSOR_MAP_SWIZZLE_128B);
    make_map(encode, &tm_wq, d_in[7], 512, 512, 64, 64, CU_TENSOR_MAP_SWIZZLE_128B);
    make_map(encode, &tm_wk, d_in[8], 16, 512, 16, 256, CU_TENSOR_MAP_SWIZZLE_32B);
    make_map(encode, &tm_wv, d_in[9], 16, 512, 16, 256, CU_TENSOR_MAP_SWIZZLE_32B);
    make_map(encode, &tm_wo, d_in[10], 512, 512, 64, 64, CU_TENSOR_MAP_SWIZZLE_128B);
    make_map(encode, &tm_o, o_ptr, 512, 2048, 64, 64, CU_TENSOR_MAP_SWIZZLE_128B);
    make_map(encode, &tm_h, d_in[4], 32, 512 * 64, 32, 64, CU_TENSOR_MAP_SWIZZLE_64B);
    Params prm;
    prm.aq = (const __nv_bfloat16*)d_in[0];
    prm.ak = (const __nv_bfloat16*)d_in[1];
    prm.av = (const __nv_bfloat16*)d_in[2];
    prm.shift_k = (const __nv_bfloat16*)d_in[3];
    prm.ssm_D = (const __nv_bfloat16*)d_in[5];
    prm.out = (__nv_bfloat16*)d_out;
    fused_kernel<<<NCTA, NTHREADS, SMEM_TOTAL>>>(tm_x, tm_wq, tm_wo, tm_wk, tm_wv, tm_o, tm_h, prm);
}
```

```cpp
#include <cuda_runtime.h>
#include <cuda_bf16.h>
#include <cuda_fp16.h>
#include <cuda.h>
#include <stdint.h>

namespace {

constexpr int S_LEN = 2048;
constexpr int NCTA = 128;
constexpr int NTHREADS = 640;

constexpr uint32_t OFF_K = 0;
constexpr uint32_t OFF_V = 65536;
constexpr uint32_t OFF_VONES = OFF_V + 32768;
constexpr uint32_t OFF_X = 132096;
constexpr uint32_t OFF_C = 197632;
constexpr uint32_t C_KVC = OFF_C;
constexpr uint32_t C_H = OFF_C + 16384;
constexpr uint32_t C_Z = C_H + 5120;
constexpr uint32_t OFF_BAR = 231936;
constexpr uint32_t SMEM_TOTAL = 232448;

enum { B_WKV = 0, B_Q = 1, B_QEMPTY = 5, B_QDONE = 7, B_KV = 8, B_WO = 16, B_O = 20, B_ATT = 24, B_H = 25, B_CV = 26, B_COUNT = 27 };
constexpr uint32_t OFF_MISC = OFF_BAR + 8 * B_COUNT;

__device__ __align__(1024) uint8_t g_kimg[65536];
__device__ __align__(1024) uint8_t g_vimg[65792];
__device__ __align__(1024) __nv_bfloat16 g_vraw[S_LEN * 16];
__device__ __align__(1024) __nv_bfloat16 g_o[S_LEN * 512];
__device__ __align__(1024) __nv_bfloat16 g_kvT[512 * S_LEN];
__device__ __align__(1024) __nv_bfloat16 g_zT[512 * S_LEN];
__device__ float2 g_stats[NCTA];
__device__ unsigned int g_kv_count;
__device__ unsigned int g_kvt_count[4];
__device__ unsigned int g_z_count[4];
__device__ unsigned int g_o_count[32];
__device__ unsigned int g_done;
#define TSTAMP(i) do {} while (0)

__device__ __forceinline__ void wg_fence() { asm volatile("wgmma.fence.sync.aligned;" ::: "memory"); }
__device__ __forceinline__ void wg_commit() { asm volatile("wgmma.commit_group.sync.aligned;" ::: "memory"); }
template <int N> __device__ __forceinline__ void wg_wait() { asm volatile("wgmma.wait_group.sync.aligned %0;" ::"n"(N) : "memory"); }
template <int N> __device__ __forceinline__ void fence_regs(float* r) {
#pragma unroll
    for (int i = 0; i < N; i++) asm volatile("" : "+f"(r[i])::"memory");
}
template <int N> __device__ __forceinline__ void fence_uregs(uint32_t* r) {
#pragma unroll
    for (int i = 0; i < N; i++) asm volatile("" : "+r"(r[i])::"memory");
}
__device__ __forceinline__ uint64_t make_desc(uint32_t saddr, uint32_t lbo, uint32_t sbo, uint32_t swz) {
    return (uint64_t)((saddr & 0x3FFFF) >> 4) | ((uint64_t)(lbo >> 4) << 16) | ((uint64_t)(sbo >> 4) << 32) | ((uint64_t)swz << 62);
}
__device__ __forceinline__ void mbar_init(uint32_t bar, uint32_t count) {
    asm volatile("mbarrier.init.shared::cta.b64 [%0], %1;" ::"r"(bar), "r"(count) : "memory");
}
__device__ __forceinline__ void mbar_expect_tx(uint32_t bar, uint32_t bytes) {
    asm volatile("mbarrier.arrive.expect_tx.shared::cta.b64 _, [%0], %1;" ::"r"(bar), "r"(bytes) : "memory");
}
__device__ __forceinline__ void mbar_arrive(uint32_t bar) {
    asm volatile("mbarrier.arrive.shared::cta.b64 _, [%0];" ::"r"(bar) : "memory");
}
__device__ __forceinline__ bool mbar_try(uint32_t bar, uint32_t parity) {
    uint32_t ok;
    asm volatile("{\n.reg .pred p;\nmbarrier.try_wait.parity.shared::cta.b64 p, [%1], %2;\nselp.u32 %0, 1, 0, p;\n}\n"
                 : "=r"(ok) : "r"(bar), "r"(parity) : "memory");
    return ok != 0;
}
__device__ __forceinline__ void mbar_wait(uint32_t bar, uint32_t parity) {
    uint32_t spins = 0;
    while (!mbar_try(bar, parity)) {
        if (++spins > (1u << 24)) __trap();
    }
}
__device__ __forceinline__ void tma2d(uint32_t dst, const CUtensorMap* tm, int c0, int c1, uint32_t bar) {
    asm volatile("cp.async.bulk.tensor.2d.shared::cluster.global.mbarrier::complete_tx::bytes [%0], [%1, {%3, %4}], [%2];"
                 ::"r"(dst), "l"((uint64_t)tm), "r"(bar), "r"(c0), "r"(c1) : "memory");
}
__device__ __forceinline__ void tma3d(uint32_t dst, const CUtensorMap* tm, int c0, int c1, int c2, uint32_t bar) {
    asm volatile("cp.async.bulk.tensor.3d.shared::cluster.global.mbarrier::complete_tx::bytes [%0], [%1, {%3, %4, %5}], [%2];"
                 ::"r"(dst), "l"((uint64_t)tm), "r"(bar), "r"(c0), "r"(c1), "r"(c2) : "memory");
}
__device__ __forceinline__ void tma4d(uint32_t dst, const CUtensorMap* tm, int c0, int c1, int c2, int c3, uint32_t bar) {
    asm volatile("cp.async.bulk.tensor.4d.shared::cluster.global.mbarrier::complete_tx::bytes [%0], [%1, {%3, %4, %5, %6}], [%2];"
                 ::"r"(dst), "l"((uint64_t)tm), "r"(bar), "r"(c0), "r"(c1), "r"(c2), "r"(c3) : "memory");
}
__device__ __forceinline__ void prefetch_tm(const CUtensorMap* tm) { asm volatile("prefetch.tensormap [%0];" ::"l"((uint64_t)tm) : "memory"); }
__device__ __forceinline__ void bulk_s2g(void* dst, uint32_t src, uint32_t bytes) {
    asm volatile("cp.async.bulk.global.shared::cta.bulk_group [%0], [%1], %2;" ::"l"(dst), "r"(src), "r"(bytes) : "memory");
}
__device__ __forceinline__ void bulk_commit() { asm volatile("cp.async.bulk.commit_group;" ::: "memory"); }
__device__ __forceinline__ void bulk_wait_all() { asm volatile("cp.async.bulk.wait_group 0;" ::: "memory"); }
__device__ __forceinline__ void fence_async_global() { asm volatile("fence.proxy.async.global;" ::: "memory"); }
__device__ __forceinline__ void bulk_g2s(uint32_t dst, const void* src, uint32_t bytes, uint32_t bar) {
    asm volatile("cp.async.bulk.shared::cluster.global.mbarrier::complete_tx::bytes [%0], [%1], %2, [%3];"
                 ::"r"(dst), "l"(src), "r"(bytes), "r"(bar) : "memory");
}
__device__ __forceinline__ void fence_async_smem() { asm volatile("fence.proxy.async.shared::cta;" ::: "memory"); }
__device__ __forceinline__ void named_bar(int id, int n) { asm volatile("bar.sync %0, %1;" ::"r"(id), "r"(n) : "memory"); }
__device__ __forceinline__ bool named_bar_and(int id, int n, bool pred) {
    uint32_t r;
    asm volatile("{\n.reg .pred p, q;\nsetp.ne.u32 p, %3, 0;\nbarrier.cta.red.and.pred q, %1, %2, p;\nselp.u32 %0, 1, 0, q;\n}\n"
                 : "=r"(r) : "r"(id), "r"(n), "r"((uint32_t)pred) : "memory");
    return r != 0;
}
__device__ __forceinline__ unsigned int ld_acquire(const unsigned int* p) {
    unsigned int v;
    asm volatile("ld.acquire.gpu.global.u32 %0, [%1];" : "=r"(v) : "l"(p) : "memory");
    return v;
}
__device__ __forceinline__ void red_release_add(unsigned int* p, unsigned int v) {
    asm volatile("red.release.gpu.global.add.u32 [%0], %1;" ::"l"(p), "r"(v) : "memory");
}
__device__ __forceinline__ void poll_counter(const unsigned int* p, unsigned int target) {
    uint32_t spins = 0;
    while (ld_acquire(p) < target) {
        if (++spins > (1u << 22)) __trap();
    }
}
__device__ __forceinline__ float ex2f(float x) { float y; asm("ex2.approx.ftz.f32 %0, %1;" : "=f"(y) : "f"(x)); return y; }
__device__ __forceinline__ uint32_t pack_f16(float lo, float hi) { uint32_t r; asm("cvt.rn.f16x2.f32 %0, %1, %2;" : "=r"(r) : "f"(hi), "f"(lo)); return r; }
__device__ __forceinline__ uint32_t pack_bf16(float lo, float hi) { uint32_t r; asm("cvt.rn.bf16x2.f32 %0, %1, %2;" : "=r"(r) : "f"(hi), "f"(lo)); return r; }
__device__ __forceinline__ float bf_lo(uint32_t v) { return __uint_as_float(v << 16); }
__device__ __forceinline__ float bf_hi(uint32_t v) { return __uint_as_float(v & 0xFFFF0000u); }
__device__ __forceinline__ uint32_t hfma2(uint32_t a, uint32_t b, uint32_t c) { uint32_t r; asm("fma.rn.f16x2 %0, %1, %2, %3;" : "=r"(r) : "r"(a), "r"(b), "r"(c)); return r; }
__device__ __forceinline__ uint32_t bmul2(uint32_t a, uint32_t b) { uint32_t r; asm("mul.rn.bf16x2 %0, %1, %2;" : "=r"(r) : "r"(a), "r"(b)); return r; }
__device__ __forceinline__ uint32_t badd2(uint32_t a, uint32_t b) { uint32_t r; asm("add.rn.bf16x2 %0, %1, %2;" : "=r"(r) : "r"(a), "r"(b)); return r; }
template <int LUT> __device__ __forceinline__ uint32_t lop3(uint32_t a, uint32_t b, uint32_t c) {
    uint32_t r; asm("lop3.b32 %0, %1, %2, %3, %4;" : "=r"(r) : "r"(a), "r"(b), "r"(c), "n"(LUT)); return r;
}
__device__ __forceinline__ uint32_t lds32(uint32_t a) { uint32_t v; asm volatile("ld.shared.u32 %0, [%1];" : "=r"(v) : "r"(a)); return v; }
__device__ __forceinline__ float ldsf(uint32_t a) { float v; asm volatile("ld.shared.f32 %0, [%1];" : "=f"(v) : "r"(a)); return v; }
__device__ __forceinline__ uint32_t lds16(uint32_t a) { uint16_t v; asm volatile("ld.shared.u16 %0, [%1];" : "=h"(v) : "r"(a)); return v; }
__device__ __forceinline__ uint4 lds128(uint32_t a) { uint4 v; asm volatile("ld.shared.v4.u32 {%0,%1,%2,%3}, [%4];" : "=r"(v.x), "=r"(v.y), "=r"(v.z), "=r"(v.w) : "r"(a)); return v; }
__device__ __forceinline__ void sts32(uint32_t a, uint32_t v) { asm volatile("st.shared.u32 [%0], %1;" ::"r"(a), "r"(v) : "memory"); }
__device__ __forceinline__ void sts16(uint32_t a, uint32_t v) { asm volatile("st.shared.u16 [%0], %1;" ::"r"(a), "h"((uint16_t)v) : "memory"); }
__device__ __forceinline__ void sts64f(uint32_t a, float x, float y) { asm volatile("st.shared.v2.f32 [%0], {%1,%2};" ::"r"(a), "f"(x), "f"(y) : "memory"); }
__device__ __forceinline__ void sts128(uint32_t a, uint32_t x, uint32_t y, uint32_t z, uint32_t w) {
    asm volatile("st.shared.v4.u32 [%0], {%1,%2,%3,%4};" ::"r"(a), "r"(x), "r"(y), "r"(z), "r"(w) : "memory");
}

__device__ __forceinline__ void wg_ss_n32_tb(float* d, uint64_t descA, uint64_t descB) {
    asm volatile("wgmma.mma_async.sync.aligned.m64n32k16.f32.bf16.bf16 {%0,%1,%2,%3,%4,%5,%6,%7,%8,%9,%10,%11,%12,%13,%14,%15}, %16, %17, 1, 1, 1, 0, 1;\n"
        : "+f"(d[0]), "+f"(d[1]), "+f"(d[2]), "+f"(d[3]), "+f"(d[4]), "+f"(d[5]), "+f"(d[6]), "+f"(d[7]), "+f"(d[8]), "+f"(d[9]), "+f"(d[10]), "+f"(d[11]), "+f"(d[12]), "+f"(d[13]), "+f"(d[14]), "+f"(d[15])
        : "l"(descA), "l"(descB));
}
__device__ __forceinline__ void wg_qk_n64(float* d, const uint32_t* a, uint64_t desc) {
    asm volatile("wgmma.mma_async.sync.aligned.m64n64k16.f32.bf16.bf16 {%0,%1,%2,%3,%4,%5,%6,%7,%8,%9,%10,%11,%12,%13,%14,%15,%16,%17,%18,%19,%20,%21,%22,%23,%24,%25,%26,%27,%28,%29,%30,%31}, {%32,%33,%34,%35}, %36, 0, 1, 1, 0;\n"
        : "+f"(d[0]), "+f"(d[1]), "+f"(d[2]), "+f"(d[3]), "+f"(d[4]), "+f"(d[5]), "+f"(d[6]), "+f"(d[7]), "+f"(d[8]), "+f"(d[9]), "+f"(d[10]), "+f"(d[11]), "+f"(d[12]), "+f"(d[13]), "+f"(d[14]), "+f"(d[15]), "+f"(d[16]), "+f"(d[17]), "+f"(d[18]), "+f"(d[19]), "+f"(d[20]), "+f"(d[21]), "+f"(d[22]), "+f"(d[23]), "+f"(d[24]), "+f"(d[25]), "+f"(d[26]), "+f"(d[27]), "+f"(d[28]), "+f"(d[29]), "+f"(d[30]), "+f"(d[31])
        : "r"(a[0]), "r"(a[1]), "r"(a[2]), "r"(a[3]), "l"(desc));
}
__device__ __forceinline__ void wg_pv_n24(float* d, const uint32_t* a, uint64_t desc) {
    asm volatile("wgmma.mma_async.sync.aligned.m64n24k16.f32.f16.f16 {%0,%1,%2,%3,%4,%5,%6,%7,%8,%9,%10,%11}, {%12,%13,%14,%15}, %16, 1, 1, 1, 1;\n"
        : "+f"(d[0]), "+f"(d[1]), "+f"(d[2]), "+f"(d[3]), "+f"(d[4]), "+f"(d[5]), "+f"(d[6]), "+f"(d[7]), "+f"(d[8]), "+f"(d[9]), "+f"(d[10]), "+f"(d[11])
        : "r"(a[0]), "r"(a[1]), "r"(a[2]), "r"(a[3]), "l"(desc));
}
__device__ __forceinline__ void wg_cv_n16(float* d, const uint32_t* a, uint64_t desc) {
    asm volatile("wgmma.mma_async.sync.aligned.m64n16k16.f32.bf16.bf16 {%0,%1,%2,%3,%4,%5,%6,%7}, {%8,%9,%10,%11}, %12, 1, 1, 1, 0;\n"
        : "+f"(d[0]), "+f"(d[1]), "+f"(d[2]), "+f"(d[3]), "+f"(d[4]), "+f"(d[5]), "+f"(d[6]), "+f"(d[7])
        : "r"(a[0]), "r"(a[1]), "r"(a[2]), "r"(a[3]), "l"(desc));
}
__device__ __forceinline__ void wg_cv_n32(float* d, const uint32_t* a, uint64_t desc) {
    asm volatile("wgmma.mma_async.sync.aligned.m64n32k16.f32.bf16.bf16 {%0,%1,%2,%3,%4,%5,%6,%7,%8,%9,%10,%11,%12,%13,%14,%15}, {%16,%17,%18,%19}, %20, 1, 1, 1, 0;\n"
        : "+f"(d[0]), "+f"(d[1]), "+f"(d[2]), "+f"(d[3]), "+f"(d[4]), "+f"(d[5]), "+f"(d[6]), "+f"(d[7]), "+f"(d[8]), "+f"(d[9]), "+f"(d[10]), "+f"(d[11]), "+f"(d[12]), "+f"(d[13]), "+f"(d[14]), "+f"(d[15])
        : "r"(a[0]), "r"(a[1]), "r"(a[2]), "r"(a[3]), "l"(desc));
}
__device__ __forceinline__ void wg_cv_n48(float* d, const uint32_t* a, uint64_t desc) {
    asm volatile("wgmma.mma_async.sync.aligned.m64n48k16.f32.bf16.bf16 {%0,%1,%2,%3,%4,%5,%6,%7,%8,%9,%10,%11,%12,%13,%14,%15,%16,%17,%18,%19,%20,%21,%22,%23}, {%24,%25,%26,%27}, %28, 1, 1, 1, 0;\n"
        : "+f"(d[0]), "+f"(d[1]), "+f"(d[2]), "+f"(d[3]), "+f"(d[4]), "+f"(d[5]), "+f"(d[6]), "+f"(d[7]), "+f"(d[8]), "+f"(d[9]), "+f"(d[10]), "+f"(d[11]), "+f"(d[12]), "+f"(d[13]), "+f"(d[14]), "+f"(d[15]), "+f"(d[16]), "+f"(d[17]), "+f"(d[18]), "+f"(d[19]), "+f"(d[20]), "+f"(d[21]), "+f"(d[22]), "+f"(d[23])
        : "r"(a[0]), "r"(a[1]), "r"(a[2]), "r"(a[3]), "l"(desc));
}
__device__ __forceinline__ void wg_cv_n64(float* d, const uint32_t* a, uint64_t desc) {
    asm volatile("wgmma.mma_async.sync.aligned.m64n64k16.f32.bf16.bf16 {%0,%1,%2,%3,%4,%5,%6,%7,%8,%9,%10,%11,%12,%13,%14,%15,%16,%17,%18,%19,%20,%21,%22,%23,%24,%25,%26,%27,%28,%29,%30,%31}, {%32,%33,%34,%35}, %36, 1, 1, 1, 0;\n"
        : "+f"(d[0]), "+f"(d[1]), "+f"(d[2]), "+f"(d[3]), "+f"(d[4]), "+f"(d[5]), "+f"(d[6]), "+f"(d[7]), "+f"(d[8]), "+f"(d[9]), "+f"(d[10]), "+f"(d[11]), "+f"(d[12]), "+f"(d[13]), "+f"(d[14]), "+f"(d[15]), "+f"(d[16]), "+f"(d[17]), "+f"(d[18]), "+f"(d[19]), "+f"(d[20]), "+f"(d[21]), "+f"(d[22]), "+f"(d[23]), "+f"(d[24]), "+f"(d[25]), "+f"(d[26]), "+f"(d[27]), "+f"(d[28]), "+f"(d[29]), "+f"(d[30]), "+f"(d[31])
        : "r"(a[0]), "r"(a[1]), "r"(a[2]), "r"(a[3]), "l"(desc));
}

template <int N> __device__ __forceinline__ void wg_cv(float* d, const uint32_t* a, uint64_t desc);
template <> __device__ __forceinline__ void wg_cv<16>(float* d, const uint32_t* a, uint64_t s) { wg_cv_n16(d, a, s); }
template <> __device__ __forceinline__ void wg_cv<32>(float* d, const uint32_t* a, uint64_t s) { wg_cv_n32(d, a, s); }
template <> __device__ __forceinline__ void wg_cv<48>(float* d, const uint32_t* a, uint64_t s) { wg_cv_n48(d, a, s); }
template <> __device__ __forceinline__ void wg_cv<64>(float* d, const uint32_t* a, uint64_t s) { wg_cv_n64(d, a, s); }

constexpr uint32_t POLYMASK = 0xB5B5u;
__device__ __forceinline__ void softmax_fast(const float* s, uint32_t* p, uint32_t mlo) {
    const uint32_t C3 = 0x2cfb2cfbu, C2 = 0x9fec9fecu, C1 = 0x37a837a8u, C0 = 0x37383738u;
#pragma unroll
    for (int i = 0; i < 16; i++) {
        const float s0 = s[2 * i], s1 = s[2 * i + 1];
        if ((POLYMASK >> i) & 1) {
            const float t0 = s0 + 12303.0f, t1 = s1 + 12303.0f;
            const uint32_t T = __byte_perm(__float_as_uint(t0), __float_as_uint(t1), 0x5410);
            const uint32_t U = lop3<0xEA>(T, mlo, 0x3C003C00u);
            uint32_t h = hfma2(U, C3, C2);
            h = hfma2(h, U, C1);
            h = hfma2(h, U, C0);
            p[i] = lop3<0xE4>(h, T, 0x03FF03FFu);
        } else {
            p[i] = pack_f16(ex2f(s0), ex2f(s1));
        }
    }
}

__device__ __forceinline__ void gemm_chunk(float* acc, uint32_t a_addr, uint32_t b_addr) {
    const uint64_t da = make_desc(a_addr, 16, 1024, 1);
    const uint64_t db = make_desc(b_addr, 8192, 1024, 1);
#pragma unroll
    for (int ks = 0; ks < 4; ks++) wg_ss_n32_tb(acc, da + ks * 2, db + ks * 128);
}

struct Params {
    const __nv_bfloat16 *aq, *ak, *av, *shift_k, *ssm_D;
    __nv_bfloat16* out;
};

template <int NQ>
__device__ __forceinline__ void conv_group(float* D, uint32_t zaddr, uint64_t hdesc) {
    float Dn[NQ / 2];
#pragma unroll
    for (int i = 0; i < NQ / 2; i++) asm volatile("mov.f32 %0, %1;" : "=f"(Dn[i]) : "f"(D[(64 - NQ) / 2 + i]));
    uint32_t a[2][16];
#pragma unroll
    for (int st = 0; st < 4; st++) {
        uint32_t* aa = a[st & 1];
        if (st >= 2) wg_wait<1>();
#pragma unroll
        for (int u = 0; u < 2; u++) {
            const uint32_t z = zaddr + (st * 2 + u) * 256;
            aa[8 * u + 0] = lds32(z);      aa[8 * u + 1] = lds32(z + 32); aa[8 * u + 2] = lds32(z - 32); aa[8 * u + 3] = lds32(z);
            aa[8 * u + 4] = lds32(z - 64); aa[8 * u + 5] = lds32(z - 32); aa[8 * u + 6] = lds32(z - 96); aa[8 * u + 7] = lds32(z - 64);
        }
        wg_fence();
#pragma unroll
        for (int u = 0; u < 2; u++) {
            const int qi = st * 2 + u;
            wg_cv<NQ>(Dn, &aa[8 * u], hdesc - qi * 8);
            wg_cv<NQ>(Dn, &aa[8 * u + 4], hdesc - qi * 8 + 2);
        }
        wg_commit();
    }
    wg_wait<0>();
    fence_regs<NQ / 2>(Dn);
#pragma unroll
    for (int i = 0; i < NQ / 2; i++) asm volatile("mov.f32 %0, %1;" : "=f"(D[(64 - NQ) / 2 + i]) : "f"(Dn[i]));
}

__global__ void __launch_bounds__(NTHREADS, 1)
fused_kernel(const __grid_constant__ CUtensorMap tm_x16, const __grid_constant__ CUtensorMap tm_x,
             const __grid_constant__ CUtensorMap tm_wq, const __grid_constant__ CUtensorMap tm_wo,
             const __grid_constant__ CUtensorMap tm_wk, const __grid_constant__ CUtensorMap tm_wv,
             const __grid_constant__ CUtensorMap tm_o, const __grid_constant__ CUtensorMap tm_h, const Params prm) {
    extern __shared__ __align__(1024) uint8_t smem_raw[];
    const uint32_t sb = (uint32_t)__cvta_generic_to_shared(smem_raw);
    const int warp_id = __shfl_sync(0xffffffffu, threadIdx.x >> 5, 0);
    const int lane = threadIdx.x & 31;
    const int g = lane >> 2, t = lane & 3;
    const int b = blockIdx.x, pb = b >> 2, hg = b & 3;
    auto bar = [&](int i) { return sb + OFF_BAR + 8 * i; };

    if (threadIdx.x == 512) {
        TSTAMP(0);
        prefetch_tm(&tm_wk); prefetch_tm(&tm_wv); prefetch_tm(&tm_x16); prefetch_tm(&tm_x); prefetch_tm(&tm_wq);
        mbar_init(bar(B_WKV), 1);
        for (int j = 0; j < 4; j++) { mbar_init(bar(B_Q + j), 1); mbar_init(bar(B_WO + j), 1); mbar_init(bar(B_O + j), 1); }
        for (int j = 0; j < 8; j++) mbar_init(bar(B_KV + j), j == 0 ? 2 : 1);
        mbar_init(bar(B_QEMPTY), 4); mbar_init(bar(B_QEMPTY + 1), 4);
        mbar_init(bar(B_QDONE), 4); mbar_init(bar(B_ATT), 4);
        mbar_init(bar(B_H), 1); mbar_init(bar(B_CV), 1);
        asm volatile("fence.mbarrier_init.release.cluster;" ::: "memory");
    }

    if (warp_id < 16) {
        const int w = warp_id >> 2, wq = warp_id & 3;
        {
            const int pr = lane & 7, cg = wq * 4 + (lane >> 3);
            const int p0 = pb * 64 + w * 16 + 2 * pr, ch0 = hg * 128 + cg * 8;
            uint4 kr[5], vr[2], sw[4];
#pragma unroll
            for (int i = 0; i < 5; i++) {
                const int s = p0 - 3 + i;
                kr[i] = s >= 0 ? __ldg((const uint4*)(prm.ak + (size_t)s * 512 + ch0)) : make_uint4(0u, 0u, 0u, 0u);
            }
#pragma unroll
            for (int i = 0; i < 2; i++) vr[i] = __ldg((const uint4*)(prm.av + (size_t)(p0 + i) * 512 + ch0));
#pragma unroll
            for (int i = 0; i < 4; i++) sw[i] = __ldg((const uint4*)(prm.shift_k + ch0 * 4) + i);
            __syncthreads();
            uint32_t x0[4], x1[4];
#pragma unroll
            for (int i = 0; i < 4; i++) {
                const uint32_t w0 = __byte_perm(sw[i].x, sw[i].z, 0x5410), w1 = __byte_perm(sw[i].x, sw[i].z, 0x7632);
                const uint32_t w2 = __byte_perm(sw[i].y, sw[i].w, 0x5410), w3 = __byte_perm(sw[i].y, sw[i].w, 0x7632);
                const uint32_t k0 = (&kr[0].x)[i], k1 = (&kr[1].x)[i], k2 = (&kr[2].x)[i], k3 = (&kr[3].x)[i], k4 = (&kr[4].x)[i];
                x0[i] = bmul2(badd2(badd2(badd2(bmul2(k0, w3), bmul2(k1, w2)), bmul2(k2, w1)), bmul2(k3, w0)), (&vr[0].x)[i]);
                x1[i] = bmul2(badd2(badd2(badd2(bmul2(k1, w3), bmul2(k2, w2)), bmul2(k3, w1)), bmul2(k4, w0)), (&vr[1].x)[i]);
            }
            uint32_t* dst = (uint32_t*)(g_kvT + (size_t)ch0 * S_LEN + p0);
#pragma unroll
            for (int i = 0; i < 4; i++) {
                dst[(2 * i) * (S_LEN / 2)] = __byte_perm(x0[i], x1[i], 0x5410);
                dst[(2 * i + 1) * (S_LEN / 2)] = __byte_perm(x0[i], x1[i], 0x7632);
            }
        }
        named_bar(6, 512);
        if (threadIdx.x == 0) { red_release_add(&g_kvt_count[hg], 1); TSTAMP(34); }
        float acc[16];
#pragma unroll
        for (int i = 0; i < 16; i++) acc[i] = 0.f;
        fence_regs<16>(acc);
        const uint32_t bcol = (w >> 1) * 8192 + (w & 1) * 64;
#pragma unroll 1
        for (int jj = 0; jj < 4; jj++) {
            mbar_wait(bar(B_Q + jj), 0);
            wg_fence();
            gemm_chunk(acc, sb + OFF_X + jj * 16384, sb + OFF_V + (jj & 1) * 32768 + bcol);
            gemm_chunk(acc, sb + OFF_X + jj * 16384 + 8192, sb + OFF_V + (jj & 1) * 32768 + 16384 + bcol);
            wg_commit();
            wg_wait<0>();
            if (jj < 2 && (threadIdx.x & 127) == 0) mbar_arrive(bar(B_QEMPTY + jj));
        }
        fence_regs<16>(acc);
        if ((threadIdx.x & 127) == 0) { mbar_arrive(bar(B_QDONE)); if (w == 0) TSTAMP(1); }
        uint32_t qa[2][4];
        float qn[2];
        {
            const float c = 0.25f * 1.4426950408889634f;
#pragma unroll
            for (int hh = 0; hh < 2; hh++) {
                float n0 = 0.f, n1 = 0.f;
#pragma unroll
                for (int i = 0; i < 4; i++) {
                    const uint32_t qb = pack_bf16(acc[8 * hh + 2 * i], acc[8 * hh + 2 * i + 1]);
                    const uint32_t qs = pack_bf16(bf_lo(qb) * c, bf_hi(qb) * c);
                    qa[hh][i] = qs;
                    const float e = bf_lo(qs) * bf_lo(qs) + bf_hi(qs) * bf_hi(qs);
                    if (i & 1) n1 += e; else n0 += e;
                }
                n0 += __shfl_xor_sync(0xffffffffu, n0, 1); n0 += __shfl_xor_sync(0xffffffffu, n0, 2);
                n1 += __shfl_xor_sync(0xffffffffu, n1, 1); n1 += __shfl_xor_sync(0xffffffffu, n1, 2);
                qn[hh] = fmaxf(n0, n1);
            }
        }
        uint32_t mlo = 0x03FF03FFu; asm volatile("" : "+r"(mlo));
        const uint64_t kdesc0 = make_desc(sb + OFF_K, 128, 256, 0);
        const uint64_t vdesc0 = make_desc(sb + OFF_VONES - 256, 128, 256, 0);
        constexpr uint64_t VSTEP = ((uint64_t)16 << 32) - 16;
        mbar_wait(bar(B_KV + 0), 0);
        if ((threadIdx.x & 127) == 0 && w == 0) TSTAMP(2);
        const float kmax2 = ldsf(sb + OFF_MISC);
        const bool fast0 = named_bar_and(1 + w, 128, qn[0] * kmax2 <= 193.0f);
        const bool fast1 = named_bar_and(1 + w, 128, qn[1] * kmax2 <= 193.0f);
        uint32_t a[4] = {qa[0][0], qa[0][1], qa[0][2], qa[0][3]};
#pragma unroll 1
        for (int hh = 0; hh < 2; hh++) {
            const bool fast = hh ? fast1 : fast0;
            float S[32], O[12];
#pragma unroll
            for (int i = 0; i < 12; i++) O[i] = 0.f;
#pragma unroll
            for (int i = 0; i < 32; i++) S[i] = 0.f;
            fence_regs<12>(O); fence_regs<32>(S);
            wg_fence();
            wg_qk_n64(S, a, kdesc0);
            wg_commit();
            wg_wait<0>();
            uint64_t kd = kdesc0 + 128, vd = vdesc0;
            if (fast) {
                uint32_t P[16];
#pragma unroll 1
                for (int c = 0; c < 8; c++) {
                    if (c < 7) mbar_wait(bar(B_KV + c + 1), 0);
#pragma unroll 1
                    for (int j = 0; j < 4; j++) {
                        fence_regs<32>(S);
                        softmax_fast(S, P, mlo);
                        fence_regs<32>(S);
                        wg_fence();
                        wg_qk_n64(S, a, kd);
#pragma unroll
                        for (int i = 0; i < 4; i++) wg_pv_n24(O, &P[4 * i], vd + i * VSTEP);
                        wg_commit();
                        wg_wait<0>();
                        kd += 128; vd += 4 * VSTEP;
                    }
                }
            } else {
                uint32_t P[16];
                float m0 = -INFINITY, m1 = -INFINITY;
#pragma unroll 1
                for (int c = 0; c < 8; c++) {
                    if (c < 7) mbar_wait(bar(B_KV + c + 1), 0);
#pragma unroll 1
                    for (int j = 0; j < 4; j++) {
                        fence_regs<32>(S); fence_regs<12>(O);
                        float x0 = m0, x1 = m1;
#pragma unroll
                        for (int i = 0; i < 8; i++) {
                            x0 = fmaxf(x0, fmaxf(S[4 * i], S[4 * i + 1]));
                            x1 = fmaxf(x1, fmaxf(S[4 * i + 2], S[4 * i + 3]));
                        }
                        x0 = fmaxf(x0, __shfl_xor_sync(0xffffffffu, x0, 1)); x0 = fmaxf(x0, __shfl_xor_sync(0xffffffffu, x0, 2));
                        x1 = fmaxf(x1, __shfl_xor_sync(0xffffffffu, x1, 1)); x1 = fmaxf(x1, __shfl_xor_sync(0xffffffffu, x1, 2));
                        const float r0 = ex2f(m0 - x0), r1 = ex2f(m1 - x1);
                        m0 = x0; m1 = x1;
#pragma unroll
                        for (int i = 0; i < 3; i++) { O[4 * i] *= r0; O[4 * i + 1] *= r0; O[4 * i + 2] *= r1; O[4 * i + 3] *= r1; }
#pragma unroll
                        for (int i = 0; i < 8; i++) {
                            P[2 * i] = pack_f16(ex2f(S[4 * i] - m0), ex2f(S[4 * i + 1] - m0));
                            P[2 * i + 1] = pack_f16(ex2f(S[4 * i + 2] - m1), ex2f(S[4 * i + 3] - m1));
                        }
                        fence_regs<32>(S); fence_regs<12>(O);
                        wg_fence();
                        wg_qk_n64(S, a, kd);
#pragma unroll
                        for (int i = 0; i < 4; i++) wg_pv_n24(O, &P[4 * i], vd + i * VSTEP);
                        wg_commit();
                        wg_wait<0>();
                        kd += 128; vd += 4 * VSTEP;
                    }
                }
            }
            fence_regs<12>(O);
            const float vscale = ldsf(sb + OFF_MISC + 4);
            const float i0 = __fdividef(vscale, O[4]), i1 = __fdividef(vscale, O[6]);
            const int row = pb * 64 + wq * 16 + g;
            uint32_t* o0 = (uint32_t*)(g_o + (size_t)row * 512 + (hg * 8 + 2 * w + hh) * 16) + t;
            uint32_t* o1 = o0 + 8 * 256;
            o0[0] = pack_bf16(O[0] * i0, O[1] * i0);
            o0[4] = pack_bf16(O[8] * i0, O[9] * i0);
            o1[0] = pack_bf16(O[2] * i1, O[3] * i1);
            o1[4] = pack_bf16(O[10] * i1, O[11] * i1);
            if ((threadIdx.x & 127) == 0 && w == 0) TSTAMP(3 + hh);
#pragma unroll
            for (int i = 0; i < 4; i++) a[i] = qa[1][i];
        }
        named_bar(1 + w, 128);
        if ((threadIdx.x & 127) == 0) {
            red_release_add(&g_o_count[pb], 1);
            mbar_arrive(bar(B_ATT));
        }
        if (threadIdx.x == 0) {
            TSTAMP(30);
            mbar_wait(bar(B_ATT), 0);
            TSTAMP(31);
            poll_counter(&g_o_count[pb], 16);
            TSTAMP(18);
            fence_async_global();
            for (int jj = 0; jj < 4; jj++) {
                mbar_expect_tx(bar(B_O + jj), 16384);
                tma3d(sb + OFF_V + jj * 16384, &tm_o, 0, pb * 64, 2 * jj, bar(B_O + jj));
            }
            __threadfence();
            if (atomicAdd(&g_done, 1) == 2 * NCTA - 1) {
                g_kv_count = 0;
                for (int i = 0; i < 4; i++) { g_kvt_count[i] = 0; g_z_count[i] = 0; }
                for (int i = 0; i < 32; i++) g_o_count[i] = 0;
                g_done = 0;
                __threadfence();
            }
        } else if (threadIdx.x == 128) {
            mbar_wait(bar(B_ATT), 0);
            for (int jj = 2; jj < 4; jj++) {
                mbar_expect_tx(bar(B_WO + jj), 32768);
                tma4d(sb + OFF_K + (jj - 2) * 32768, &tm_wo, 0, 0, hg * 2, 2 * jj, bar(B_WO + jj));
            }
        }
        __syncwarp();
#pragma unroll
        for (int i = 0; i < 16; i++) acc[i] = 0.f;
        fence_regs<16>(acc);
#pragma unroll 1
        for (int jj = 0; jj < 4; jj++) {
            mbar_wait(bar(B_WO + jj), 0);
            mbar_wait(bar(B_O + jj), 0);
            if (threadIdx.x == 0 && (jj == 0 || jj == 3)) TSTAMP(jj == 0 ? 32 : 33);
            const uint32_t wb = sb + (jj < 2 ? OFF_X + jj * 32768 : OFF_K + (jj - 2) * 32768) + bcol;
            wg_fence();
            gemm_chunk(acc, sb + OFF_V + jj * 16384, wb);
            gemm_chunk(acc, sb + OFF_V + jj * 16384 + 8192, wb + 16384);
            wg_commit();
        }
        wg_wait<0>();
        fence_regs<16>(acc);
        {
            const int row = pb * 64 + wq * 16 + g;
            uint32_t* d0 = (uint32_t*)(prm.out + (size_t)row * 1024 + 512 + hg * 128 + w * 32) + t;
            uint32_t* d1 = d0 + 8 * 512;
#pragma unroll
            for (int i = 0; i < 4; i++) {
                d0[4 * i] = pack_bf16(acc[4 * i], acc[4 * i + 1]);
                d1[4 * i] = pack_bf16(acc[4 * i + 2], acc[4 * i + 3]);
            }
        }
        if ((threadIdx.x & 127) == 0 && w == 0) TSTAMP(5);
    } else {
        const int wa = warp_id - 16, tau = threadIdx.x - 512;
        __syncthreads();
        if (tau == 0) {
            mbar_expect_tx(bar(B_WKV), 32768 + 16384);
            tma3d(sb + OFF_C, &tm_wk, 0, 0, 0, bar(B_WKV));
            tma3d(sb + OFF_C + 16384, &tm_wv, 0, 0, 0, bar(B_WKV));
            tma3d(sb + OFF_K, &tm_x16, 0, pb * 64 + hg * 16, 0, bar(B_WKV));
            TSTAMP(25);
        } else if (tau == 32) {
            for (int jj = 0; jj < 4; jj++) {
                mbar_expect_tx(bar(B_Q + jj), 16384 + 32768);
                tma3d(sb + OFF_X + jj * 16384, &tm_x, 0, pb * 64, 2 * jj, bar(B_Q + jj));
                if (jj < 2) tma4d(sb + OFF_V + jj * 32768, &tm_wq, 0, 0, hg * 2, 2 * jj, bar(B_Q + jj));
            }
        }
        __syncwarp();
        {
            float acc[16];
#pragma unroll
            for (int i = 0; i < 16; i++) acc[i] = 0.f;
            fence_regs<16>(acc);
            mbar_wait(bar(B_WKV), 0);
            if (tau == 0) TSTAMP(20);
            wg_fence();
#pragma unroll
            for (int j = 0; j < 8; j++) {
                const uint64_t da = make_desc(sb + OFF_K + j * 2048, 16, 1024, 1);
                const uint64_t db = make_desc(sb + OFF_C + j * 2048, 16384, 256, 3);
#pragma unroll
                for (int ks = 0; ks < 4; ks++) wg_ss_n32_tb(acc, da + ks * 2, db + ks * 32);
            }
            wg_commit();
            wg_wait<0>();
            fence_regs<16>(acc);
            if (tau == 0) TSTAMP(22);
            if (wa == 0) {
                uint32_t kk[4], vv[4];
#pragma unroll
                for (int i = 0; i < 4; i++) { kk[i] = pack_bf16(acc[2 * i], acc[2 * i + 1]); vv[i] = pack_bf16(acc[8 + 2 * i], acc[8 + 2 * i + 1]); }
                uint32_t* kp = (uint32_t*)(g_kimg + (8 * pb + 2 * hg) * 256 + g * 16 + 4 * t);
                kp[0] = kk[0]; kp[64] = kk[1]; kp[32] = kk[2]; kp[96] = kk[3];
                const int s = 4 * pb + hg;
                uint32_t* vlo = (uint32_t*)(g_vimg + (127 - s) * 256 + g * 16 + 4 * t);
                uint32_t* vhi = (uint32_t*)(g_vimg + 32768 + 256 + s * 256 + g * 16 + 4 * t);
                vlo[0] = pack_f16(bf_lo(vv[0]), bf_hi(vv[0])); vlo[32] = pack_f16(bf_lo(vv[1]), bf_hi(vv[1]));
                vhi[0] = pack_f16(bf_lo(vv[2]), bf_hi(vv[2])); vhi[32] = pack_f16(bf_lo(vv[3]), bf_hi(vv[3]));
                uint32_t* vr = (uint32_t*)(g_vraw + (size_t)(64 * pb + 16 * hg + g) * 16) + t;
                vr[0] = vv[0]; vr[64] = vv[1]; vr[4] = vv[2]; vr[68] = vv[3];
                float n0 = bf_lo(kk[0]) * bf_lo(kk[0]) + bf_hi(kk[0]) * bf_hi(kk[0]) + bf_lo(kk[2]) * bf_lo(kk[2]) + bf_hi(kk[2]) * bf_hi(kk[2]);
                float n1 = bf_lo(kk[1]) * bf_lo(kk[1]) + bf_hi(kk[1]) * bf_hi(kk[1]) + bf_lo(kk[3]) * bf_lo(kk[3]) + bf_hi(kk[3]) * bf_hi(kk[3]);
                n0 += __shfl_xor_sync(0xffffffffu, n0, 1); n0 += __shfl_xor_sync(0xffffffffu, n0, 2);
                n1 += __shfl_xor_sync(0xffffffffu, n1, 1); n1 += __shfl_xor_sync(0xffffffffu, n1, 2);
                float km = fmaxf(n0, n1), vm = 0.f;
#pragma unroll
                for (int i = 0; i < 4; i++) vm = fmaxf(vm, fmaxf(fabsf(bf_lo(vv[i])), fabsf(bf_hi(vv[i]))));
#pragma unroll
                for (int o = 4; o < 32; o <<= 1) km = fmaxf(km, __shfl_xor_sync(0xffffffffu, km, o));
#pragma unroll
                for (int o = 1; o < 32; o <<= 1) vm = fmaxf(vm, __shfl_xor_sync(0xffffffffu, vm, o));
                if (lane == 0) g_stats[b] = make_float2(km, vm);
                __syncwarp();
                if (lane == 0) { red_release_add(&g_kv_count, 1); TSTAMP(8); }
            }
        }
        const int c0 = 4 * b;
        if (wa == 0) {
            if (lane == 0) {
                for (int jj = 2; jj < 4; jj++) {
                    mbar_wait(bar(B_QEMPTY + jj - 2), 0);
                    tma4d(sb + OFF_V + (jj - 2) * 32768, &tm_wq, 0, 0, hg * 2, 2 * jj, bar(B_Q + jj));
                }
                poll_counter(&g_kv_count, NCTA);
                TSTAMP(16);
            }
            __syncwarp();
            float km = 0.f, vm = 0.f;
#pragma unroll
            for (int i = 0; i < 4; i++) { const float2 st = __ldcg(&g_stats[lane + 32 * i]); km = fmaxf(km, st.x); vm = fmaxf(vm, st.y); }
#pragma unroll
            for (int o = 1; o < 32; o <<= 1) { km = fmaxf(km, __shfl_xor_sync(0xffffffffu, km, o)); vm = fmaxf(vm, __shfl_xor_sync(0xffffffffu, vm, o)); }
            const bool vdirect = (vm <= 32768.f && vm >= 9.765625e-4f) || vm == 0.f;
            float vs = 1.f;
            if (!vdirect && vm < INFINITY) {
                int e = (int)((__float_as_uint(vm) >> 23) & 0xFF) - 127;
                e = max(-100, min(100, e));
                vs = __uint_as_float((uint32_t)(127 + e - 13) << 23);
            }
            if (lane == 0) {
                fence_async_global();
                for (int c = 0; c < 8; c++) {
                    mbar_expect_tx(bar(B_KV + c), vdirect ? 16384 : 8192);
                    bulk_g2s(sb + OFF_K + c * 8192, g_kimg + c * 8192, 8192, bar(B_KV + c));
                }
                asm volatile("st.shared.f32 [%0], %1;" ::"r"(sb + OFF_MISC), "f"(km) : "memory");
                asm volatile("st.shared.f32 [%0], %1;" ::"r"(sb + OFF_MISC + 4), "f"(vs) : "memory");
                TSTAMP(28);
                mbar_wait(bar(B_QDONE), 0);
                TSTAMP(17);
                if (vdirect) {
                    for (int c = 0; c < 8; c++) {
                        bulk_g2s(sb + OFF_V + (112 - 16 * c) * 256, g_vimg + (112 - 16 * c) * 256, 4096, bar(B_KV + c));
                        bulk_g2s(sb + OFF_VONES + 256 + c * 4096, g_vimg + 32768 + 256 + c * 4096, 4096, bar(B_KV + c));
                    }
                }
            }
            __syncwarp();
            sts32(sb + OFF_VONES + lane * 8, 0x3C003C00u);
            sts32(sb + OFF_VONES + lane * 8 + 4, 0x3C003C00u);
            if (!vdirect) {
                const float inv = 1.f / vs;
                for (int idx = lane; idx < S_LEN * 8; idx += 32) {
                    const int key = idx >> 3, dp = idx & 7;
                    const uint32_t v = __ldcg((const uint32_t*)g_vraw + idx);
                    const uint32_t h = pack_f16(bf_lo(v) * inv, bf_hi(v) * inv);
                    const int st = key >> 4, hf = (key >> 3) & 1;
                    const uint32_t base = (dp < 4) ? (OFF_V + (127 - st) * 256) : (OFF_VONES + 256 + st * 256);
                    sts32(sb + base + hf * 128 + (key & 7) * 16 + (dp & 3) * 4, h);
                }
            }
            fence_async_smem();
            __syncwarp();
            if (lane == 0) {
                mbar_arrive(bar(B_KV + 0));
                prefetch_tm(&tm_wo); prefetch_tm(&tm_o);
                for (int jj = 0; jj < 2; jj++) {
                    mbar_expect_tx(bar(B_WO + jj), 32768);
                    tma4d(sb + OFF_X + jj * 32768, &tm_wo, 0, 0, hg * 2, 2 * jj, bar(B_WO + jj));
                }
            }
            __syncwarp();
        } else if (wa == 1) {
            if (lane == 0) {
                mbar_expect_tx(bar(B_H), 4096);
                tma2d(sb + C_H + 1024, &tm_h, 0, c0 * 64, bar(B_H));
                poll_counter(&g_kvt_count[b >> 5], 32);
                fence_async_global();
                mbar_expect_tx(bar(B_CV), 16384);
                bulk_g2s(sb + C_KVC, g_kvT + (size_t)c0 * S_LEN, 16384, bar(B_CV));
            }
            __syncwarp();
        } else {
            sts128(sb + C_H + (tau - 64) * 16, 0u, 0u, 0u, 0u);
            fence_async_smem();
        }
        named_bar(5, 128);
        mbar_wait(bar(B_CV), 0);
        if (tau == 0) TSTAMP(9);
#pragma unroll 1
        for (int ch = 0; ch < 4; ch++) {
            {
                const uint32_t src = sb + C_KVC + ch * 4096 + tau * 32;
                const uint4 u0 = lds128(src), u1 = lds128(src + 16);
                const uint32_t prev = tau > 0 ? lds32(src - 4) : 0u;
                const uint32_t zd = sb + C_Z + (32 + tau * 16) * 4;
                sts128(zd,      __byte_perm(u0.x, prev, 0x7610), __byte_perm(u0.x, u0.x, 0x1032), __byte_perm(u0.y, u0.x, 0x7610), __byte_perm(u0.y, u0.y, 0x1032));
                sts128(zd + 16, __byte_perm(u0.z, u0.y, 0x7610), __byte_perm(u0.z, u0.z, 0x1032), __byte_perm(u0.w, u0.z, 0x7610), __byte_perm(u0.w, u0.w, 0x1032));
                sts128(zd + 32, __byte_perm(u1.x, u0.w, 0x7610), __byte_perm(u1.x, u1.x, 0x1032), __byte_perm(u1.y, u1.x, 0x7610), __byte_perm(u1.y, u1.y, 0x1032));
                sts128(zd + 48, __byte_perm(u1.z, u1.y, 0x7610), __byte_perm(u1.z, u1.z, 0x1032), __byte_perm(u1.w, u1.z, 0x7610), __byte_perm(u1.w, u1.w, 0x1032));
                if (tau < 32) sts32(sb + C_Z + tau * 4, 0u);
            }
            named_bar(5, 128);
            mbar_wait(bar(B_H), ch & 1);
            float D[32];
#pragma unroll
            for (int i = 0; i < 32; i++) D[i] = 0.f;
            const uint32_t z0 = sb + C_Z + (32 + 32 * (wa >> 1) + 16 * (wa & 1) + g - 2 * t) * 4;
            const uint64_t hd = make_desc(sb + C_H + 1024, 16, 512, 2);
            conv_group<64>(D, z0 + 0 * 2048, hd);
            conv_group<48>(D, z0 + 1 * 2048, hd);
            conv_group<32>(D, z0 + 2 * 2048, hd);
            conv_group<16>(D, z0 + 3 * 2048, hd);
            if (tau == 0 && ch < 3) {
                mbar_expect_tx(bar(B_H), 4096);
                tma2d(sb + C_H + 1024, &tm_h, 0, (c0 + ch + 1) * 64, bar(B_H));
            }
            if (wa >= 2) {
#pragma unroll
                for (int jn = 0; jn < 8; jn++) {
#pragma unroll
                    for (int r = 0; r < 2; r++) {
                        const int bb = 16 * (wa & 1) + g + 8 * r;
                        const int n = 8 * jn + 2 * t;
                        sts64f(sb + C_Z + (bb * 64 + (n ^ ((bb & 3) << 3))) * 4, D[4 * jn + 2 * r], D[4 * jn + 2 * r + 1]);
                    }
                }
            }
            named_bar(5, 128);
            if (wa < 2) {
                const float dsc = __bfloat162float(prm.ssm_D[c0 + ch]);
#pragma unroll
                for (int jn = 0; jn < 8; jn++) {
#pragma unroll
                    for (int r = 0; r < 2; r++) {
                        const int bb = 16 * wa + g + 8 * r;
#pragma unroll
                        for (int e = 0; e < 2; e++) {
                            const int m = 8 * jn + 2 * t + e;
                            float y = D[4 * jn + 2 * r + e];
                            if (m > 0) y += ldsf(sb + C_Z + (bb * 64 + ((m - 1) ^ ((bb & 3) << 3))) * 4);
                            const uint32_t addr = sb + C_KVC + ch * 4096 + (32 * m + bb) * 2;
                            const float kv = __uint_as_float(lds16(addr) << 16);
                            const float yb = __bfloat162float(__float2bfloat16_rn(y));
                            const float kd = __bfloat162float(__float2bfloat16_rn(kv * dsc));
                            sts16(addr, (uint32_t)__bfloat16_as_ushort(__float2bfloat16_rn(yb + kd)));
                        }
                    }
                }
                fence_async_smem();
            }
            named_bar(5, 128);
            if (tau == 0) {
                bulk_s2g(g_zT + (size_t)(c0 + ch) * S_LEN, sb + C_KVC + ch * 4096, 4096);
                bulk_commit();
                TSTAMP(10 + ch);
            }
        }
        {
            const int cg = tau & 15, pr = tau >> 4;
            const int p0 = pb * 64 + pr * 8, ch0 = hg * 128 + cg * 8;
            uint4 qr[8];
#pragma unroll
            for (int i = 0; i < 8; i++) qr[i] = __ldg((const uint4*)(prm.aq + (size_t)(p0 + i) * 512 + ch0));
            if (tau == 0) {
                bulk_wait_all();
                fence_async_global();
                red_release_add(&g_z_count[b >> 5], 1);
                poll_counter(&g_z_count[hg], 32);
                __threadfence();
                if (atomicAdd(&g_done, 1) == 2 * NCTA - 1) {
                    g_kv_count = 0;
                    for (int i = 0; i < 4; i++) { g_kvt_count[i] = 0; g_z_count[i] = 0; }
                    for (int i = 0; i < 32; i++) g_o_count[i] = 0;
                    g_done = 0;
                    __threadfence();
                }
            }
            named_bar(5, 128);
            uint4 zz[8];
#pragma unroll
            for (int c = 0; c < 8; c++) zz[c] = __ldcg((const uint4*)(g_zT + (size_t)(ch0 + c) * S_LEN + p0));
#pragma unroll
            for (int i = 0; i < 8; i++) {
                uint32_t r[4];
#pragma unroll
                for (int k = 0; k < 4; k++) {
                    const uint32_t pr2 = __byte_perm((&zz[2 * k].x)[i >> 1], (&zz[2 * k + 1].x)[i >> 1], (i & 1) ? 0x7632 : 0x5410);
                    r[k] = bmul2((&qr[i].x)[k], pr2);
                }
                *(uint4*)(prm.out + (size_t)(p0 + i) * 1024 + ch0) = make_uint4(r[0], r[1], r[2], r[3]);
            }
        }
        if (tau == 0) TSTAMP(14);
    }
}

typedef CUresult (*EncodeFn)(CUtensorMap*, CUtensorMapDataType, cuuint32_t, void*, const cuuint64_t*, const cuuint64_t*,
                             const cuuint32_t*, const cuuint32_t*, CUtensorMapInterleave, CUtensorMapSwizzle,
                             CUtensorMapL2promotion, CUtensorMapFloatOOBfill);

void make_map(EncodeFn fn, CUtensorMap* tm, const void* ptr, int rank, const cuuint64_t* dims, const cuuint64_t* strides, const cuuint32_t* box, CUtensorMapSwizzle swz) {
    cuuint32_t es[4] = {1, 1, 1, 1};
    fn(tm, CU_TENSOR_MAP_DATA_TYPE_BFLOAT16, rank, const_cast<void*>(ptr), dims, strides, box, es, CU_TENSOR_MAP_INTERLEAVE_NONE, swz,
       CU_TENSOR_MAP_L2_PROMOTION_L2_128B, CU_TENSOR_MAP_FLOAT_OOB_FILL_NONE);
}

}

extern "C" void kernel_launch(void* const* d_in, const int* in_sizes, int n_in, void* d_out, int out_size) {
    (void)in_sizes; (void)n_in; (void)out_size;
    static EncodeFn encode = nullptr;
    static void* o_ptr = nullptr;
    if (!encode) {
        cudaDriverEntryPointQueryResult qres;
        void* fn = nullptr;
        cudaGetDriverEntryPoint("cuTensorMapEncodeTiled", &fn, cudaEnableDefault, &qres);
        encode = (EncodeFn)fn;
        cudaGetSymbolAddress(&o_ptr, g_o);
        cudaFuncSetAttribute(fused_kernel, cudaFuncAttributeMaxDynamicSharedMemorySize, SMEM_TOTAL);
    }
    CUtensorMap tm_x16, tm_x, tm_wq, tm_wo, tm_wk, tm_wv, tm_o, tm_h;
    {
        const cuuint64_t dims[3] = {64, 2048, 8}, str[2] = {1024, 128};
        const cuuint32_t b16[3] = {64, 16, 8}, b64[3] = {64, 64, 2};
        make_map(encode, &tm_x16, d_in[6], 3, dims, str, b16, CU_TENSOR_MAP_SWIZZLE_128B);
        make_map(encode, &tm_x, d_in[6], 3, dims, str, b64, CU_TENSOR_MAP_SWIZZLE_128B);
        make_map(encode, &tm_o, o_ptr, 3, dims, str, b64, CU_TENSOR_MAP_SWIZZLE_128B);
    }
    {
        const cuuint64_t dims[4] = {64, 64, 8, 8}, str[3] = {1024, 128, 65536};
        const cuuint32_t box[4] = {64, 64, 2, 2};
        make_map(encode, &tm_wq, d_in[7], 4, dims, str, box, CU_TENSOR_MAP_SWIZZLE_128B);
        make_map(encode, &tm_wo, d_in[10], 4, dims, str, box, CU_TENSOR_MAP_SWIZZLE_128B);
    }
    {
        const cuuint64_t dims[3] = {16, 256, 2}, str[2] = {32, 8192};
        const cuuint32_t box[3] = {16, 256, 2};
        make_map(encode, &tm_wk, d_in[8], 3, dims, str, box, CU_TENSOR_MAP_SWIZZLE_32B);
        make_map(encode, &tm_wv, d_in[9], 3, dims, str, box, CU_TENSOR_MAP_SWIZZLE_32B);
    }
    {
        const cuuint64_t dims[2] = {32, 512 * 64}, str[1] = {64};
        const cuuint32_t box[2] = {32, 64};
        make_map(encode, &tm_h, d_in[4], 2, dims, str, box, CU_TENSOR_MAP_SWIZZLE_64B);
    }
    Params prm;
    prm.aq = (const __nv_bfloat16*)d_in[0];
    prm.ak = (const __nv_bfloat16*)d_in[1];
    prm.av = (const __nv_bfloat16*)d_in[2];
    prm.shift_k = (const __nv_bfloat16*)d_in[3];
    prm.ssm_D = (const __nv_bfloat16*)d_in[5];
    prm.out = (__nv_bfloat16*)d_out;
    fused_kernel<<<NCTA, NTHREADS, SMEM_TOTAL>>>(tm_x16, tm_x, tm_wq, tm_wo, tm_wk, tm_wv, tm_o, tm_h, prm);
}
```

```cpp
#include <cuda_runtime.h>
#include <cuda_bf16.h>
#include <cuda_fp16.h>
#include <cuda.h>
#include <stdint.h>

namespace {

constexpr int S_LEN = 2048;
constexpr int NCTA = 128;
constexpr int NTHREADS = 640;

constexpr uint32_t OFF_K = 0;
constexpr uint32_t OFF_V = 65536;
constexpr uint32_t OFF_VONES = OFF_V + 32768;
constexpr uint32_t OFF_X = 132096;
constexpr uint32_t OFF_C = 197632;
constexpr uint32_t C_KVC = OFF_C;
constexpr uint32_t C_H = OFF_C + 16384;
constexpr uint32_t C_Z = C_H + 5120;
constexpr uint32_t OFF_BAR = 231936;
constexpr uint32_t SMEM_TOTAL = 232448;

enum { B_WKV = 0, B_X = 1, B_QEMPTY = 5, B_QDONE = 7, B_KV = 8, B_WO = 16, B_O = 20, B_ATT = 24, B_H = 25, B_CV = 26, B_W = 27, B_COUNT = 31 };
constexpr uint32_t OFF_MISC = OFF_BAR + 8 * B_COUNT;

__device__ __align__(1024) uint8_t g_kimg[65536];
__device__ __align__(1024) uint8_t g_vimg[65792];
__device__ __align__(1024) __nv_bfloat16 g_vraw[S_LEN * 16];
__device__ __align__(1024) __nv_bfloat16 g_o[S_LEN * 512];
__device__ __align__(1024) __nv_bfloat16 g_kvT[512 * S_LEN];
__device__ __align__(1024) __nv_bfloat16 g_zT[512 * S_LEN];
__device__ float2 g_stats[NCTA];
__device__ unsigned int g_kv_count;
__device__ unsigned int g_kvt_count[4];
__device__ unsigned int g_z_count[4];
__device__ unsigned int g_o_count[32];
__device__ unsigned int g_done;
#define TSTAMP(i) do {} while (0)
#define CSTAMP(i) do {} while (0)

__device__ __forceinline__ void wg_fence() { asm volatile("wgmma.fence.sync.aligned;" ::: "memory"); }
__device__ __forceinline__ void wg_commit() { asm volatile("wgmma.commit_group.sync.aligned;" ::: "memory"); }
template <int N> __device__ __forceinline__ void wg_wait() { asm volatile("wgmma.wait_group.sync.aligned %0;" ::"n"(N) : "memory"); }
template <int N> __device__ __forceinline__ void fence_regs(float* r) {
#pragma unroll
    for (int i = 0; i < N; i++) asm volatile("" : "+f"(r[i])::"memory");
}
template <int N> __device__ __forceinline__ void fence_uregs(uint32_t* r) {
#pragma unroll
    for (int i = 0; i < N; i++) asm volatile("" : "+r"(r[i])::"memory");
}
__device__ __forceinline__ uint64_t make_desc(uint32_t saddr, uint32_t lbo, uint32_t sbo, uint32_t swz) {
    return (uint64_t)((saddr & 0x3FFFF) >> 4) | ((uint64_t)(lbo >> 4) << 16) | ((uint64_t)(sbo >> 4) << 32) | ((uint64_t)swz << 62);
}
__device__ __forceinline__ void mbar_init(uint32_t bar, uint32_t count) {
    asm volatile("mbarrier.init.shared::cta.b64 [%0], %1;" ::"r"(bar), "r"(count) : "memory");
}
__device__ __forceinline__ void mbar_expect_tx(uint32_t bar, uint32_t bytes) {
    asm volatile("mbarrier.arrive.expect_tx.shared::cta.b64 _, [%0], %1;" ::"r"(bar), "r"(bytes) : "memory");
}
__device__ __forceinline__ void mbar_arrive(uint32_t bar) {
    asm volatile("mbarrier.arrive.shared::cta.b64 _, [%0];" ::"r"(bar) : "memory");
}
__device__ __forceinline__ bool mbar_try(uint32_t bar, uint32_t parity) {
    uint32_t ok;
    asm volatile("{\n.reg .pred p;\nmbarrier.try_wait.parity.shared::cta.b64 p, [%1], %2;\nselp.u32 %0, 1, 0, p;\n}\n"
                 : "=r"(ok) : "r"(bar), "r"(parity) : "memory");
    return ok != 0;
}
__device__ __forceinline__ void mbar_wait(uint32_t bar, uint32_t parity) {
    uint32_t spins = 0;
    while (!mbar_try(bar, parity)) {
        if (++spins > (1u << 24)) __trap();
    }
}
__device__ __forceinline__ void mbar_wait_w(uint32_t bar, uint32_t parity) {
    uint32_t spins = 0;
    while (!__all_sync(0xffffffffu, mbar_try(bar, parity))) {
        if (++spins > (1u << 24)) __trap();
    }
}
__device__ __forceinline__ void tma2d(uint32_t dst, const CUtensorMap* tm, int c0, int c1, uint32_t bar) {
    asm volatile("cp.async.bulk.tensor.2d.shared::cluster.global.mbarrier::complete_tx::bytes [%0], [%1, {%3, %4}], [%2];"
                 ::"r"(dst), "l"((uint64_t)tm), "r"(bar), "r"(c0), "r"(c1) : "memory");
}
__device__ __forceinline__ void tma3d(uint32_t dst, const CUtensorMap* tm, int c0, int c1, int c2, uint32_t bar) {
    asm volatile("cp.async.bulk.tensor.3d.shared::cluster.global.mbarrier::complete_tx::bytes [%0], [%1, {%3, %4, %5}], [%2];"
                 ::"r"(dst), "l"((uint64_t)tm), "r"(bar), "r"(c0), "r"(c1), "r"(c2) : "memory");
}
__device__ __forceinline__ void tma4d(uint32_t dst, const CUtensorMap* tm, int c0, int c1, int c2, int c3, uint32_t bar) {
    asm volatile("cp.async.bulk.tensor.4d.shared::cluster.global.mbarrier::complete_tx::bytes [%0], [%1, {%3, %4, %5, %6}], [%2];"
                 ::"r"(dst), "l"((uint64_t)tm), "r"(bar), "r"(c0), "r"(c1), "r"(c2), "r"(c3) : "memory");
}
__device__ __forceinline__ void prefetch_tm(const CUtensorMap* tm) { asm volatile("prefetch.tensormap [%0];" ::"l"((uint64_t)tm) : "memory"); }
__device__ __forceinline__ void bulk_s2g(void* dst, uint32_t src, uint32_t bytes) {
    asm volatile("cp.async.bulk.global.shared::cta.bulk_group [%0], [%1], %2;" ::"l"(dst), "r"(src), "r"(bytes) : "memory");
}
__device__ __forceinline__ void bulk_commit() { asm volatile("cp.async.bulk.commit_group;" ::: "memory"); }
__device__ __forceinline__ void bulk_wait_all() { asm volatile("cp.async.bulk.wait_group 0;" ::: "memory"); }
__device__ __forceinline__ void fence_async_global() { asm volatile("fence.proxy.async.global;" ::: "memory"); }
__device__ __forceinline__ void bulk_g2s(uint32_t dst, const void* src, uint32_t bytes, uint32_t bar) {
    asm volatile("cp.async.bulk.shared::cluster.global.mbarrier::complete_tx::bytes [%0], [%1], %2, [%3];"
                 ::"r"(dst), "l"(src), "r"(bytes), "r"(bar) : "memory");
}
__device__ __forceinline__ void fence_async_smem() { asm volatile("fence.proxy.async.shared::cta;" ::: "memory"); }
__device__ __forceinline__ void named_bar(int id, int n) { asm volatile("bar.sync %0, %1;" ::"r"(id), "r"(n) : "memory"); }
__device__ __forceinline__ bool named_bar_and(int id, int n, bool pred) {
    uint32_t r;
    asm volatile("{\n.reg .pred p, q;\nsetp.ne.u32 p, %3, 0;\nbarrier.cta.red.and.pred q, %1, %2, p;\nselp.u32 %0, 1, 0, q;\n}\n"
                 : "=r"(r) : "r"(id), "r"(n), "r"((uint32_t)pred) : "memory");
    return r != 0;
}
__device__ __forceinline__ unsigned int ld_acquire(const unsigned int* p) {
    unsigned int v;
    asm volatile("ld.acquire.gpu.global.u32 %0, [%1];" : "=r"(v) : "l"(p) : "memory");
    return v;
}
__device__ __forceinline__ void red_release_add(unsigned int* p, unsigned int v) {
    asm volatile("red.release.gpu.global.add.u32 [%0], %1;" ::"l"(p), "r"(v) : "memory");
}
__device__ __forceinline__ void poll_counter(const unsigned int* p, unsigned int target) {
    uint32_t spins = 0;
    while (ld_acquire(p) < target) {
        if (++spins > (1u << 22)) __trap();
    }
}
__device__ __forceinline__ float ex2f(float x) { float y; asm("ex2.approx.ftz.f32 %0, %1;" : "=f"(y) : "f"(x)); return y; }
__device__ __forceinline__ uint32_t pack_f16(float lo, float hi) { uint32_t r; asm("cvt.rn.f16x2.f32 %0, %1, %2;" : "=r"(r) : "f"(hi), "f"(lo)); return r; }
__device__ __forceinline__ uint32_t pack_bf16(float lo, float hi) { uint32_t r; asm("cvt.rn.bf16x2.f32 %0, %1, %2;" : "=r"(r) : "f"(hi), "f"(lo)); return r; }
__device__ __forceinline__ float bf_lo(uint32_t v) { return __uint_as_float(v << 16); }
__device__ __forceinline__ float bf_hi(uint32_t v) { return __uint_as_float(v & 0xFFFF0000u); }
__device__ __forceinline__ uint32_t hfma2(uint32_t a, uint32_t b, uint32_t c) { uint32_t r; asm("fma.rn.f16x2 %0, %1, %2, %3;" : "=r"(r) : "r"(a), "r"(b), "r"(c)); return r; }
__device__ __forceinline__ uint32_t bmul2(uint32_t a, uint32_t b) { uint32_t r; asm("mul.rn.bf16x2 %0, %1, %2;" : "=r"(r) : "r"(a), "r"(b)); return r; }
__device__ __forceinline__ uint32_t badd2(uint32_t a, uint32_t b) { uint32_t r; asm("add.rn.bf16x2 %0, %1, %2;" : "=r"(r) : "r"(a), "r"(b)); return r; }
template <int LUT> __device__ __forceinline__ uint32_t lop3(uint32_t a, uint32_t b, uint32_t c) {
    uint32_t r; asm("lop3.b32 %0, %1, %2, %3, %4;" : "=r"(r) : "r"(a), "r"(b), "r"(c), "n"(LUT)); return r;
}
__device__ __forceinline__ uint32_t lds32(uint32_t a) { uint32_t v; asm volatile("ld.shared.u32 %0, [%1];" : "=r"(v) : "r"(a)); return v; }
__device__ __forceinline__ float ldsf(uint32_t a) { float v; asm volatile("ld.shared.f32 %0, [%1];" : "=f"(v) : "r"(a)); return v; }
__device__ __forceinline__ uint32_t lds16(uint32_t a) { uint16_t v; asm volatile("ld.shared.u16 %0, [%1];" : "=h"(v) : "r"(a)); return v; }
__device__ __forceinline__ uint4 lds128(uint32_t a) { uint4 v; asm volatile("ld.shared.v4.u32 {%0,%1,%2,%3}, [%4];" : "=r"(v.x), "=r"(v.y), "=r"(v.z), "=r"(v.w) : "r"(a)); return v; }
__device__ __forceinline__ void sts32(uint32_t a, uint32_t v) { asm volatile("st.shared.u32 [%0], %1;" ::"r"(a), "r"(v) : "memory"); }
__device__ __forceinline__ void sts16(uint32_t a, uint32_t v) { asm volatile("st.shared.u16 [%0], %1;" ::"r"(a), "h"((uint16_t)v) : "memory"); }
__device__ __forceinline__ void sts64f(uint32_t a, float x, float y) { asm volatile("st.shared.v2.f32 [%0], {%1,%2};" ::"r"(a), "f"(x), "f"(y) : "memory"); }
__device__ __forceinline__ void sts128(uint32_t a, uint32_t x, uint32_t y, uint32_t z, uint32_t w) {
    asm volatile("st.shared.v4.u32 [%0], {%1,%2,%3,%4};" ::"r"(a), "r"(x), "r"(y), "r"(z), "r"(w) : "memory");
}

__device__ __forceinline__ void wg_ss_n32_tb(float* d, uint64_t descA, uint64_t descB) {
    asm volatile("wgmma.mma_async.sync.aligned.m64n32k16.f32.bf16.bf16 {%0,%1,%2,%3,%4,%5,%6,%7,%8,%9,%10,%11,%12,%13,%14,%15}, %16, %17, 1, 1, 1, 0, 1;\n"
        : "+f"(d[0]), "+f"(d[1]), "+f"(d[2]), "+f"(d[3]), "+f"(d[4]), "+f"(d[5]), "+f"(d[6]), "+f"(d[7]), "+f"(d[8]), "+f"(d[9]), "+f"(d[10]), "+f"(d[11]), "+f"(d[12]), "+f"(d[13]), "+f"(d[14]), "+f"(d[15])
        : "l"(descA), "l"(descB));
}
__device__ __forceinline__ void wg_qk_n64(float* d, const uint32_t* a, uint64_t desc) {
    asm volatile("wgmma.mma_async.sync.aligned.m64n64k16.f32.bf16.bf16 {%0,%1,%2,%3,%4,%5,%6,%7,%8,%9,%10,%11,%12,%13,%14,%15,%16,%17,%18,%19,%20,%21,%22,%23,%24,%25,%26,%27,%28,%29,%30,%31}, {%32,%33,%34,%35}, %36, 0, 1, 1, 0;\n"
        : "+f"(d[0]), "+f"(d[1]), "+f"(d[2]), "+f"(d[3]), "+f"(d[4]), "+f"(d[5]), "+f"(d[6]), "+f"(d[7]), "+f"(d[8]), "+f"(d[9]), "+f"(d[10]), "+f"(d[11]), "+f"(d[12]), "+f"(d[13]), "+f"(d[14]), "+f"(d[15]), "+f"(d[16]), "+f"(d[17]), "+f"(d[18]), "+f"(d[19]), "+f"(d[20]), "+f"(d[21]), "+f"(d[22]), "+f"(d[23]), "+f"(d[24]), "+f"(d[25]), "+f"(d[26]), "+f"(d[27]), "+f"(d[28]), "+f"(d[29]), "+f"(d[30]), "+f"(d[31])
        : "r"(a[0]), "r"(a[1]), "r"(a[2]), "r"(a[3]), "l"(desc));
}
__device__ __forceinline__ void wg_pv_n24(float* d, const uint32_t* a, uint64_t desc) {
    asm volatile("wgmma.mma_async.sync.aligned.m64n24k16.f32.f16.f16 {%0,%1,%2,%3,%4,%5,%6,%7,%8,%9,%10,%11}, {%12,%13,%14,%15}, %16, 1, 1, 1, 1;\n"
        : "+f"(d[0]), "+f"(d[1]), "+f"(d[2]), "+f"(d[3]), "+f"(d[4]), "+f"(d[5]), "+f"(d[6]), "+f"(d[7]), "+f"(d[8]), "+f"(d[9]), "+f"(d[10]), "+f"(d[11])
        : "r"(a[0]), "r"(a[1]), "r"(a[2]), "r"(a[3]), "l"(desc));
}
__device__ __forceinline__ void wg_cv_n16(float* d, const uint32_t* a, uint64_t desc) {
    asm volatile("wgmma.mma_async.sync.aligned.m64n16k16.f32.bf16.bf16 {%0,%1,%2,%3,%4,%5,%6,%7}, {%8,%9,%10,%11}, %12, 1, 1, 1, 0;\n"
        : "+f"(d[0]), "+f"(d[1]), "+f"(d[2]), "+f"(d[3]), "+f"(d[4]), "+f"(d[5]), "+f"(d[6]), "+f"(d[7])
        : "r"(a[0]), "r"(a[1]), "r"(a[2]), "r"(a[3]), "l"(desc));
}
__device__ __forceinline__ void wg_cv_n32(float* d, const uint32_t* a, uint64_t desc) {
    asm volatile("wgmma.mma_async.sync.aligned.m64n32k16.f32.bf16.bf16 {%0,%1,%2,%3,%4,%5,%6,%7,%8,%9,%10,%11,%12,%13,%14,%15}, {%16,%17,%18,%19}, %20, 1, 1, 1, 0;\n"
        : "+f"(d[0]), "+f"(d[1]), "+f"(d[2]), "+f"(d[3]), "+f"(d[4]), "+f"(d[5]), "+f"(d[6]), "+f"(d[7]), "+f"(d[8]), "+f"(d[9]), "+f"(d[10]), "+f"(d[11]), "+f"(d[12]), "+f"(d[13]), "+f"(d[14]), "+f"(d[15])
        : "r"(a[0]), "r"(a[1]), "r"(a[2]), "r"(a[3]), "l"(desc));
}
__device__ __forceinline__ void wg_cv_n48(float* d, const uint32_t* a, uint64_t desc) {
    asm volatile("wgmma.mma_async.sync.aligned.m64n48k16.f32.bf16.bf16 {%0,%1,%2,%3,%4,%5,%6,%7,%8,%9,%10,%11,%12,%13,%14,%15,%16,%17,%18,%19,%20,%21,%22,%23}, {%24,%25,%26,%27}, %28, 1, 1, 1, 0;\n"
        : "+f"(d[0]), "+f"(d[1]), "+f"(d[2]), "+f"(d[3]), "+f"(d[4]), "+f"(d[5]), "+f"(d[6]), "+f"(d[7]), "+f"(d[8]), "+f"(d[9]), "+f"(d[10]), "+f"(d[11]), "+f"(d[12]), "+f"(d[13]), "+f"(d[14]), "+f"(d[15]), "+f"(d[16]), "+f"(d[17]), "+f"(d[18]), "+f"(d[19]), "+f"(d[20]), "+f"(d[21]), "+f"(d[22]), "+f"(d[23])
        : "r"(a[0]), "r"(a[1]), "r"(a[2]), "r"(a[3]), "l"(desc));
}
__device__ __forceinline__ void wg_cv_n64(float* d, const uint32_t* a, uint64_t desc) {
    asm volatile("wgmma.mma_async.sync.aligned.m64n64k16.f32.bf16.bf16 {%0,%1,%2,%3,%4,%5,%6,%7,%8,%9,%10,%11,%12,%13,%14,%15,%16,%17,%18,%19,%20,%21,%22,%23,%24,%25,%26,%27,%28,%29,%30,%31}, {%32,%33,%34,%35}, %36, 1, 1, 1, 0;\n"
        : "+f"(d[0]), "+f"(d[1]), "+f"(d[2]), "+f"(d[3]), "+f"(d[4]), "+f"(d[5]), "+f"(d[6]), "+f"(d[7]), "+f"(d[8]), "+f"(d[9]), "+f"(d[10]), "+f"(d[11]), "+f"(d[12]), "+f"(d[13]), "+f"(d[14]), "+f"(d[15]), "+f"(d[16]), "+f"(d[17]), "+f"(d[18]), "+f"(d[19]), "+f"(d[20]), "+f"(d[21]), "+f"(d[22]), "+f"(d[23]), "+f"(d[24]), "+f"(d[25]), "+f"(d[26]), "+f"(d[27]), "+f"(d[28]), "+f"(d[29]), "+f"(d[30]), "+f"(d[31])
        : "r"(a[0]), "r"(a[1]), "r"(a[2]), "r"(a[3]), "l"(desc));
}

template <int N> __device__ __forceinline__ void wg_cv(float* d, const uint32_t* a, uint64_t desc);
template <> __device__ __forceinline__ void wg_cv<16>(float* d, const uint32_t* a, uint64_t s) { wg_cv_n16(d, a, s); }
template <> __device__ __forceinline__ void wg_cv<32>(float* d, const uint32_t* a, uint64_t s) { wg_cv_n32(d, a, s); }
template <> __device__ __forceinline__ void wg_cv<48>(float* d, const uint32_t* a, uint64_t s) { wg_cv_n48(d, a, s); }
template <> __device__ __forceinline__ void wg_cv<64>(float* d, const uint32_t* a, uint64_t s) { wg_cv_n64(d, a, s); }

constexpr uint32_t POLYMASK = 0xB5B5u;
__device__ __forceinline__ void softmax_fast(const float* s, uint32_t* p, uint32_t mlo) {
    const uint32_t C3 = 0x2cfb2cfbu, C2 = 0x9fec9fecu, C1 = 0x37a837a8u, C0 = 0x37383738u;
#pragma unroll
    for (int i = 0; i < 16; i++) {
        const float s0 = s[2 * i], s1 = s[2 * i + 1];
        if ((POLYMASK >> i) & 1) {
            const float t0 = s0 + 12303.0f, t1 = s1 + 12303.0f;
            const uint32_t T = __byte_perm(__float_as_uint(t0), __float_as_uint(t1), 0x5410);
            const uint32_t U = lop3<0xEA>(T, mlo, 0x3C003C00u);
            uint32_t h = hfma2(U, C3, C2);
            h = hfma2(h, U, C1);
            h = hfma2(h, U, C0);
            p[i] = lop3<0xE4>(h, T, 0x03FF03FFu);
        } else {
            p[i] = pack_f16(ex2f(s0), ex2f(s1));
        }
    }
}

__device__ __forceinline__ void gemm_chunk(float* acc, uint32_t a_addr, uint32_t b_addr) {
    const uint64_t da = make_desc(a_addr, 16, 1024, 1);
    const uint64_t db = make_desc(b_addr, 8192, 1024, 1);
#pragma unroll
    for (int ks = 0; ks < 4; ks++) wg_ss_n32_tb(acc, da + ks * 2, db + ks * 128);
}

__device__ __forceinline__ void wo_half(uint32_t sb, const CUtensorMap* tm_wo, int hg) {
    uint32_t old;
    asm volatile("atom.shared.add.u32 %0, [%1], 1;" : "=r"(old) : "r"(sb + OFF_MISC + 8) : "memory");
    if (old == 3) {
        mbar_expect_tx(sb + OFF_BAR + 8 * (B_WO + 2), 32768);
        tma4d(sb + OFF_K, tm_wo, 0, 0, hg * 2, 4, sb + OFF_BAR + 8 * (B_WO + 2));
    }
}

struct Params {
    const __nv_bfloat16 *aq, *ak, *av, *shift_k, *ssm_D;
    __nv_bfloat16* out;
};

template <int NQ>
__device__ __forceinline__ void conv_group(float* D, uint32_t zaddr, uint64_t hdesc) {
    float Dn[NQ / 2];
#pragma unroll
    for (int i = 0; i < NQ / 2; i++) asm volatile("mov.f32 %0, %1;" : "=f"(Dn[i]) : "f"(D[(64 - NQ) / 2 + i]));
    uint32_t a[2][16];
#pragma unroll
    for (int st = 0; st < 4; st++) {
        uint32_t* aa = a[st & 1];
        if (st >= 2) wg_wait<1>();
#pragma unroll
        for (int u = 0; u < 2; u++) {
            const uint32_t z = zaddr + (st * 2 + u) * 256;
            aa[8 * u + 0] = lds32(z);      aa[8 * u + 1] = lds32(z + 32); aa[8 * u + 2] = lds32(z - 32); aa[8 * u + 3] = lds32(z);
            aa[8 * u + 4] = lds32(z - 64); aa[8 * u + 5] = lds32(z - 32); aa[8 * u + 6] = lds32(z - 96); aa[8 * u + 7] = lds32(z - 64);
        }
        wg_fence();
#pragma unroll
        for (int u = 0; u < 2; u++) {
            const int qi = st * 2 + u;
            wg_cv<NQ>(Dn, &aa[8 * u], hdesc - qi * 8);
            wg_cv<NQ>(Dn, &aa[8 * u + 4], hdesc - qi * 8 + 2);
        }
        wg_commit();
    }
    wg_wait<0>();
    fence_regs<NQ / 2>(Dn);
#pragma unroll
    for (int i = 0; i < NQ / 2; i++) asm volatile("mov.f32 %0, %1;" : "=f"(D[(64 - NQ) / 2 + i]) : "f"(Dn[i]));
}

__global__ void __launch_bounds__(NTHREADS, 1)
fused_kernel(const __grid_constant__ CUtensorMap tm_x,
             const __grid_constant__ CUtensorMap tm_wq, const __grid_constant__ CUtensorMap tm_wo,
             const __grid_constant__ CUtensorMap tm_wk, const __grid_constant__ CUtensorMap tm_wv,
             const __grid_constant__ CUtensorMap tm_o, const __grid_constant__ CUtensorMap tm_h, const Params prm) {
    extern __shared__ __align__(1024) uint8_t smem_raw[];
    const uint32_t sb = (uint32_t)__cvta_generic_to_shared(smem_raw);
    const int warp_id = __shfl_sync(0xffffffffu, threadIdx.x >> 5, 0);
    const int lane = threadIdx.x & 31;
    const int g = lane >> 2, t = lane & 3;
    const int b = blockIdx.x, pb = b >> 2, hg = b & 3;
    auto bar = [&](int i) { return sb + OFF_BAR + 8 * i; };

    if (threadIdx.x == 512) {
        TSTAMP(0);
        prefetch_tm(&tm_x); prefetch_tm(&tm_wq); prefetch_tm(&tm_wk); prefetch_tm(&tm_wv);
        mbar_init(bar(B_WKV), 1);
        for (int j = 0; j < 4; j++) { mbar_init(bar(B_X + j), 1); mbar_init(bar(B_W + j), 1); mbar_init(bar(B_WO + j), 1); mbar_init(bar(B_O + j), 1); }
        sts32(sb + OFF_MISC + 8, 0u);
        for (int j = 0; j < 8; j++) mbar_init(bar(B_KV + j), j == 0 ? 2 : 1);
        mbar_init(bar(B_QEMPTY), 4); mbar_init(bar(B_QEMPTY + 1), 4);
        mbar_init(bar(B_QDONE), 4); mbar_init(bar(B_ATT), 4);
        mbar_init(bar(B_H), 1); mbar_init(bar(B_CV), 1);
        asm volatile("fence.mbarrier_init.release.cluster;" ::: "memory");
    }

    if (warp_id < 16) {
        const int w = warp_id >> 2, wq = warp_id & 3;
        __syncthreads();
        float acc[16];
#pragma unroll
        for (int i = 0; i < 16; i++) acc[i] = 0.f;
        fence_regs<16>(acc);
        const uint32_t bcol = (w >> 1) * 8192 + (w & 1) * 64;
        const int kpr = lane & 7, kcg = wq * 4 + (lane >> 3);
        const int kp0 = pb * 64 + w * 16 + 2 * kpr, kch0 = hg * 128 + kcg * 8;
        uint4 kr[5], vr[2], sw[4];
        mbar_wait_w(bar(B_X + 0), 0);
#pragma unroll
        for (int i = 0; i < 5; i++) {
            const int s = kp0 - 3 + i;
            kr[i] = s >= 0 ? __ldg((const uint4*)(prm.ak + (size_t)s * 512 + kch0)) : make_uint4(0u, 0u, 0u, 0u);
        }
#pragma unroll
        for (int i = 0; i < 2; i++) vr[i] = __ldg((const uint4*)(prm.av + (size_t)(kp0 + i) * 512 + kch0));
#pragma unroll
        for (int i = 0; i < 4; i++) sw[i] = __ldg((const uint4*)(prm.shift_k + kch0 * 4) + i);
#pragma unroll 1
        for (int jj = 0; jj < 4; jj++) {
            mbar_wait_w(bar(B_X + jj), 0);
            mbar_wait_w(bar(B_W + jj), 0);
            wg_fence();
            gemm_chunk(acc, sb + OFF_X + jj * 16384, sb + OFF_V + (jj & 1) * 32768 + bcol);
            gemm_chunk(acc, sb + OFF_X + jj * 16384 + 8192, sb + OFF_V + (jj & 1) * 32768 + 16384 + bcol);
            wg_commit();
            wg_wait<0>();
            if (jj < 2 && (threadIdx.x & 127) == 0) mbar_arrive(bar(B_QEMPTY + jj));
        }
        fence_regs<16>(acc);
        if ((threadIdx.x & 127) == 0) { mbar_arrive(bar(B_QDONE)); if (w == 0) TSTAMP(1); }
        {
            uint32_t x0[4], x1[4];
#pragma unroll
            for (int i = 0; i < 4; i++) {
                const uint32_t w0 = __byte_perm(sw[i].x, sw[i].z, 0x5410), w1 = __byte_perm(sw[i].x, sw[i].z, 0x7632);
                const uint32_t w2 = __byte_perm(sw[i].y, sw[i].w, 0x5410), w3 = __byte_perm(sw[i].y, sw[i].w, 0x7632);
                const uint32_t k0 = (&kr[0].x)[i], k1 = (&kr[1].x)[i], k2 = (&kr[2].x)[i], k3 = (&kr[3].x)[i], k4 = (&kr[4].x)[i];
                x0[i] = bmul2(badd2(badd2(badd2(bmul2(k0, w3), bmul2(k1, w2)), bmul2(k2, w1)), bmul2(k3, w0)), (&vr[0].x)[i]);
                x1[i] = bmul2(badd2(badd2(badd2(bmul2(k1, w3), bmul2(k2, w2)), bmul2(k3, w1)), bmul2(k4, w0)), (&vr[1].x)[i]);
            }
            uint32_t* dst = (uint32_t*)(g_kvT + (size_t)kch0 * S_LEN + kp0);
#pragma unroll
            for (int i = 0; i < 4; i++) {
                dst[(2 * i) * (S_LEN / 2)] = __byte_perm(x0[i], x1[i], 0x5410);
                dst[(2 * i + 1) * (S_LEN / 2)] = __byte_perm(x0[i], x1[i], 0x7632);
            }
        }
        named_bar(6, 512);
        if (threadIdx.x == 0) { red_release_add(&g_kvt_count[hg], 1); TSTAMP(34); }
        uint32_t qa[2][4];
        float qn[2];
        {
            const float c = 0.25f * 1.4426950408889634f;
#pragma unroll
            for (int hh = 0; hh < 2; hh++) {
                float n0 = 0.f, n1 = 0.f;
#pragma unroll
                for (int i = 0; i < 4; i++) {
                    const uint32_t qb = pack_bf16(acc[8 * hh + 2 * i], acc[8 * hh + 2 * i + 1]);
                    const uint32_t qs = pack_bf16(bf_lo(qb) * c, bf_hi(qb) * c);
                    qa[hh][i] = qs;
                    const float e = bf_lo(qs) * bf_lo(qs) + bf_hi(qs) * bf_hi(qs);
                    if (i & 1) n1 += e; else n0 += e;
                }
                n0 += __shfl_xor_sync(0xffffffffu, n0, 1); n0 += __shfl_xor_sync(0xffffffffu, n0, 2);
                n1 += __shfl_xor_sync(0xffffffffu, n1, 1); n1 += __shfl_xor_sync(0xffffffffu, n1, 2);
                qn[hh] = fmaxf(n0, n1);
            }
        }
        uint32_t mlo = 0x03FF03FFu; asm volatile("" : "+r"(mlo));
        const uint64_t kdesc0 = make_desc(sb + OFF_K, 128, 256, 0);
        const uint64_t vdesc0 = make_desc(sb + OFF_VONES - 256, 128, 256, 0);
        constexpr uint64_t VSTEP = ((uint64_t)16 << 32) - 16;
        mbar_wait_w(bar(B_KV + 0), 0);
        if ((threadIdx.x & 127) == 0 && w == 0) TSTAMP(2);
        const float kmax2 = ldsf(sb + OFF_MISC);
        const bool fast0 = __all_sync(0xffffffffu, named_bar_and(1 + w, 128, qn[0] * kmax2 <= 193.0f));
        const bool fast1 = __all_sync(0xffffffffu, named_bar_and(1 + w, 128, qn[1] * kmax2 <= 193.0f));
        uint32_t a[4] = {qa[0][0], qa[0][1], qa[0][2], qa[0][3]};
#pragma unroll 1
        for (int hh = 0; hh < 2; hh++) {
            const bool fast = hh ? fast1 : fast0;
            float S[32], O[12];
#pragma unroll
            for (int i = 0; i < 12; i++) O[i] = 0.f;
#pragma unroll
            for (int i = 0; i < 32; i++) S[i] = 0.f;
            fence_regs<12>(O); fence_regs<32>(S);
            wg_fence();
            wg_qk_n64(S, a, kdesc0);
            wg_commit();
            wg_wait<0>();
            uint64_t kd = kdesc0 + 128, vd = vdesc0;
            if (fast) {
                uint32_t P[16];
#pragma unroll 1
                for (int c = 0; c < 8; c++) {
                    if (c < 7) mbar_wait_w(bar(B_KV + c + 1), 0);
#pragma unroll 1
                    for (int j = 0; j < 4; j++) {
                        fence_regs<32>(S);
                        softmax_fast(S, P, mlo);
                        fence_regs<32>(S);
                        wg_fence();
                        wg_qk_n64(S, a, kd);
#pragma unroll
                        for (int i = 0; i < 4; i++) wg_pv_n24(O, &P[4 * i], vd + i * VSTEP);
                        wg_commit();
                        wg_wait<0>();
                        kd += 128; vd += 4 * VSTEP;
                    }
                    if (hh == 1 && c == 3 && (threadIdx.x & 127) == 0) wo_half(sb, &tm_wo, hg);
                }
            } else {
                uint32_t P[16];
                float m0 = -INFINITY, m1 = -INFINITY;
#pragma unroll 1
                for (int c = 0; c < 8; c++) {
                    if (c < 7) mbar_wait_w(bar(B_KV + c + 1), 0);
#pragma unroll 1
                    for (int j = 0; j < 4; j++) {
                        fence_regs<32>(S); fence_regs<12>(O);
                        float x0 = m0, x1 = m1;
#pragma unroll
                        for (int i = 0; i < 8; i++) {
                            x0 = fmaxf(x0, fmaxf(S[4 * i], S[4 * i + 1]));
                            x1 = fmaxf(x1, fmaxf(S[4 * i + 2], S[4 * i + 3]));
                        }
                        x0 = fmaxf(x0, __shfl_xor_sync(0xffffffffu, x0, 1)); x0 = fmaxf(x0, __shfl_xor_sync(0xffffffffu, x0, 2));
                        x1 = fmaxf(x1, __shfl_xor_sync(0xffffffffu, x1, 1)); x1 = fmaxf(x1, __shfl_xor_sync(0xffffffffu, x1, 2));
                        const float r0 = ex2f(m0 - x0), r1 = ex2f(m1 - x1);
                        m0 = x0; m1 = x1;
#pragma unroll
                        for (int i = 0; i < 3; i++) { O[4 * i] *= r0; O[4 * i + 1] *= r0; O[4 * i + 2] *= r1; O[4 * i + 3] *= r1; }
#pragma unroll
                        for (int i = 0; i < 8; i++) {
                            P[2 * i] = pack_f16(ex2f(S[4 * i] - m0), ex2f(S[4 * i + 1] - m0));
                            P[2 * i + 1] = pack_f16(ex2f(S[4 * i + 2] - m1), ex2f(S[4 * i + 3] - m1));
                        }
                        fence_regs<32>(S); fence_regs<12>(O);
                        wg_fence();
                        wg_qk_n64(S, a, kd);
#pragma unroll
                        for (int i = 0; i < 4; i++) wg_pv_n24(O, &P[4 * i], vd + i * VSTEP);
                        wg_commit();
                        wg_wait<0>();
                        kd += 128; vd += 4 * VSTEP;
                    }
                    if (hh == 1 && c == 3 && (threadIdx.x & 127) == 0) wo_half(sb, &tm_wo, hg);
                }
            }
            fence_regs<12>(O);
            const float vscale = ldsf(sb + OFF_MISC + 4);
            const float i0 = __fdividef(vscale, O[4]), i1 = __fdividef(vscale, O[6]);
            const int row = pb * 64 + wq * 16 + g;
            uint32_t* o0 = (uint32_t*)(g_o + (size_t)row * 512 + (hg * 8 + 2 * w + hh) * 16) + t;
            uint32_t* o1 = o0 + 8 * 256;
            o0[0] = pack_bf16(O[0] * i0, O[1] * i0);
            o0[4] = pack_bf16(O[8] * i0, O[9] * i0);
            o1[0] = pack_bf16(O[2] * i1, O[3] * i1);
            o1[4] = pack_bf16(O[10] * i1, O[11] * i1);
            if ((threadIdx.x & 127) == 0 && w == 0) { TSTAMP(3 + hh); CSTAMP(40 + hh); }
#pragma unroll
            for (int i = 0; i < 4; i++) a[i] = qa[1][i];
        }
        named_bar(1 + w, 128);
        if ((threadIdx.x & 127) == 0) {
            red_release_add(&g_o_count[pb], 1);
            mbar_arrive(bar(B_ATT));
        }
        if (threadIdx.x == 0) {
            TSTAMP(30);
            mbar_wait(bar(B_ATT), 0);
            TSTAMP(31);
            poll_counter(&g_o_count[pb], 16);
            TSTAMP(18);
            fence_async_global();
            for (int jj = 0; jj < 4; jj++) {
                mbar_expect_tx(bar(B_O + jj), 16384);
                tma3d(sb + OFF_V + jj * 16384, &tm_o, 0, pb * 64, 2 * jj, bar(B_O + jj));
            }
            __threadfence();
            if (atomicAdd(&g_done, 1) == 2 * NCTA - 1) {
                g_kv_count = 0;
                for (int i = 0; i < 4; i++) { g_kvt_count[i] = 0; g_z_count[i] = 0; }
                for (int i = 0; i < 32; i++) g_o_count[i] = 0;
                g_done = 0;
                __threadfence();
            }
        }
        __syncwarp();
#pragma unroll
        for (int i = 0; i < 16; i++) acc[i] = 0.f;
        fence_regs<16>(acc);
#pragma unroll 1
        for (int jj = 0; jj < 4; jj++) {
            mbar_wait_w(bar(B_WO + jj), 0);
            mbar_wait_w(bar(B_O + jj), 0);
            if (threadIdx.x == 0 && (jj == 0 || jj == 3)) TSTAMP(jj == 0 ? 32 : 33);
            const uint32_t wb = sb + (jj < 2 ? OFF_X + jj * 32768 : (jj == 2 ? OFF_K : OFF_C)) + bcol;
            wg_fence();
            gemm_chunk(acc, sb + OFF_V + jj * 16384, wb);
            gemm_chunk(acc, sb + OFF_V + jj * 16384 + 8192, wb + 16384);
            wg_commit();
        }
        wg_wait<0>();
        fence_regs<16>(acc);
        {
            const int row = pb * 64 + wq * 16 + g;
            uint32_t* d0 = (uint32_t*)(prm.out + (size_t)row * 1024 + 512 + hg * 128 + w * 32) + t;
            uint32_t* d1 = d0 + 8 * 512;
#pragma unroll
            for (int i = 0; i < 4; i++) {
                d0[4 * i] = pack_bf16(acc[4 * i], acc[4 * i + 1]);
                d1[4 * i] = pack_bf16(acc[4 * i + 2], acc[4 * i + 3]);
            }
        }
        if ((threadIdx.x & 127) == 0 && w == 0) TSTAMP(5);
    } else {
        const int wa = warp_id - 16, tau = threadIdx.x - 512;
        __syncthreads();
        const bool kv_cta = (hg == (pb & 3));
        if (tau == 0) {
            if (kv_cta) {
                mbar_expect_tx(bar(B_WKV), 32768);
                tma3d(sb + OFF_C, &tm_wk, 0, 0, 0, bar(B_WKV));
                tma3d(sb + OFF_C + 16384, &tm_wv, 0, 0, 0, bar(B_WKV));
            }
            for (int jj = 0; jj < 4; jj++) {
                mbar_expect_tx(bar(B_X + jj), 16384);
                tma3d(sb + OFF_X + jj * 16384, &tm_x, 0, pb * 64, 2 * jj, bar(B_X + jj));
                if (!kv_cta && jj < 2) {
                    mbar_expect_tx(bar(B_W + jj), 32768);
                    tma4d(sb + OFF_V + jj * 32768, &tm_wq, 0, 0, hg * 2, 2 * jj, bar(B_W + jj));
                }
            }
            if (kv_cta) {
                for (int jj = 0; jj < 2; jj++) {
                    mbar_expect_tx(bar(B_W + jj), 32768);
                    tma4d(sb + OFF_V + jj * 32768, &tm_wq, 0, 0, hg * 2, 2 * jj, bar(B_W + jj));
                }
            }
            TSTAMP(25);
        }
        __syncwarp();
        if (kv_cta) {
            float acc[16];
#pragma unroll
            for (int i = 0; i < 16; i++) acc[i] = 0.f;
            fence_regs<16>(acc);
            mbar_wait_w(bar(B_WKV), 0);
            if (tau == 0) TSTAMP(20);
#pragma unroll
            for (int jj = 0; jj < 4; jj++) {
                mbar_wait_w(bar(B_X + jj), 0);
                wg_fence();
#pragma unroll
                for (int j = 2 * jj; j < 2 * jj + 2; j++) {
                    const uint64_t da = make_desc(sb + OFF_X + j * 8192, 16, 1024, 1);
                    const uint64_t db = make_desc(sb + OFF_C + j * 2048, 16384, 256, 3);
#pragma unroll
                    for (int ks = 0; ks < 4; ks++) wg_ss_n32_tb(acc, da + ks * 2, db + ks * 32);
                }
                wg_commit();
            }
            wg_wait<0>();
            fence_regs<16>(acc);
            if (tau == 0) TSTAMP(22);
            {
                uint32_t kk[4], vv[4];
#pragma unroll
                for (int i = 0; i < 4; i++) { kk[i] = pack_bf16(acc[2 * i], acc[2 * i + 1]); vv[i] = pack_bf16(acc[8 + 2 * i], acc[8 + 2 * i + 1]); }
                const int s = 4 * pb + wa;
                uint32_t* kp = (uint32_t*)(g_kimg + s * 512 + g * 16 + 4 * t);
                kp[0] = kk[0]; kp[64] = kk[1]; kp[32] = kk[2]; kp[96] = kk[3];
                uint32_t* vlo = (uint32_t*)(g_vimg + (127 - s) * 256 + g * 16 + 4 * t);
                uint32_t* vhi = (uint32_t*)(g_vimg + 32768 + 256 + s * 256 + g * 16 + 4 * t);
                vlo[0] = pack_f16(bf_lo(vv[0]), bf_hi(vv[0])); vlo[32] = pack_f16(bf_lo(vv[1]), bf_hi(vv[1]));
                vhi[0] = pack_f16(bf_lo(vv[2]), bf_hi(vv[2])); vhi[32] = pack_f16(bf_lo(vv[3]), bf_hi(vv[3]));
                uint32_t* vr = (uint32_t*)(g_vraw + (size_t)(16 * s + g) * 16) + t;
                vr[0] = vv[0]; vr[64] = vv[1]; vr[4] = vv[2]; vr[68] = vv[3];
                float n0 = bf_lo(kk[0]) * bf_lo(kk[0]) + bf_hi(kk[0]) * bf_hi(kk[0]) + bf_lo(kk[2]) * bf_lo(kk[2]) + bf_hi(kk[2]) * bf_hi(kk[2]);
                float n1 = bf_lo(kk[1]) * bf_lo(kk[1]) + bf_hi(kk[1]) * bf_hi(kk[1]) + bf_lo(kk[3]) * bf_lo(kk[3]) + bf_hi(kk[3]) * bf_hi(kk[3]);
                n0 += __shfl_xor_sync(0xffffffffu, n0, 1); n0 += __shfl_xor_sync(0xffffffffu, n0, 2);
                n1 += __shfl_xor_sync(0xffffffffu, n1, 1); n1 += __shfl_xor_sync(0xffffffffu, n1, 2);
                float km = fmaxf(n0, n1), vm = 0.f;
#pragma unroll
                for (int i = 0; i < 4; i++) vm = fmaxf(vm, fmaxf(fabsf(bf_lo(vv[i])), fabsf(bf_hi(vv[i]))));
#pragma unroll
                for (int o = 4; o < 32; o <<= 1) km = fmaxf(km, __shfl_xor_sync(0xffffffffu, km, o));
#pragma unroll
                for (int o = 1; o < 32; o <<= 1) vm = fmaxf(vm, __shfl_xor_sync(0xffffffffu, vm, o));
                if (lane == 0) g_stats[s] = make_float2(km, vm);
                __syncwarp();
                if (lane == 0) { red_release_add(&g_kv_count, 1); if (wa == 0) TSTAMP(8); }
            }
        }
        const int c0 = 4 * b;
        if (wa == 0) {
            if (lane == 0) {
                for (int jj = 2; jj < 4; jj++) {
                    mbar_wait(bar(B_QEMPTY + jj - 2), 0);
                    mbar_expect_tx(bar(B_W + jj), 32768);
                    tma4d(sb + OFF_V + (jj - 2) * 32768, &tm_wq, 0, 0, hg * 2, 2 * jj, bar(B_W + jj));
                }
                poll_counter(&g_kv_count, NCTA);
                TSTAMP(16);
            }
            __syncwarp();
            float km = 0.f, vm = 0.f;
#pragma unroll
            for (int i = 0; i < 4; i++) { const float2 st = __ldcg(&g_stats[lane + 32 * i]); km = fmaxf(km, st.x); vm = fmaxf(vm, st.y); }
#pragma unroll
            for (int o = 1; o < 32; o <<= 1) { km = fmaxf(km, __shfl_xor_sync(0xffffffffu, km, o)); vm = fmaxf(vm, __shfl_xor_sync(0xffffffffu, vm, o)); }
            const bool vdirect = (vm <= 32768.f && vm >= 9.765625e-4f) || vm == 0.f;
            float vs = 1.f;
            if (!vdirect && vm < INFINITY) {
                int e = (int)((__float_as_uint(vm) >> 23) & 0xFF) - 127;
                e = max(-100, min(100, e));
                vs = __uint_as_float((uint32_t)(127 + e - 13) << 23);
            }
            if (lane == 0) {
                fence_async_global();
                for (int c = 0; c < 8; c++) {
                    mbar_expect_tx(bar(B_KV + c), vdirect ? 16384 : 8192);
                    bulk_g2s(sb + OFF_K + c * 8192, g_kimg + c * 8192, 8192, bar(B_KV + c));
                }
                asm volatile("st.shared.f32 [%0], %1;" ::"r"(sb + OFF_MISC), "f"(km) : "memory");
                asm volatile("st.shared.f32 [%0], %1;" ::"r"(sb + OFF_MISC + 4), "f"(vs) : "memory");
                TSTAMP(28);
                mbar_wait(bar(B_QDONE), 0);
                TSTAMP(17);
                if (vdirect) {
                    for (int c = 0; c < 8; c++) {
                        bulk_g2s(sb + OFF_V + (112 - 16 * c) * 256, g_vimg + (112 - 16 * c) * 256, 4096, bar(B_KV + c));
                        bulk_g2s(sb + OFF_VONES + 256 + c * 4096, g_vimg + 32768 + 256 + c * 4096, 4096, bar(B_KV + c));
                    }
                }
            }
            __syncwarp();
            sts32(sb + OFF_VONES + lane * 8, 0x3C003C00u);
            sts32(sb + OFF_VONES + lane * 8 + 4, 0x3C003C00u);
            if (!vdirect) {
                const float inv = 1.f / vs;
                for (int idx = lane; idx < S_LEN * 8; idx += 32) {
                    const int key = idx >> 3, dp = idx & 7;
                    const uint32_t v = __ldcg((const uint32_t*)g_vraw + idx);
                    const uint32_t h = pack_f16(bf_lo(v) * inv, bf_hi(v) * inv);
                    const int st = key >> 4, hf = (key >> 3) & 1;
                    const uint32_t base = (dp < 4) ? (OFF_V + (127 - st) * 256) : (OFF_VONES + 256 + st * 256);
                    sts32(sb + base + hf * 128 + (key & 7) * 16 + (dp & 3) * 4, h);
                }
            }
            fence_async_smem();
            __syncwarp();
            if (lane == 0) {
                mbar_arrive(bar(B_KV + 0));
                prefetch_tm(&tm_wo); prefetch_tm(&tm_o);
                for (int jj = 0; jj < 2; jj++) {
                    mbar_expect_tx(bar(B_WO + jj), 32768);
                    tma4d(sb + OFF_X + jj * 32768, &tm_wo, 0, 0, hg * 2, 2 * jj, bar(B_WO + jj));
                }
            }
            __syncwarp();
        } else if (wa == 1) {
            if (lane == 0) {
                mbar_expect_tx(bar(B_H), 4096);
                tma2d(sb + C_H + 1024, &tm_h, 0, c0 * 64, bar(B_H));
                poll_counter(&g_kvt_count[b >> 5], 32);
                fence_async_global();
                mbar_expect_tx(bar(B_CV), 16384);
                bulk_g2s(sb + C_KVC, g_kvT + (size_t)c0 * S_LEN, 16384, bar(B_CV));
            }
            __syncwarp();
        } else {
            sts128(sb + C_H + (tau - 64) * 16, 0u, 0u, 0u, 0u);
            fence_async_smem();
        }
        named_bar(5, 128);
        mbar_wait_w(bar(B_CV), 0);
        if (tau == 0) TSTAMP(9);
        const int NCH = 4;
#pragma unroll 1
        for (int ch = 0; ch < NCH; ch++) {
            {
                const uint32_t src = sb + C_KVC + ch * 4096 + tau * 32;
                const uint4 u0 = lds128(src), u1 = lds128(src + 16);
                const uint32_t prev = tau > 0 ? lds32(src - 4) : 0u;
                const uint32_t zd = sb + C_Z + (32 + tau * 16) * 4;
                sts128(zd,      __byte_perm(u0.x, prev, 0x7610), __byte_perm(u0.x, u0.x, 0x1032), __byte_perm(u0.y, u0.x, 0x7610), __byte_perm(u0.y, u0.y, 0x1032));
                sts128(zd + 16, __byte_perm(u0.z, u0.y, 0x7610), __byte_perm(u0.z, u0.z, 0x1032), __byte_perm(u0.w, u0.z, 0x7610), __byte_perm(u0.w, u0.w, 0x1032));
                sts128(zd + 32, __byte_perm(u1.x, u0.w, 0x7610), __byte_perm(u1.x, u1.x, 0x1032), __byte_perm(u1.y, u1.x, 0x7610), __byte_perm(u1.y, u1.y, 0x1032));
                sts128(zd + 48, __byte_perm(u1.z, u1.y, 0x7610), __byte_perm(u1.z, u1.z, 0x1032), __byte_perm(u1.w, u1.z, 0x7610), __byte_perm(u1.w, u1.w, 0x1032));
                if (tau < 32) sts32(sb + C_Z + tau * 4, 0u);
            }
            named_bar(5, 128);
            mbar_wait_w(bar(B_H), ch & 1);
            float D[32];
#pragma unroll
            for (int i = 0; i < 32; i++) D[i] = 0.f;
            const uint32_t z0 = sb + C_Z + (32 + 32 * (wa >> 1) + 16 * (wa & 1) + g - 2 * t) * 4;
            const uint64_t hd = make_desc(sb + C_H + 1024, 16, 512, 2);
            conv_group<64>(D, z0 + 0 * 2048, hd);
            conv_group<48>(D, z0 + 1 * 2048, hd);
            conv_group<32>(D, z0 + 2 * 2048, hd);
            conv_group<16>(D, z0 + 3 * 2048, hd);
            if (tau == 0 && ch < 3) {
                mbar_expect_tx(bar(B_H), 4096);
                tma2d(sb + C_H + 1024, &tm_h, 0, (c0 + ch + 1) * 64, bar(B_H));
            }
            if (wa >= 2) {
#pragma unroll
                for (int jn = 0; jn < 8; jn++) {
#pragma unroll
                    for (int r = 0; r < 2; r++) {
                        const int bb = 16 * (wa & 1) + g + 8 * r;
                        const int n = 8 * jn + 2 * t;
                        sts64f(sb + C_Z + (bb * 64 + (n ^ ((bb & 3) << 3))) * 4, D[4 * jn + 2 * r], D[4 * jn + 2 * r + 1]);
                    }
                }
            }
            named_bar(5, 128);
            if (wa < 2) {
                const float dsc = __bfloat162float(prm.ssm_D[c0 + ch]);
#pragma unroll
                for (int jn = 0; jn < 8; jn++) {
#pragma unroll
                    for (int r = 0; r < 2; r++) {
                        const int bb = 16 * wa + g + 8 * r;
#pragma unroll
                        for (int e = 0; e < 2; e++) {
                            const int m = 8 * jn + 2 * t + e;
                            float y = D[4 * jn + 2 * r + e];
                            if (m > 0) y += ldsf(sb + C_Z + (bb * 64 + ((m - 1) ^ ((bb & 3) << 3))) * 4);
                            const uint32_t addr = sb + C_KVC + ch * 4096 + (32 * m + bb) * 2;
                            const float kv = __uint_as_float(lds16(addr) << 16);
                            const float yb = __bfloat162float(__float2bfloat16_rn(y));
                            const float kd = __bfloat162float(__float2bfloat16_rn(kv * dsc));
                            sts16(addr, (uint32_t)__bfloat16_as_ushort(__float2bfloat16_rn(yb + kd)));
                        }
                    }
                }
                fence_async_smem();
            }
            named_bar(5, 128);
            if (tau == 0) {
                bulk_s2g(g_zT + (size_t)(c0 + ch) * S_LEN, sb + C_KVC + ch * 4096, 4096);
                bulk_commit();
                TSTAMP(10 + ch);
            }
        }
        {
            const int cg = tau & 15, pr = tau >> 4;
            const int p0 = pb * 64 + pr * 8, ch0 = hg * 128 + cg * 8;
            uint4 qr[8];
#pragma unroll
            for (int i = 0; i < 8; i++) qr[i] = __ldg((const uint4*)(prm.aq + (size_t)(p0 + i) * 512 + ch0));
            if (tau == 0) {
                bulk_wait_all();
                mbar_expect_tx(bar(B_WO + 3), 32768);
                tma4d(sb + OFF_C, &tm_wo, 0, 0, hg * 2, 6, bar(B_WO + 3));
                fence_async_global();
                red_release_add(&g_z_count[b >> 5], 1);
                poll_counter(&g_z_count[hg], 32);
                __threadfence();
                if (atomicAdd(&g_done, 1) == 2 * NCTA - 1) {
                    g_kv_count = 0;
                    for (int i = 0; i < 4; i++) { g_kvt_count[i] = 0; g_z_count[i] = 0; }
                    for (int i = 0; i < 32; i++) g_o_count[i] = 0;
                    g_done = 0;
                    __threadfence();
                }
            }
            named_bar(5, 128);
            uint4 zz[8];
#pragma unroll
            for (int c = 0; c < 8; c++) zz[c] = __ldcg((const uint4*)(g_zT + (size_t)(ch0 + c) * S_LEN + p0));
#pragma unroll
            for (int i = 0; i < 8; i++) {
                uint32_t r[4];
#pragma unroll
                for (int k = 0; k < 4; k++) {
                    const uint32_t pr2 = __byte_perm((&zz[2 * k].x)[i >> 1], (&zz[2 * k + 1].x)[i >> 1], (i & 1) ? 0x7632 : 0x5410);
                    r[k] = bmul2((&qr[i].x)[k], pr2);
                }
                *(uint4*)(prm.out + (size_t)(p0 + i) * 1024 + ch0) = make_uint4(r[0], r[1], r[2], r[3]);
            }
        }
        if (tau == 0) TSTAMP(14);
    }
}

typedef CUresult (*EncodeFn)(CUtensorMap*, CUtensorMapDataType, cuuint32_t, void*, const cuuint64_t*, const cuuint64_t*,
                             const cuuint32_t*, const cuuint32_t*, CUtensorMapInterleave, CUtensorMapSwizzle,
                             CUtensorMapL2promotion, CUtensorMapFloatOOBfill);

void make_map(EncodeFn fn, CUtensorMap* tm, const void* ptr, int rank, const cuuint64_t* dims, const cuuint64_t* strides, const cuuint32_t* box, CUtensorMapSwizzle swz) {
    cuuint32_t es[4] = {1, 1, 1, 1};
    fn(tm, CU_TENSOR_MAP_DATA_TYPE_BFLOAT16, rank, const_cast<void*>(ptr), dims, strides, box, es, CU_TENSOR_MAP_INTERLEAVE_NONE, swz,
       CU_TENSOR_MAP_L2_PROMOTION_L2_128B, CU_TENSOR_MAP_FLOAT_OOB_FILL_NONE);
}

}

extern "C" void kernel_launch(void* const* d_in, const int* in_sizes, int n_in, void* d_out, int out_size) {
    (void)in_sizes; (void)n_in; (void)out_size;
    static EncodeFn encode = nullptr;
    static void* o_ptr = nullptr;
    if (!encode) {
        cudaDriverEntryPointQueryResult qres;
        void* fn = nullptr;
        cudaGetDriverEntryPoint("cuTensorMapEncodeTiled", &fn, cudaEnableDefault, &qres);
        encode = (EncodeFn)fn;
        cudaGetSymbolAddress(&o_ptr, g_o);
        cudaFuncSetAttribute(fused_kernel, cudaFuncAttributeMaxDynamicSharedMemorySize, SMEM_TOTAL);
    }
    CUtensorMap tm_x, tm_wq, tm_wo, tm_wk, tm_wv, tm_o, tm_h;
    {
        const cuuint64_t dims[3] = {64, 2048, 8}, str[2] = {1024, 128};
        const cuuint32_t b64[3] = {64, 64, 2};
        make_map(encode, &tm_x, d_in[6], 3, dims, str, b64, CU_TENSOR_MAP_SWIZZLE_128B);
        make_map(encode, &tm_o, o_ptr, 3, dims, str, b64, CU_TENSOR_MAP_SWIZZLE_128B);
    }
    {
        const cuuint64_t dims[4] = {64, 64, 8, 8}, str[3] = {1024, 128, 65536};
        const cuuint32_t box[4] = {64, 64, 2, 2};
        make_map(encode, &tm_wq, d_in[7], 4, dims, str, box, CU_TENSOR_MAP_SWIZZLE_128B);
        make_map(encode, &tm_wo, d_in[10], 4, dims, str, box, CU_TENSOR_MAP_SWIZZLE_128B);
    }
    {
        const cuuint64_t dims[3] = {16, 256, 2}, str[2] = {32, 8192};
        const cuuint32_t box[3] = {16, 256, 2};
        make_map(encode, &tm_wk, d_in[8], 3, dims, str, box, CU_TENSOR_MAP_SWIZZLE_32B);
        make_map(encode, &tm_wv, d_in[9], 3, dims, str, box, CU_TENSOR_MAP_SWIZZLE_32B);
    }
    {
        const cuuint64_t dims[2] = {32, 512 * 64}, str[1] = {64};
        const cuuint32_t box[2] = {32, 64};
        make_map(encode, &tm_h, d_in[4], 2, dims, str, box, CU_TENSOR_MAP_SWIZZLE_64B);
    }
    Params prm;
    prm.aq = (const __nv_bfloat16*)d_in[0];
    prm.ak = (const __nv_bfloat16*)d_in[1];
    prm.av = (const __nv_bfloat16*)d_in[2];
    prm.shift_k = (const __nv_bfloat16*)d_in[3];
    prm.ssm_D = (const __nv_bfloat16*)d_in[5];
    prm.out = (__nv_bfloat16*)d_out;
    fused_kernel<<<NCTA, NTHREADS, SMEM_TOTAL>>>(tm_x, tm_wq, tm_wo, tm_wk, tm_wv, tm_o, tm_h, prm);
}
```

```cpp
#include <cuda_runtime.h>
#include <cuda_bf16.h>
#include <cuda_fp16.h>
#include <cuda.h>
#include <stdint.h>

namespace {

constexpr int S_LEN = 2048;
constexpr int NCTA = 128;
constexpr int NTHREADS = 640;

constexpr uint32_t OFF_K = 0;
constexpr uint32_t OFF_V = 65536;
constexpr uint32_t OFF_VONES = OFF_V + 32768;
constexpr uint32_t OFF_X = 132096;
constexpr uint32_t OFF_C = 197632;
constexpr uint32_t C_KVC = OFF_C;
constexpr uint32_t C_H = OFF_C + 16384;
constexpr uint32_t C_Z = C_H + 5120;
constexpr uint32_t OFF_BAR = 231936;
constexpr uint32_t SMEM_TOTAL = 232448;

enum { B_WKV = 0, B_X = 1, B_QEMPTY = 5, B_QDONE = 7, B_KV = 8, B_WO = 16, B_O = 20, B_ATT = 24, B_H = 25, B_CV = 26, B_W = 27, B_COUNT = 31 };
constexpr uint32_t OFF_MISC = OFF_BAR + 8 * B_COUNT;

__device__ __align__(1024) uint8_t g_kimg[65536];
__device__ __align__(1024) uint8_t g_vimg[65792];
__device__ __align__(1024) __nv_bfloat16 g_vraw[S_LEN * 16];
__device__ __align__(1024) __nv_bfloat16 g_o[S_LEN * 512];
__device__ __align__(1024) __nv_bfloat16 g_kvT[512 * S_LEN];
__device__ __align__(1024) __nv_bfloat16 g_zT[512 * S_LEN];
__device__ float2 g_stats[NCTA];
__device__ unsigned int g_kv_count;
__device__ unsigned int g_kvt_count[4];
__device__ unsigned int g_z_count[4];
__device__ unsigned int g_o_count[32];
__device__ unsigned int g_done;
#define TSTAMP(i) do {} while (0)
#define CSTAMP(i) do {} while (0)

__device__ __forceinline__ void wg_fence() { asm volatile("wgmma.fence.sync.aligned;" ::: "memory"); }
__device__ __forceinline__ void wg_commit() { asm volatile("wgmma.commit_group.sync.aligned;" ::: "memory"); }
template <int N> __device__ __forceinline__ void wg_wait() { asm volatile("wgmma.wait_group.sync.aligned %0;" ::"n"(N) : "memory"); }
template <int N> __device__ __forceinline__ void fence_regs(float* r) {
#pragma unroll
    for (int i = 0; i < N; i++) asm volatile("" : "+f"(r[i])::"memory");
}
template <int N> __device__ __forceinline__ void fence_uregs(uint32_t* r) {
#pragma unroll
    for (int i = 0; i < N; i++) asm volatile("" : "+r"(r[i])::"memory");
}
__device__ __forceinline__ uint64_t make_desc(uint32_t saddr, uint32_t lbo, uint32_t sbo, uint32_t swz) {
    return (uint64_t)((saddr & 0x3FFFF) >> 4) | ((uint64_t)(lbo >> 4) << 16) | ((uint64_t)(sbo >> 4) << 32) | ((uint64_t)swz << 62);
}
__device__ __forceinline__ void mbar_init(uint32_t bar, uint32_t count) {
    asm volatile("mbarrier.init.shared::cta.b64 [%0], %1;" ::"r"(bar), "r"(count) : "memory");
}
__device__ __forceinline__ void mbar_expect_tx(uint32_t bar, uint32_t bytes) {
    asm volatile("mbarrier.arrive.expect_tx.shared::cta.b64 _, [%0], %1;" ::"r"(bar), "r"(bytes) : "memory");
}
__device__ __forceinline__ void mbar_expect_tx_noarrive(uint32_t bar, uint32_t bytes) {
    asm volatile("mbarrier.expect_tx.relaxed.cta.shared::cta.b64 [%0], %1;" ::"r"(bar), "r"(bytes) : "memory");
}
__device__ __forceinline__ void mbar_arrive(uint32_t bar) {
    asm volatile("mbarrier.arrive.shared::cta.b64 _, [%0];" ::"r"(bar) : "memory");
}
__device__ __forceinline__ bool mbar_try(uint32_t bar, uint32_t parity) {
    uint32_t ok;
    asm volatile("{\n.reg .pred p;\nmbarrier.try_wait.parity.shared::cta.b64 p, [%1], %2;\nselp.u32 %0, 1, 0, p;\n}\n"
                 : "=r"(ok) : "r"(bar), "r"(parity) : "memory");
    return ok != 0;
}
__device__ __forceinline__ void mbar_wait(uint32_t bar, uint32_t parity) {
    uint32_t spins = 0;
    while (!mbar_try(bar, parity)) {
        if (++spins > (1u << 24)) __trap();
    }
}
__device__ __forceinline__ void mbar_wait_w(uint32_t bar, uint32_t parity) {
    uint32_t spins = 0;
    while (!__all_sync(0xffffffffu, mbar_try(bar, parity))) {
        if (++spins > (1u << 24)) __trap();
    }
}
__device__ __forceinline__ void tma2d(uint32_t dst, const CUtensorMap* tm, int c0, int c1, uint32_t bar) {
    asm volatile("cp.async.bulk.tensor.2d.shared::cluster.global.mbarrier::complete_tx::bytes [%0], [%1, {%3, %4}], [%2];"
                 ::"r"(dst), "l"((uint64_t)tm), "r"(bar), "r"(c0), "r"(c1) : "memory");
}
__device__ __forceinline__ void tma3d(uint32_t dst, const CUtensorMap* tm, int c0, int c1, int c2, uint32_t bar) {
    asm volatile("cp.async.bulk.tensor.3d.shared::cluster.global.mbarrier::complete_tx::bytes [%0], [%1, {%3, %4, %5}], [%2];"
                 ::"r"(dst), "l"((uint64_t)tm), "r"(bar), "r"(c0), "r"(c1), "r"(c2) : "memory");
}
__device__ __forceinline__ void tma4d(uint32_t dst, const CUtensorMap* tm, int c0, int c1, int c2, int c3, uint32_t bar) {
    asm volatile("cp.async.bulk.tensor.4d.shared::cluster.global.mbarrier::complete_tx::bytes [%0], [%1, {%3, %4, %5, %6}], [%2];"
                 ::"r"(dst), "l"((uint64_t)tm), "r"(bar), "r"(c0), "r"(c1), "r"(c2), "r"(c3) : "memory");
}
__device__ __forceinline__ void prefetch_tm(const CUtensorMap* tm) { asm volatile("prefetch.tensormap [%0];" ::"l"((uint64_t)tm) : "memory"); }
__device__ __forceinline__ void bulk_s2g(void* dst, uint32_t src, uint32_t bytes) {
    asm volatile("cp.async.bulk.global.shared::cta.bulk_group [%0], [%1], %2;" ::"l"(dst), "r"(src), "r"(bytes) : "memory");
}
__device__ __forceinline__ void bulk_commit() { asm volatile("cp.async.bulk.commit_group;" ::: "memory"); }
__device__ __forceinline__ void bulk_wait_all() { asm volatile("cp.async.bulk.wait_group 0;" ::: "memory"); }
__device__ __forceinline__ void fence_async_global() { asm volatile("fence.proxy.async.global;" ::: "memory"); }
__device__ __forceinline__ void bulk_g2s(uint32_t dst, const void* src, uint32_t bytes, uint32_t bar) {
    asm volatile("cp.async.bulk.shared::cluster.global.mbarrier::complete_tx::bytes [%0], [%1], %2, [%3];"
                 ::"r"(dst), "l"(src), "r"(bytes), "r"(bar) : "memory");
}
__device__ __forceinline__ void fence_async_smem() { asm volatile("fence.proxy.async.shared::cta;" ::: "memory"); }
__device__ __forceinline__ void named_bar(int id, int n) { asm volatile("bar.sync %0, %1;" ::"r"(id), "r"(n) : "memory"); }
__device__ __forceinline__ bool named_bar_and(int id, int n, bool pred) {
    uint32_t r;
    asm volatile("{\n.reg .pred p, q;\nsetp.ne.u32 p, %3, 0;\nbarrier.cta.red.and.pred q, %1, %2, p;\nselp.u32 %0, 1, 0, q;\n}\n"
                 : "=r"(r) : "r"(id), "r"(n), "r"((uint32_t)pred) : "memory");
    return r != 0;
}
__device__ __forceinline__ unsigned int ld_acquire(const unsigned int* p) {
    unsigned int v;
    asm volatile("ld.acquire.gpu.global.u32 %0, [%1];" : "=r"(v) : "l"(p) : "memory");
    return v;
}
__device__ __forceinline__ void red_release_add(unsigned int* p, unsigned int v) {
    asm volatile("red.release.gpu.global.add.u32 [%0], %1;" ::"l"(p), "r"(v) : "memory");
}
__device__ __forceinline__ void poll_counter(const unsigned int* p, unsigned int target) {
    uint32_t spins = 0;
    while (ld_acquire(p) < target) {
        if (++spins > (1u << 22)) __trap();
    }
}
__device__ __forceinline__ float ex2f(float x) { float y; asm("ex2.approx.ftz.f32 %0, %1;" : "=f"(y) : "f"(x)); return y; }
__device__ __forceinline__ uint32_t pack_f16(float lo, float hi) { uint32_t r; asm("cvt.rn.f16x2.f32 %0, %1, %2;" : "=r"(r) : "f"(hi), "f"(lo)); return r; }
__device__ __forceinline__ uint32_t pack_bf16(float lo, float hi) { uint32_t r; asm("cvt.rn.bf16x2.f32 %0, %1, %2;" : "=r"(r) : "f"(hi), "f"(lo)); return r; }
__device__ __forceinline__ float bf_lo(uint32_t v) { return __uint_as_float(v << 16); }
__device__ __forceinline__ float bf_hi(uint32_t v) { return __uint_as_float(v & 0xFFFF0000u); }
__device__ __forceinline__ uint32_t hfma2(uint32_t a, uint32_t b, uint32_t c) { uint32_t r; asm("fma.rn.f16x2 %0, %1, %2, %3;" : "=r"(r) : "r"(a), "r"(b), "r"(c)); return r; }
__device__ __forceinline__ uint32_t bmul2(uint32_t a, uint32_t b) { uint32_t r; asm("mul.rn.bf16x2 %0, %1, %2;" : "=r"(r) : "r"(a), "r"(b)); return r; }
__device__ __forceinline__ uint32_t badd2(uint32_t a, uint32_t b) { uint32_t r; asm("add.rn.bf16x2 %0, %1, %2;" : "=r"(r) : "r"(a), "r"(b)); return r; }
template <int LUT> __device__ __forceinline__ uint32_t lop3(uint32_t a, uint32_t b, uint32_t c) {
    uint32_t r; asm("lop3.b32 %0, %1, %2, %3, %4;" : "=r"(r) : "r"(a), "r"(b), "r"(c), "n"(LUT)); return r;
}
__device__ __forceinline__ uint32_t lds32(uint32_t a) { uint32_t v; asm volatile("ld.shared.u32 %0, [%1];" : "=r"(v) : "r"(a)); return v; }
__device__ __forceinline__ float ldsf(uint32_t a) { float v; asm volatile("ld.shared.f32 %0, [%1];" : "=f"(v) : "r"(a)); return v; }
__device__ __forceinline__ uint32_t lds16(uint32_t a) { uint16_t v; asm volatile("ld.shared.u16 %0, [%1];" : "=h"(v) : "r"(a)); return v; }
__device__ __forceinline__ uint4 lds128(uint32_t a) { uint4 v; asm volatile("ld.shared.v4.u32 {%0,%1,%2,%3}, [%4];" : "=r"(v.x), "=r"(v.y), "=r"(v.z), "=r"(v.w) : "r"(a)); return v; }
__device__ __forceinline__ void sts32(uint32_t a, uint32_t v) { asm volatile("st.shared.u32 [%0], %1;" ::"r"(a), "r"(v) : "memory"); }
__device__ __forceinline__ void sts16(uint32_t a, uint32_t v) { asm volatile("st.shared.u16 [%0], %1;" ::"r"(a), "h"((uint16_t)v) : "memory"); }
__device__ __forceinline__ void sts64f(uint32_t a, float x, float y) { asm volatile("st.shared.v2.f32 [%0], {%1,%2};" ::"r"(a), "f"(x), "f"(y) : "memory"); }
__device__ __forceinline__ void sts128(uint32_t a, uint32_t x, uint32_t y, uint32_t z, uint32_t w) {
    asm volatile("st.shared.v4.u32 [%0], {%1,%2,%3,%4};" ::"r"(a), "r"(x), "r"(y), "r"(z), "r"(w) : "memory");
}

__device__ __forceinline__ void wg_ss_n32_tb(float* d, uint64_t descA, uint64_t descB) {
    asm volatile("wgmma.mma_async.sync.aligned.m64n32k16.f32.bf16.bf16 {%0,%1,%2,%3,%4,%5,%6,%7,%8,%9,%10,%11,%12,%13,%14,%15}, %16, %17, 1, 1, 1, 0, 1;\n"
        : "+f"(d[0]), "+f"(d[1]), "+f"(d[2]), "+f"(d[3]), "+f"(d[4]), "+f"(d[5]), "+f"(d[6]), "+f"(d[7]), "+f"(d[8]), "+f"(d[9]), "+f"(d[10]), "+f"(d[11]), "+f"(d[12]), "+f"(d[13]), "+f"(d[14]), "+f"(d[15])
        : "l"(descA), "l"(descB));
}
__device__ __forceinline__ void wg_qk_n64(float* d, const uint32_t* a, uint64_t desc) {
    asm volatile("wgmma.mma_async.sync.aligned.m64n64k16.f32.bf16.bf16 {%0,%1,%2,%3,%4,%5,%6,%7,%8,%9,%10,%11,%12,%13,%14,%15,%16,%17,%18,%19,%20,%21,%22,%23,%24,%25,%26,%27,%28,%29,%30,%31}, {%32,%33,%34,%35}, %36, 0, 1, 1, 0;\n"
        : "+f"(d[0]), "+f"(d[1]), "+f"(d[2]), "+f"(d[3]), "+f"(d[4]), "+f"(d[5]), "+f"(d[6]), "+f"(d[7]), "+f"(d[8]), "+f"(d[9]), "+f"(d[10]), "+f"(d[11]), "+f"(d[12]), "+f"(d[13]), "+f"(d[14]), "+f"(d[15]), "+f"(d[16]), "+f"(d[17]), "+f"(d[18]), "+f"(d[19]), "+f"(d[20]), "+f"(d[21]), "+f"(d[22]), "+f"(d[23]), "+f"(d[24]), "+f"(d[25]), "+f"(d[26]), "+f"(d[27]), "+f"(d[28]), "+f"(d[29]), "+f"(d[30]), "+f"(d[31])
        : "r"(a[0]), "r"(a[1]), "r"(a[2]), "r"(a[3]), "l"(desc));
}
__device__ __forceinline__ void wg_pv_n24(float* d, const uint32_t* a, uint64_t desc) {
    asm volatile("wgmma.mma_async.sync.aligned.m64n24k16.f32.f16.f16 {%0,%1,%2,%3,%4,%5,%6,%7,%8,%9,%10,%11}, {%12,%13,%14,%15}, %16, 1, 1, 1, 1;\n"
        : "+f"(d[0]), "+f"(d[1]), "+f"(d[2]), "+f"(d[3]), "+f"(d[4]), "+f"(d[5]), "+f"(d[6]), "+f"(d[7]), "+f"(d[8]), "+f"(d[9]), "+f"(d[10]), "+f"(d[11])
        : "r"(a[0]), "r"(a[1]), "r"(a[2]), "r"(a[3]), "l"(desc));
}
__device__ __forceinline__ void wg_cv_n16(float* d, const uint32_t* a, uint64_t desc) {
    asm volatile("wgmma.mma_async.sync.aligned.m64n16k16.f32.bf16.bf16 {%0,%1,%2,%3,%4,%5,%6,%7}, {%8,%9,%10,%11}, %12, 1, 1, 1, 0;\n"
        : "+f"(d[0]), "+f"(d[1]), "+f"(d[2]), "+f"(d[3]), "+f"(d[4]), "+f"(d[5]), "+f"(d[6]), "+f"(d[7])
        : "r"(a[0]), "r"(a[1]), "r"(a[2]), "r"(a[3]), "l"(desc));
}
__device__ __forceinline__ void wg_cv_n32(float* d, const uint32_t* a, uint64_t desc) {
    asm volatile("wgmma.mma_async.sync.aligned.m64n32k16.f32.bf16.bf16 {%0,%1,%2,%3,%4,%5,%6,%7,%8,%9,%10,%11,%12,%13,%14,%15}, {%16,%17,%18,%19}, %20, 1, 1, 1, 0;\n"
        : "+f"(d[0]), "+f"(d[1]), "+f"(d[2]), "+f"(d[3]), "+f"(d[4]), "+f"(d[5]), "+f"(d[6]), "+f"(d[7]), "+f"(d[8]), "+f"(d[9]), "+f"(d[10]), "+f"(d[11]), "+f"(d[12]), "+f"(d[13]), "+f"(d[14]), "+f"(d[15])
        : "r"(a[0]), "r"(a[1]), "r"(a[2]), "r"(a[3]), "l"(desc));
}
__device__ __forceinline__ void wg_cv_n48(float* d, const uint32_t* a, uint64_t desc) {
    asm volatile("wgmma.mma_async.sync.aligned.m64n48k16.f32.bf16.bf16 {%0,%1,%2,%3,%4,%5,%6,%7,%8,%9,%10,%11,%12,%13,%14,%15,%16,%17,%18,%19,%20,%21,%22,%23}, {%24,%25,%26,%27}, %28, 1, 1, 1, 0;\n"
        : "+f"(d[0]), "+f"(d[1]), "+f"(d[2]), "+f"(d[3]), "+f"(d[4]), "+f"(d[5]), "+f"(d[6]), "+f"(d[7]), "+f"(d[8]), "+f"(d[9]), "+f"(d[10]), "+f"(d[11]), "+f"(d[12]), "+f"(d[13]), "+f"(d[14]), "+f"(d[15]), "+f"(d[16]), "+f"(d[17]), "+f"(d[18]), "+f"(d[19]), "+f"(d[20]), "+f"(d[21]), "+f"(d[22]), "+f"(d[23])
        : "r"(a[0]), "r"(a[1]), "r"(a[2]), "r"(a[3]), "l"(desc));
}
__device__ __forceinline__ void wg_cv_n64(float* d, const uint32_t* a, uint64_t desc) {
    asm volatile("wgmma.mma_async.sync.aligned.m64n64k16.f32.bf16.bf16 {%0,%1,%2,%3,%4,%5,%6,%7,%8,%9,%10,%11,%12,%13,%14,%15,%16,%17,%18,%19,%20,%21,%22,%23,%24,%25,%26,%27,%28,%29,%30,%31}, {%32,%33,%34,%35}, %36, 1, 1, 1, 0;\n"
        : "+f"(d[0]), "+f"(d[1]), "+f"(d[2]), "+f"(d[3]), "+f"(d[4]), "+f"(d[5]), "+f"(d[6]), "+f"(d[7]), "+f"(d[8]), "+f"(d[9]), "+f"(d[10]), "+f"(d[11]), "+f"(d[12]), "+f"(d[13]), "+f"(d[14]), "+f"(d[15]), "+f"(d[16]), "+f"(d[17]), "+f"(d[18]), "+f"(d[19]), "+f"(d[20]), "+f"(d[21]), "+f"(d[22]), "+f"(d[23]), "+f"(d[24]), "+f"(d[25]), "+f"(d[26]), "+f"(d[27]), "+f"(d[28]), "+f"(d[29]), "+f"(d[30]), "+f"(d[31])
        : "r"(a[0]), "r"(a[1]), "r"(a[2]), "r"(a[3]), "l"(desc));
}

template <int N> __device__ __forceinline__ void wg_cv(float* d, const uint32_t* a, uint64_t desc);
template <> __device__ __forceinline__ void wg_cv<16>(float* d, const uint32_t* a, uint64_t s) { wg_cv_n16(d, a, s); }
template <> __device__ __forceinline__ void wg_cv<32>(float* d, const uint32_t* a, uint64_t s) { wg_cv_n32(d, a, s); }
template <> __device__ __forceinline__ void wg_cv<48>(float* d, const uint32_t* a, uint64_t s) { wg_cv_n48(d, a, s); }
template <> __device__ __forceinline__ void wg_cv<64>(float* d, const uint32_t* a, uint64_t s) { wg_cv_n64(d, a, s); }

constexpr uint32_t POLYMASK = 0xB5B5u;
__device__ __forceinline__ void softmax_fast(const float* s, uint32_t* p, uint32_t mlo) {
    const uint32_t C3 = 0x2cfb2cfbu, C2 = 0x9fec9fecu, C1 = 0x37a837a8u, C0 = 0x37383738u;
#pragma unroll
    for (int i = 0; i < 16; i++) {
        const float s0 = s[2 * i], s1 = s[2 * i + 1];
        if ((POLYMASK >> i) & 1) {
            const float t0 = s0 + 12303.0f, t1 = s1 + 12303.0f;
            const uint32_t T = __byte_perm(__float_as_uint(t0), __float_as_uint(t1), 0x5410);
            const uint32_t U = lop3<0xEA>(T, mlo, 0x3C003C00u);
            uint32_t h = hfma2(U, C3, C2);
            h = hfma2(h, U, C1);
            h = hfma2(h, U, C0);
            p[i] = lop3<0xE4>(h, T, 0x03FF03FFu);
        } else {
            p[i] = pack_f16(ex2f(s0), ex2f(s1));
        }
    }
}

__device__ __forceinline__ void gemm_chunk(float* acc, uint32_t a_addr, uint32_t b_addr) {
    const uint64_t da = make_desc(a_addr, 16, 1024, 1);
    const uint64_t db = make_desc(b_addr, 8192, 1024, 1);
#pragma unroll
    for (int ks = 0; ks < 4; ks++) wg_ss_n32_tb(acc, da + ks * 2, db + ks * 128);
}

__device__ __forceinline__ void wo_half(uint32_t sb, const CUtensorMap* tm_wo, int hg) {
    uint32_t old;
    asm volatile("atom.shared.add.u32 %0, [%1], 1;" : "=r"(old) : "r"(sb + OFF_MISC + 8) : "memory");
    if (old == 3) {
        mbar_expect_tx(sb + OFF_BAR + 8 * (B_WO + 2), 32768);
        tma4d(sb + OFF_K, tm_wo, 0, 0, hg * 2, 4, sb + OFF_BAR + 8 * (B_WO + 2));
    }
}

struct Params {
    const __nv_bfloat16 *aq, *ak, *av, *shift_k, *ssm_D;
    __nv_bfloat16* out;
};

template <int NQ>
__device__ __forceinline__ void conv_group(float* D, uint32_t zaddr, uint64_t hdesc) {
    float Dn[NQ / 2];
#pragma unroll
    for (int i = 0; i < NQ / 2; i++) asm volatile("mov.f32 %0, %1;" : "=f"(Dn[i]) : "f"(D[(64 - NQ) / 2 + i]));
    uint32_t a[2][16];
#pragma unroll
    for (int st = 0; st < 4; st++) {
        uint32_t* aa = a[st & 1];
        if (st >= 2) wg_wait<1>();
#pragma unroll
        for (int u = 0; u < 2; u++) {
            const uint32_t z = zaddr + (st * 2 + u) * 256;
            aa[8 * u + 0] = lds32(z);      aa[8 * u + 1] = lds32(z + 32); aa[8 * u + 2] = lds32(z - 32); aa[8 * u + 3] = lds32(z);
            aa[8 * u + 4] = lds32(z - 64); aa[8 * u + 5] = lds32(z - 32); aa[8 * u + 6] = lds32(z - 96); aa[8 * u + 7] = lds32(z - 64);
        }
        wg_fence();
#pragma unroll
        for (int u = 0; u < 2; u++) {
            const int qi = st * 2 + u;
            wg_cv<NQ>(Dn, &aa[8 * u], hdesc - qi * 8);
            wg_cv<NQ>(Dn, &aa[8 * u + 4], hdesc - qi * 8 + 2);
        }
        wg_commit();
    }
    wg_wait<0>();
    fence_regs<NQ / 2>(Dn);
#pragma unroll
    for (int i = 0; i < NQ / 2; i++) asm volatile("mov.f32 %0, %1;" : "=f"(D[(64 - NQ) / 2 + i]) : "f"(Dn[i]));
}

__global__ void __launch_bounds__(NTHREADS, 1)
fused_kernel(const __grid_constant__ CUtensorMap tm_x,
             const __grid_constant__ CUtensorMap tm_wq, const __grid_constant__ CUtensorMap tm_wo,
             const __grid_constant__ CUtensorMap tm_wk, const __grid_constant__ CUtensorMap tm_wv,
             const __grid_constant__ CUtensorMap tm_o, const __grid_constant__ CUtensorMap tm_h, const Params prm) {
    extern __shared__ __align__(1024) uint8_t smem_raw[];
    const uint32_t sb = (uint32_t)__cvta_generic_to_shared(smem_raw);
    const int warp_id = __shfl_sync(0xffffffffu, threadIdx.x >> 5, 0);
    const int lane = threadIdx.x & 31;
    const int g = lane >> 2, t = lane & 3;
    const int b = blockIdx.x, pb = b >> 2, hg = b & 3;
    auto bar = [&](int i) { return sb + OFF_BAR + 8 * i; };

    if (threadIdx.x == 512) {
        TSTAMP(0);
        prefetch_tm(&tm_x); prefetch_tm(&tm_wq); prefetch_tm(&tm_wk); prefetch_tm(&tm_wv);
        mbar_init(bar(B_WKV), 1);
        for (int j = 0; j < 4; j++) { mbar_init(bar(B_X + j), 1); mbar_init(bar(B_W + j), 1); mbar_init(bar(B_WO + j), 1); mbar_init(bar(B_O + j), 1); }
        sts32(sb + OFF_MISC + 8, 0u);
        for (int j = 0; j < 8; j++) mbar_init(bar(B_KV + j), j == 0 ? 2 : 1);
        mbar_init(bar(B_QEMPTY), 4); mbar_init(bar(B_QEMPTY + 1), 4);
        mbar_init(bar(B_QDONE), 4); mbar_init(bar(B_ATT), 4);
        mbar_init(bar(B_H), 1); mbar_init(bar(B_CV), 1);
        asm volatile("fence.mbarrier_init.release.cluster;" ::: "memory");
    }

    if (warp_id < 16) {
        const int w = warp_id >> 2, wq = warp_id & 3;
        __syncthreads();
        float acc[16];
#pragma unroll
        for (int i = 0; i < 16; i++) acc[i] = 0.f;
        fence_regs<16>(acc);
        const uint32_t bcol = (w >> 1) * 8192 + (w & 1) * 64;
#pragma unroll 1
        for (int jj = 0; jj < 4; jj++) {
            mbar_wait_w(bar(B_X + jj), 0);
            mbar_wait_w(bar(B_W + jj), 0);
            if (threadIdx.x == 0 && jj < 4) TSTAMP(jj == 0 ? 23 : jj == 1 ? 24 : jj == 2 ? 26 : 27);
            wg_fence();
            gemm_chunk(acc, sb + OFF_X + jj * 16384, sb + OFF_V + (jj & 1) * 32768 + bcol);
            gemm_chunk(acc, sb + OFF_X + jj * 16384 + 8192, sb + OFF_V + (jj & 1) * 32768 + 16384 + bcol);
            wg_commit();
            wg_wait<0>();
            if (jj < 2 && (threadIdx.x & 127) == 0) mbar_arrive(bar(B_QEMPTY + jj));
        }
        fence_regs<16>(acc);
        if ((threadIdx.x & 127) == 0) { mbar_arrive(bar(B_QDONE)); if (w == 0) TSTAMP(1); }
        uint32_t qa[2][4];
        float qn[2];
        {
            const float c = 0.25f * 1.4426950408889634f;
#pragma unroll
            for (int hh = 0; hh < 2; hh++) {
                float n0 = 0.f, n1 = 0.f;
#pragma unroll
                for (int i = 0; i < 4; i++) {
                    const uint32_t qb = pack_bf16(acc[8 * hh + 2 * i], acc[8 * hh + 2 * i + 1]);
                    const uint32_t qs = pack_bf16(bf_lo(qb) * c, bf_hi(qb) * c);
                    qa[hh][i] = qs;
                    const float e = bf_lo(qs) * bf_lo(qs) + bf_hi(qs) * bf_hi(qs);
                    if (i & 1) n1 += e; else n0 += e;
                }
                n0 += __shfl_xor_sync(0xffffffffu, n0, 1); n0 += __shfl_xor_sync(0xffffffffu, n0, 2);
                n1 += __shfl_xor_sync(0xffffffffu, n1, 1); n1 += __shfl_xor_sync(0xffffffffu, n1, 2);
                qn[hh] = fmaxf(n0, n1);
            }
        }
        uint32_t mlo = 0x03FF03FFu; asm volatile("" : "+r"(mlo));
        const uint64_t kdesc0 = make_desc(sb + OFF_K, 128, 256, 0);
        const uint64_t vdesc0 = make_desc(sb + OFF_VONES - 256, 128, 256, 0);
        constexpr uint64_t VSTEP = ((uint64_t)16 << 32) - 16;
        mbar_wait_w(bar(B_KV + 0), 0);
        if ((threadIdx.x & 127) == 0 && w == 0) TSTAMP(2);
        const float kmax2 = ldsf(sb + OFF_MISC);
        const bool fast0 = __all_sync(0xffffffffu, named_bar_and(1 + w, 128, qn[0] * kmax2 <= 193.0f));
        const bool fast1 = __all_sync(0xffffffffu, named_bar_and(1 + w, 128, qn[1] * kmax2 <= 193.0f));
        uint32_t a[4] = {qa[0][0], qa[0][1], qa[0][2], qa[0][3]};
#pragma unroll 1
        for (int hh = 0; hh < 2; hh++) {
            const bool fast = hh ? fast1 : fast0;
            float S[32], O[12];
#pragma unroll
            for (int i = 0; i < 12; i++) O[i] = 0.f;
#pragma unroll
            for (int i = 0; i < 32; i++) S[i] = 0.f;
            fence_regs<12>(O); fence_regs<32>(S);
            wg_fence();
            wg_qk_n64(S, a, kdesc0);
            wg_commit();
            wg_wait<0>();
            uint64_t kd = kdesc0 + 128, vd = vdesc0;
            if (fast) {
                uint32_t P[16];
#pragma unroll 1
                for (int c = 0; c < 8; c++) {
                    if (c < 7) mbar_wait_w(bar(B_KV + c + 1), 0);
#pragma unroll 1
                    for (int j = 0; j < 4; j++) {
                        fence_regs<32>(S);
                        softmax_fast(S, P, mlo);
                        fence_regs<32>(S);
                        wg_fence();
                        wg_qk_n64(S, a, kd);
#pragma unroll
                        for (int i = 0; i < 4; i++) wg_pv_n24(O, &P[4 * i], vd + i * VSTEP);
                        wg_commit();
                        wg_wait<0>();
                        kd += 128; vd += 4 * VSTEP;
                    }
                    if (hh == 1 && c == 3 && (threadIdx.x & 127) == 0) wo_half(sb, &tm_wo, hg);
                }
            } else {
                uint32_t P[16];
                float m0 = -INFINITY, m1 = -INFINITY;
#pragma unroll 1
                for (int c = 0; c < 8; c++) {
                    if (c < 7) mbar_wait_w(bar(B_KV + c + 1), 0);
#pragma unroll 1
                    for (int j = 0; j < 4; j++) {
                        fence_regs<32>(S); fence_regs<12>(O);
                        float x0 = m0, x1 = m1;
#pragma unroll
                        for (int i = 0; i < 8; i++) {
                            x0 = fmaxf(x0, fmaxf(S[4 * i], S[4 * i + 1]));
                            x1 = fmaxf(x1, fmaxf(S[4 * i + 2], S[4 * i + 3]));
                        }
                        x0 = fmaxf(x0, __shfl_xor_sync(0xffffffffu, x0, 1)); x0 = fmaxf(x0, __shfl_xor_sync(0xffffffffu, x0, 2));
                        x1 = fmaxf(x1, __shfl_xor_sync(0xffffffffu, x1, 1)); x1 = fmaxf(x1, __shfl_xor_sync(0xffffffffu, x1, 2));
                        const float r0 = ex2f(m0 - x0), r1 = ex2f(m1 - x1);
                        m0 = x0; m1 = x1;
#pragma unroll
                        for (int i = 0; i < 3; i++) { O[4 * i] *= r0; O[4 * i + 1] *= r0; O[4 * i + 2] *= r1; O[4 * i + 3] *= r1; }
#pragma unroll
                        for (int i = 0; i < 8; i++) {
                            P[2 * i] = pack_f16(ex2f(S[4 * i] - m0), ex2f(S[4 * i + 1] - m0));
                            P[2 * i + 1] = pack_f16(ex2f(S[4 * i + 2] - m1), ex2f(S[4 * i + 3] - m1));
                        }
                        fence_regs<32>(S); fence_regs<12>(O);
                        wg_fence();
                        wg_qk_n64(S, a, kd);
#pragma unroll
                        for (int i = 0; i < 4; i++) wg_pv_n24(O, &P[4 * i], vd + i * VSTEP);
                        wg_commit();
                        wg_wait<0>();
                        kd += 128; vd += 4 * VSTEP;
                    }
                    if (hh == 1 && c == 3 && (threadIdx.x & 127) == 0) wo_half(sb, &tm_wo, hg);
                }
            }
            fence_regs<12>(O);
            const float vscale = ldsf(sb + OFF_MISC + 4);
            const float i0 = __fdividef(vscale, O[4]), i1 = __fdividef(vscale, O[6]);
            const int row = pb * 64 + wq * 16 + g;
            uint32_t* o0 = (uint32_t*)(g_o + (size_t)row * 512 + (hg * 8 + 2 * w + hh) * 16) + t;
            uint32_t* o1 = o0 + 8 * 256;
            o0[0] = pack_bf16(O[0] * i0, O[1] * i0);
            o0[4] = pack_bf16(O[8] * i0, O[9] * i0);
            o1[0] = pack_bf16(O[2] * i1, O[3] * i1);
            o1[4] = pack_bf16(O[10] * i1, O[11] * i1);
            if ((threadIdx.x & 127) == 0 && w == 0) { TSTAMP(3 + hh); CSTAMP(40 + hh); }
#pragma unroll
            for (int i = 0; i < 4; i++) a[i] = qa[1][i];
        }
        named_bar(1 + w, 128);
        if ((threadIdx.x & 127) == 0) {
            red_release_add(&g_o_count[pb], 1);
            mbar_arrive(bar(B_ATT));
        }
        if (threadIdx.x == 0) {
            TSTAMP(30);
            mbar_wait(bar(B_ATT), 0);
            TSTAMP(31);
            poll_counter(&g_o_count[pb], 16);
            TSTAMP(18);
            fence_async_global();
            for (int jj = 0; jj < 4; jj++) {
                mbar_expect_tx(bar(B_O + jj), 16384);
                tma3d(sb + OFF_V + jj * 16384, &tm_o, 0, pb * 64, 2 * jj, bar(B_O + jj));
            }
            __threadfence();
            if (atomicAdd(&g_done, 1) == 2 * NCTA - 1) {
                g_kv_count = 0;
                for (int i = 0; i < 4; i++) { g_kvt_count[i] = 0; g_z_count[i] = 0; }
                for (int i = 0; i < 32; i++) g_o_count[i] = 0;
                g_done = 0;
                __threadfence();
            }
        }
        __syncwarp();
#pragma unroll
        for (int i = 0; i < 16; i++) acc[i] = 0.f;
        fence_regs<16>(acc);
#pragma unroll 1
        for (int jj = 0; jj < 4; jj++) {
            mbar_wait_w(bar(B_WO + jj), 0);
            mbar_wait_w(bar(B_O + jj), 0);
            if (threadIdx.x == 0 && (jj == 0 || jj == 3)) TSTAMP(jj == 0 ? 32 : 33);
            const uint32_t wb = sb + (jj < 2 ? OFF_X + jj * 32768 : (jj == 2 ? OFF_K : OFF_C)) + bcol;
            wg_fence();
            gemm_chunk(acc, sb + OFF_V + jj * 16384, wb);
            gemm_chunk(acc, sb + OFF_V + jj * 16384 + 8192, wb + 16384);
            wg_commit();
        }
        wg_wait<0>();
        fence_regs<16>(acc);
        {
            const int row = pb * 64 + wq * 16 + g;
            uint32_t* d0 = (uint32_t*)(prm.out + (size_t)row * 1024 + 512 + hg * 128 + w * 32) + t;
            uint32_t* d1 = d0 + 8 * 512;
#pragma unroll
            for (int i = 0; i < 4; i++) {
                d0[4 * i] = pack_bf16(acc[4 * i], acc[4 * i + 1]);
                d1[4 * i] = pack_bf16(acc[4 * i + 2], acc[4 * i + 3]);
            }
        }
        if ((threadIdx.x & 127) == 0 && w == 0) TSTAMP(5);
    } else {
        const int wa = warp_id - 16, tau = threadIdx.x - 512;
        __syncthreads();
        const bool kv_cta = (hg == (pb & 3));
        if (tau == 0) {
            if (kv_cta) {
                mbar_expect_tx(bar(B_WKV), 32768);
                tma3d(sb + OFF_C, &tm_wk, 0, 0, 0, bar(B_WKV));
                tma3d(sb + OFF_C + 16384, &tm_wv, 0, 0, 0, bar(B_WKV));
            }
            for (int jj = 0; jj < 4; jj++) {
                mbar_expect_tx(bar(B_X + jj), 16384);
                tma3d(sb + OFF_X + jj * 16384, &tm_x, 0, pb * 64, 2 * jj, bar(B_X + jj));
                if (!kv_cta && jj < 2) {
                    mbar_expect_tx(bar(B_W + jj), 32768);
                    tma4d(sb + OFF_V + jj * 32768, &tm_wq, 0, 0, hg * 2, 2 * jj, bar(B_W + jj));
                }
            }
            TSTAMP(25);
        }
        __syncwarp();
        if (kv_cta) {
            float acc[16];
#pragma unroll
            for (int i = 0; i < 16; i++) acc[i] = 0.f;
            fence_regs<16>(acc);
            mbar_wait_w(bar(B_WKV), 0);
            if (tau == 0) TSTAMP(20);
#pragma unroll
            for (int jj = 0; jj < 4; jj++) {
                mbar_wait_w(bar(B_X + jj), 0);
                wg_fence();
#pragma unroll
                for (int j = 2 * jj; j < 2 * jj + 2; j++) {
                    const uint64_t da = make_desc(sb + OFF_X + j * 8192, 16, 1024, 1);
                    const uint64_t db = make_desc(sb + OFF_C + j * 2048, 16384, 256, 3);
#pragma unroll
                    for (int ks = 0; ks < 4; ks++) wg_ss_n32_tb(acc, da + ks * 2, db + ks * 32);
                }
                wg_commit();
            }
            wg_wait<0>();
            fence_regs<16>(acc);
            if (tau == 0) TSTAMP(22);
            {
                uint32_t kk[4], vv[4];
#pragma unroll
                for (int i = 0; i < 4; i++) { kk[i] = pack_bf16(acc[2 * i], acc[2 * i + 1]); vv[i] = pack_bf16(acc[8 + 2 * i], acc[8 + 2 * i + 1]); }
                const int s = 4 * pb + wa;
                uint32_t* kp = (uint32_t*)(g_kimg + s * 512 + g * 16 + 4 * t);
                kp[0] = kk[0]; kp[64] = kk[1]; kp[32] = kk[2]; kp[96] = kk[3];
                uint32_t* vlo = (uint32_t*)(g_vimg + (127 - s) * 256 + g * 16 + 4 * t);
                uint32_t* vhi = (uint32_t*)(g_vimg + 32768 + 256 + s * 256 + g * 16 + 4 * t);
                vlo[0] = pack_f16(bf_lo(vv[0]), bf_hi(vv[0])); vlo[32] = pack_f16(bf_lo(vv[1]), bf_hi(vv[1]));
                vhi[0] = pack_f16(bf_lo(vv[2]), bf_hi(vv[2])); vhi[32] = pack_f16(bf_lo(vv[3]), bf_hi(vv[3]));
                uint32_t* vr = (uint32_t*)(g_vraw + (size_t)(16 * s + g) * 16) + t;
                vr[0] = vv[0]; vr[64] = vv[1]; vr[4] = vv[2]; vr[68] = vv[3];
                float n0 = bf_lo(kk[0]) * bf_lo(kk[0]) + bf_hi(kk[0]) * bf_hi(kk[0]) + bf_lo(kk[2]) * bf_lo(kk[2]) + bf_hi(kk[2]) * bf_hi(kk[2]);
                float n1 = bf_lo(kk[1]) * bf_lo(kk[1]) + bf_hi(kk[1]) * bf_hi(kk[1]) + bf_lo(kk[3]) * bf_lo(kk[3]) + bf_hi(kk[3]) * bf_hi(kk[3]);
                n0 += __shfl_xor_sync(0xffffffffu, n0, 1); n0 += __shfl_xor_sync(0xffffffffu, n0, 2);
                n1 += __shfl_xor_sync(0xffffffffu, n1, 1); n1 += __shfl_xor_sync(0xffffffffu, n1, 2);
                float km = fmaxf(n0, n1), vm = 0.f;
#pragma unroll
                for (int i = 0; i < 4; i++) vm = fmaxf(vm, fmaxf(fabsf(bf_lo(vv[i])), fabsf(bf_hi(vv[i]))));
#pragma unroll
                for (int o = 4; o < 32; o <<= 1) km = fmaxf(km, __shfl_xor_sync(0xffffffffu, km, o));
#pragma unroll
                for (int o = 1; o < 32; o <<= 1) vm = fmaxf(vm, __shfl_xor_sync(0xffffffffu, vm, o));
                if (lane == 0) g_stats[s] = make_float2(km, vm);
                __syncwarp();
                if (lane == 0) { red_release_add(&g_kv_count, 1); if (wa == 0) TSTAMP(8); }
            }
            if (tau == 0) {
                for (int jj = 0; jj < 2; jj++) {
                    mbar_expect_tx(bar(B_W + jj), 32768);
                    tma4d(sb + OFF_V + jj * 32768, &tm_wq, 0, 0, hg * 2, 2 * jj, bar(B_W + jj));
                }
            }
            __syncwarp();
        }
        const int c0 = 4 * b;
        if (wa == 0) {
            if (lane == 0) {
                for (int jj = 2; jj < 4; jj++) {
                    mbar_wait(bar(B_QEMPTY + jj - 2), 0);
                    mbar_expect_tx(bar(B_W + jj), 32768);
                    tma4d(sb + OFF_V + (jj - 2) * 32768, &tm_wq, 0, 0, hg * 2, 2 * jj, bar(B_W + jj));
                }
                poll_counter(&g_kv_count, NCTA);
                TSTAMP(16);
                fence_async_global();
                for (int c = 0; c < 8; c++) {
                    mbar_expect_tx_noarrive(bar(B_KV + c), 8192);
                    bulk_g2s(sb + OFF_K + c * 8192, g_kimg + c * 8192, 8192, bar(B_KV + c));
                }
                TSTAMP(28);
            }
            __syncwarp();
            float km = 0.f, vm = 0.f;
#pragma unroll
            for (int i = 0; i < 4; i++) { const float2 st = __ldcg(&g_stats[lane + 32 * i]); km = fmaxf(km, st.x); vm = fmaxf(vm, st.y); }
#pragma unroll
            for (int o = 1; o < 32; o <<= 1) { km = fmaxf(km, __shfl_xor_sync(0xffffffffu, km, o)); vm = fmaxf(vm, __shfl_xor_sync(0xffffffffu, vm, o)); }
            const bool vdirect = (vm <= 32768.f && vm >= 9.765625e-4f) || vm == 0.f;
            float vs = 1.f;
            if (!vdirect && vm < INFINITY) {
                int e = (int)((__float_as_uint(vm) >> 23) & 0xFF) - 127;
                e = max(-100, min(100, e));
                vs = __uint_as_float((uint32_t)(127 + e - 13) << 23);
            }
            if (lane == 0) {
                asm volatile("st.shared.f32 [%0], %1;" ::"r"(sb + OFF_MISC), "f"(km) : "memory");
                asm volatile("st.shared.f32 [%0], %1;" ::"r"(sb + OFF_MISC + 4), "f"(vs) : "memory");
                mbar_wait(bar(B_QDONE), 0);
                TSTAMP(17);
                for (int c = 0; c < 8; c++) {
                    if (vdirect) {
                        mbar_expect_tx(bar(B_KV + c), 8192);
                        bulk_g2s(sb + OFF_V + (112 - 16 * c) * 256, g_vimg + (112 - 16 * c) * 256, 4096, bar(B_KV + c));
                        bulk_g2s(sb + OFF_VONES + 256 + c * 4096, g_vimg + 32768 + 256 + c * 4096, 4096, bar(B_KV + c));
                    }
                }
            }
            __syncwarp();
            sts32(sb + OFF_VONES + lane * 8, 0x3C003C00u);
            sts32(sb + OFF_VONES + lane * 8 + 4, 0x3C003C00u);
            if (!vdirect) {
                const float inv = 1.f / vs;
                for (int idx = lane; idx < S_LEN * 8; idx += 32) {
                    const int key = idx >> 3, dp = idx & 7;
                    const uint32_t v = __ldcg((const uint32_t*)g_vraw + idx);
                    const uint32_t h = pack_f16(bf_lo(v) * inv, bf_hi(v) * inv);
                    const int st = key >> 4, hf = (key >> 3) & 1;
                    const uint32_t base = (dp < 4) ? (OFF_V + (127 - st) * 256) : (OFF_VONES + 256 + st * 256);
                    sts32(sb + base + hf * 128 + (key & 7) * 16 + (dp & 3) * 4, h);
                }
            }
            fence_async_smem();
            __syncwarp();
            if (lane == 0) {
                mbar_arrive(bar(B_KV + 0));
                if (!vdirect) for (int c = 0; c < 8; c++) mbar_arrive(bar(B_KV + c));
                prefetch_tm(&tm_wo); prefetch_tm(&tm_o);
                for (int jj = 0; jj < 2; jj++) {
                    mbar_expect_tx(bar(B_WO + jj), 32768);
                    tma4d(sb + OFF_X + jj * 32768, &tm_wo, 0, 0, hg * 2, 2 * jj, bar(B_WO + jj));
                }
            }
            __syncwarp();
        } else {
            if (wa == 1 && lane == 0) {
                mbar_expect_tx(bar(B_H), 4096);
                tma2d(sb + C_H + 1024, &tm_h, 0, c0 * 64, bar(B_H));
            }
            if (wa >= 2) {
                sts128(sb + C_H + (tau - 64) * 16, 0u, 0u, 0u, 0u);
                fence_async_smem();
            }
            mbar_wait_w(bar(B_QDONE), 0);
        }
        {
            const int kch0 = hg * 128 + lane * 4, kp0 = pb * 64 + wa * 16;
            uint32_t wA[4], wB[4];
            {
                const uint4 s0 = __ldg((const uint4*)(prm.shift_k + kch0 * 4));
                const uint4 s1 = __ldg((const uint4*)(prm.shift_k + kch0 * 4) + 1);
                wA[0] = __byte_perm(s0.x, s0.z, 0x5410); wA[1] = __byte_perm(s0.x, s0.z, 0x7632);
                wA[2] = __byte_perm(s0.y, s0.w, 0x5410); wA[3] = __byte_perm(s0.y, s0.w, 0x7632);
                wB[0] = __byte_perm(s1.x, s1.z, 0x5410); wB[1] = __byte_perm(s1.x, s1.z, 0x7632);
                wB[2] = __byte_perm(s1.y, s1.w, 0x5410); wB[3] = __byte_perm(s1.y, s1.w, 0x7632);
            }
            const uint2* kp = (const uint2*)(prm.ak + kch0);
            const uint2* vp = (const uint2*)(prm.av + kch0);
#pragma unroll
            for (int half = 0; half < 2; half++) {
                uint2 kr[11], vr[8];
#pragma unroll
                for (int i = 0; i < 11; i++) {
                    const int sx = kp0 + half * 8 + i - 3;
                    kr[i] = sx >= 0 ? __ldg(kp + (size_t)sx * 128) : make_uint2(0u, 0u);
                }
#pragma unroll
                for (int i = 0; i < 8; i++) vr[i] = __ldg(vp + (size_t)(kp0 + half * 8 + i) * 128);
                uint32_t xa[8], xb[8];
#pragma unroll
                for (int i = 0; i < 8; i++) {
                    uint32_t ua = bmul2(kr[i].x, wA[3]), ub = bmul2(kr[i].y, wB[3]);
                    ua = badd2(ua, bmul2(kr[i + 1].x, wA[2])); ub = badd2(ub, bmul2(kr[i + 1].y, wB[2]));
                    ua = badd2(ua, bmul2(kr[i + 2].x, wA[1])); ub = badd2(ub, bmul2(kr[i + 2].y, wB[1]));
                    ua = badd2(ua, bmul2(kr[i + 3].x, wA[0])); ub = badd2(ub, bmul2(kr[i + 3].y, wB[0]));
                    xa[i] = bmul2(ua, vr[i].x); xb[i] = bmul2(ub, vr[i].y);
                }
                uint4* dst = (uint4*)(g_kvT + (size_t)kch0 * S_LEN + kp0 + half * 8);
                dst[0] = make_uint4(__byte_perm(xa[0], xa[1], 0x5410), __byte_perm(xa[2], xa[3], 0x5410), __byte_perm(xa[4], xa[5], 0x5410), __byte_perm(xa[6], xa[7], 0x5410));
                dst[S_LEN / 8] = make_uint4(__byte_perm(xa[0], xa[1], 0x7632), __byte_perm(xa[2], xa[3], 0x7632), __byte_perm(xa[4], xa[5], 0x7632), __byte_perm(xa[6], xa[7], 0x7632));
                dst[2 * (S_LEN / 8)] = make_uint4(__byte_perm(xb[0], xb[1], 0x5410), __byte_perm(xb[2], xb[3], 0x5410), __byte_perm(xb[4], xb[5], 0x5410), __byte_perm(xb[6], xb[7], 0x5410));
                dst[3 * (S_LEN / 8)] = make_uint4(__byte_perm(xb[0], xb[1], 0x7632), __byte_perm(xb[2], xb[3], 0x7632), __byte_perm(xb[4], xb[5], 0x7632), __byte_perm(xb[6], xb[7], 0x7632));
            }
        }
        named_bar(5, 128);
        if (tau == 0) {
            red_release_add(&g_kvt_count[hg], 1);
            TSTAMP(34);
            poll_counter(&g_kvt_count[b >> 5], 32);
            fence_async_global();
            mbar_expect_tx(bar(B_CV), 16384);
            bulk_g2s(sb + C_KVC, g_kvT + (size_t)c0 * S_LEN, 16384, bar(B_CV));
        }
        __syncwarp();
        mbar_wait_w(bar(B_CV), 0);
        if (tau == 0) TSTAMP(9);
        const int NCH = 4;
#pragma unroll 1
        for (int ch = 0; ch < NCH; ch++) {
            {
                const uint32_t src = sb + C_KVC + ch * 4096 + tau * 32;
                const uint4 u0 = lds128(src), u1 = lds128(src + 16);
                const uint32_t prev = tau > 0 ? lds32(src - 4) : 0u;
                const uint32_t zd = sb + C_Z + (32 + tau * 16) * 4;
                sts128(zd,      __byte_perm(u0.x, prev, 0x7610), __byte_perm(u0.x, u0.x, 0x1032), __byte_perm(u0.y, u0.x, 0x7610), __byte_perm(u0.y, u0.y, 0x1032));
                sts128(zd + 16, __byte_perm(u0.z, u0.y, 0x7610), __byte_perm(u0.z, u0.z, 0x1032), __byte_perm(u0.w, u0.z, 0x7610), __byte_perm(u0.w, u0.w, 0x1032));
                sts128(zd + 32, __byte_perm(u1.x, u0.w, 0x7610), __byte_perm(u1.x, u1.x, 0x1032), __byte_perm(u1.y, u1.x, 0x7610), __byte_perm(u1.y, u1.y, 0x1032));
                sts128(zd + 48, __byte_perm(u1.z, u1.y, 0x7610), __byte_perm(u1.z, u1.z, 0x1032), __byte_perm(u1.w, u1.z, 0x7610), __byte_perm(u1.w, u1.w, 0x1032));
                if (tau < 32) sts32(sb + C_Z + tau * 4, 0u);
            }
            named_bar(5, 128);
            mbar_wait_w(bar(B_H), ch & 1);
            float D[32];
#pragma unroll
            for (int i = 0; i < 32; i++) D[i] = 0.f;
            const uint32_t z0 = sb + C_Z + (32 + 32 * (wa >> 1) + 16 * (wa & 1) + g - 2 * t) * 4;
            const uint64_t hd = make_desc(sb + C_H + 1024, 16, 512, 2);
            conv_group<64>(D, z0 + 0 * 2048, hd);
            conv_group<48>(D, z0 + 1 * 2048, hd);
            conv_group<32>(D, z0 + 2 * 2048, hd);
            conv_group<16>(D, z0 + 3 * 2048, hd);
            if (tau == 0 && ch < 3) {
                mbar_expect_tx(bar(B_H), 4096);
                tma2d(sb + C_H + 1024, &tm_h, 0, (c0 + ch + 1) * 64, bar(B_H));
            }
            if (wa >= 2) {
#pragma unroll
                for (int jn = 0; jn < 8; jn++) {
#pragma unroll
                    for (int r = 0; r < 2; r++) {
                        const int bb = 16 * (wa & 1) + g + 8 * r;
                        const int n = 8 * jn + 2 * t;
                        sts64f(sb + C_Z + (bb * 64 + (n ^ ((bb & 3) << 3))) * 4, D[4 * jn + 2 * r], D[4 * jn + 2 * r + 1]);
                    }
                }
            }
            named_bar(5, 128);
            if (wa < 2) {
                const float dsc = __bfloat162float(prm.ssm_D[c0 + ch]);
#pragma unroll
                for (int jn = 0; jn < 8; jn++) {
#pragma unroll
                    for (int r = 0; r < 2; r++) {
                        const int bb = 16 * wa + g + 8 * r;
#pragma unroll
                        for (int e = 0; e < 2; e++) {
                            const int m = 8 * jn + 2 * t + e;
                            float y = D[4 * jn + 2 * r + e];
                            if (m > 0) y += ldsf(sb + C_Z + (bb * 64 + ((m - 1) ^ ((bb & 3) << 3))) * 4);
                            const uint32_t addr = sb + C_KVC + ch * 4096 + (32 * m + bb) * 2;
                            const float kv = __uint_as_float(lds16(addr) << 16);
                            const float yb = __bfloat162float(__float2bfloat16_rn(y));
                            const float kd = __bfloat162float(__float2bfloat16_rn(kv * dsc));
                            sts16(addr, (uint32_t)__bfloat16_as_ushort(__float2bfloat16_rn(yb + kd)));
                        }
                    }
                }
                fence_async_smem();
            }
            named_bar(5, 128);
            if (tau == 0) {
                bulk_s2g(g_zT + (size_t)(c0 + ch) * S_LEN, sb + C_KVC + ch * 4096, 4096);
                bulk_commit();
                TSTAMP(10 + ch);
            }
        }
        {
            const int cg = tau & 15, pr = tau >> 4;
            const int p0 = pb * 64 + pr * 8, ch0 = hg * 128 + cg * 8;
            uint4 qr[8];
#pragma unroll
            for (int i = 0; i < 8; i++) qr[i] = __ldg((const uint4*)(prm.aq + (size_t)(p0 + i) * 512 + ch0));
            if (tau == 0) {
                bulk_wait_all();
                mbar_expect_tx(bar(B_WO + 3), 32768);
                tma4d(sb + OFF_C, &tm_wo, 0, 0, hg * 2, 6, bar(B_WO + 3));
                fence_async_global();
                red_release_add(&g_z_count[b >> 5], 1);
                poll_counter(&g_z_count[hg], 32);
                __threadfence();
                if (atomicAdd(&g_done, 1) == 2 * NCTA - 1) {
                    g_kv_count = 0;
                    for (int i = 0; i < 4; i++) { g_kvt_count[i] = 0; g_z_count[i] = 0; }
                    for (int i = 0; i < 32; i++) g_o_count[i] = 0;
                    g_done = 0;
                    __threadfence();
                }
            }
            named_bar(5, 128);
            uint4 zz[8];
#pragma unroll
            for (int c = 0; c < 8; c++) zz[c] = __ldcg((const uint4*)(g_zT + (size_t)(ch0 + c) * S_LEN + p0));
#pragma unroll
            for (int i = 0; i < 8; i++) {
                uint32_t r[4];
#pragma unroll
                for (int k = 0; k < 4; k++) {
                    const uint32_t pr2 = __byte_perm((&zz[2 * k].x)[i >> 1], (&zz[2 * k + 1].x)[i >> 1], (i & 1) ? 0x7632 : 0x5410);
                    r[k] = bmul2((&qr[i].x)[k], pr2);
                }
                *(uint4*)(prm.out + (size_t)(p0 + i) * 1024 + ch0) = make_uint4(r[0], r[1], r[2], r[3]);
            }
        }
        if (tau == 0) TSTAMP(14);
    }
}

typedef CUresult (*EncodeFn)(CUtensorMap*, CUtensorMapDataType, cuuint32_t, void*, const cuuint64_t*, const cuuint64_t*,
                             const cuuint32_t*, const cuuint32_t*, CUtensorMapInterleave, CUtensorMapSwizzle,
                             CUtensorMapL2promotion, CUtensorMapFloatOOBfill);

void make_map(EncodeFn fn, CUtensorMap* tm, const void* ptr, int rank, const cuuint64_t* dims, const cuuint64_t* strides, const cuuint32_t* box, CUtensorMapSwizzle swz) {
    cuuint32_t es[4] = {1, 1, 1, 1};
    fn(tm, CU_TENSOR_MAP_DATA_TYPE_BFLOAT16, rank, const_cast<void*>(ptr), dims, strides, box, es, CU_TENSOR_MAP_INTERLEAVE_NONE, swz,
       CU_TENSOR_MAP_L2_PROMOTION_L2_128B, CU_TENSOR_MAP_FLOAT_OOB_FILL_NONE);
}

}

extern "C" void kernel_launch(void* const* d_in, const int* in_sizes, int n_in, void* d_out, int out_size) {
    (void)in_sizes; (void)n_in; (void)out_size;
    static EncodeFn encode = nullptr;
    static void* o_ptr = nullptr;
    if (!encode) {
        cudaDriverEntryPointQueryResult qres;
        void* fn = nullptr;
        cudaGetDriverEntryPoint("cuTensorMapEncodeTiled", &fn, cudaEnableDefault, &qres);
        encode = (EncodeFn)fn;
        cudaGetSymbolAddress(&o_ptr, g_o);
        cudaFuncSetAttribute(fused_kernel, cudaFuncAttributeMaxDynamicSharedMemorySize, SMEM_TOTAL);
    }
    CUtensorMap tm_x, tm_wq, tm_wo, tm_wk, tm_wv, tm_o, tm_h;
    {
        const cuuint64_t dims[3] = {64, 2048, 8}, str[2] = {1024, 128};
        const cuuint32_t b64[3] = {64, 64, 2};
        make_map(encode, &tm_x, d_in[6], 3, dims, str, b64, CU_TENSOR_MAP_SWIZZLE_128B);
        make_map(encode, &tm_o, o_ptr, 3, dims, str, b64, CU_TENSOR_MAP_SWIZZLE_128B);
    }
    {
        const cuuint64_t dims[4] = {64, 64, 8, 8}, str[3] = {1024, 128, 65536};
        const cuuint32_t box[4] = {64, 64, 2, 2};
        make_map(encode, &tm_wq, d_in[7], 4, dims, str, box, CU_TENSOR_MAP_SWIZZLE_128B);
        make_map(encode, &tm_wo, d_in[10], 4, dims, str, box, CU_TENSOR_MAP_SWIZZLE_128B);
    }
    {
        const cuuint64_t dims[3] = {16, 256, 2}, str[2] = {32, 8192};
        const cuuint32_t box[3] = {16, 256, 2};
        make_map(encode, &tm_wk, d_in[8], 3, dims, str, box, CU_TENSOR_MAP_SWIZZLE_32B);
        make_map(encode, &tm_wv, d_in[9], 3, dims, str, box, CU_TENSOR_MAP_SWIZZLE_32B);
    }
    {
        const cuuint64_t dims[2] = {32, 512 * 64}, str[1] = {64};
        const cuuint32_t box[2] = {32, 64};
        make_map(encode, &tm_h, d_in[4], 2, dims, str, box, CU_TENSOR_MAP_SWIZZLE_64B);
    }
    Params prm;
    prm.aq = (const __nv_bfloat16*)d_in[0];
    prm.ak = (const __nv_bfloat16*)d_in[1];
    prm.av = (const __nv_bfloat16*)d_in[2];
    prm.shift_k = (const __nv_bfloat16*)d_in[3];
    prm.ssm_D = (const __nv_bfloat16*)d_in[5];
    prm.out = (__nv_bfloat16*)d_out;
    fused_kernel<<<NCTA, NTHREADS, SMEM_TOTAL>>>(tm_x, tm_wq, tm_wo, tm_wk, tm_wv, tm_o, tm_h, prm);
}
```

```cpp
#include <cuda_runtime.h>
#include <cuda_bf16.h>
#include <cuda_fp16.h>
#include <cuda.h>
#include <stdint.h>

namespace {

constexpr int S_LEN = 2048;
constexpr int NCTA = 128;
constexpr int NTHREADS = 640;

constexpr uint32_t OFF_K = 0;
constexpr uint32_t OFF_V = 65536;
constexpr uint32_t OFF_VONES = OFF_V + 32768;
constexpr uint32_t OFF_X = 132096;
constexpr uint32_t OFF_C = 197632;
constexpr uint32_t C_KVC = OFF_C;
constexpr uint32_t C_H = OFF_C + 16384;
constexpr uint32_t C_Z = C_H + 6144;
constexpr uint32_t OFF_BAR = 231936;
constexpr uint32_t SMEM_TOTAL = 232448;

enum { B_WKV = 0, B_X = 1, B_QEMPTY = 5, B_QDONE = 7, B_KV = 8, B_WO = 16, B_O = 20, B_ATT = 24, B_H = 25, B_CV = 26, B_W = 27, B_COUNT = 31 };
constexpr uint32_t OFF_MISC = OFF_BAR + 8 * B_COUNT;

__device__ __align__(1024) uint8_t g_kimg[65536];
__device__ __align__(1024) uint8_t g_vimg[65792];
__device__ __align__(1024) __nv_bfloat16 g_vraw[S_LEN * 16];
__device__ __align__(1024) __nv_bfloat16 g_o[S_LEN * 512];
__device__ __align__(1024) __nv_bfloat16 g_kvT[512 * S_LEN];
__device__ __align__(1024) __nv_bfloat16 g_zT[512 * S_LEN];
__device__ unsigned long long g_stats[NCTA];
__device__ unsigned int g_kvt_count[4];
__device__ unsigned int g_z_count[4];
__device__ unsigned int g_o_count[32];
__device__ unsigned int g_done;
#define TSTAMP(i) do {} while (0)
#define CSTAMP(i) do {} while (0)

__device__ __forceinline__ void wg_fence() { asm volatile("wgmma.fence.sync.aligned;" ::: "memory"); }
__device__ __forceinline__ void wg_commit() { asm volatile("wgmma.commit_group.sync.aligned;" ::: "memory"); }
template <int N> __device__ __forceinline__ void wg_wait() { asm volatile("wgmma.wait_group.sync.aligned %0;" ::"n"(N) : "memory"); }
template <int N> __device__ __forceinline__ void fence_regs(float* r) {
#pragma unroll
    for (int i = 0; i < N; i++) asm volatile("" : "+f"(r[i])::"memory");
}
template <int N> __device__ __forceinline__ void fence_uregs(uint32_t* r) {
#pragma unroll
    for (int i = 0; i < N; i++) asm volatile("" : "+r"(r[i])::"memory");
}
__device__ __forceinline__ uint64_t make_desc(uint32_t saddr, uint32_t lbo, uint32_t sbo, uint32_t swz) {
    return (uint64_t)((saddr & 0x3FFFF) >> 4) | ((uint64_t)(lbo >> 4) << 16) | ((uint64_t)(sbo >> 4) << 32) | ((uint64_t)swz << 62);
}
__device__ __forceinline__ void mbar_init(uint32_t bar, uint32_t count) {
    asm volatile("mbarrier.init.shared::cta.b64 [%0], %1;" ::"r"(bar), "r"(count) : "memory");
}
__device__ __forceinline__ void mbar_expect_tx(uint32_t bar, uint32_t bytes) {
    asm volatile("mbarrier.arrive.expect_tx.shared::cta.b64 _, [%0], %1;" ::"r"(bar), "r"(bytes) : "memory");
}
__device__ __forceinline__ void mbar_expect_tx_noarrive(uint32_t bar, uint32_t bytes) {
    asm volatile("mbarrier.expect_tx.relaxed.cta.shared::cta.b64 [%0], %1;" ::"r"(bar), "r"(bytes) : "memory");
}
__device__ __forceinline__ void mbar_arrive(uint32_t bar) {
    asm volatile("mbarrier.arrive.shared::cta.b64 _, [%0];" ::"r"(bar) : "memory");
}
__device__ __forceinline__ bool mbar_try(uint32_t bar, uint32_t parity) {
    uint32_t ok;
    asm volatile("{\n.reg .pred p;\nmbarrier.try_wait.parity.shared::cta.b64 p, [%1], %2;\nselp.u32 %0, 1, 0, p;\n}\n"
                 : "=r"(ok) : "r"(bar), "r"(parity) : "memory");
    return ok != 0;
}
__device__ __forceinline__ void mbar_wait(uint32_t bar, uint32_t parity) {
    uint32_t spins = 0;
    while (!mbar_try(bar, parity)) {
        if (++spins > (1u << 24)) __trap();
    }
}
__device__ __forceinline__ void mbar_wait_w(uint32_t bar, uint32_t parity) {
    uint32_t spins = 0;
    while (!__all_sync(0xffffffffu, mbar_try(bar, parity))) {
        if (++spins > (1u << 24)) __trap();
    }
}
__device__ __forceinline__ void tma2d(uint32_t dst, const CUtensorMap* tm, int c0, int c1, uint32_t bar) {
    asm volatile("cp.async.bulk.tensor.2d.shared::cluster.global.mbarrier::complete_tx::bytes [%0], [%1, {%3, %4}], [%2];"
                 ::"r"(dst), "l"((uint64_t)tm), "r"(bar), "r"(c0), "r"(c1) : "memory");
}
__device__ __forceinline__ void tma3d(uint32_t dst, const CUtensorMap* tm, int c0, int c1, int c2, uint32_t bar) {
    asm volatile("cp.async.bulk.tensor.3d.shared::cluster.global.mbarrier::complete_tx::bytes [%0], [%1, {%3, %4, %5}], [%2];"
                 ::"r"(dst), "l"((uint64_t)tm), "r"(bar), "r"(c0), "r"(c1), "r"(c2) : "memory");
}
__device__ __forceinline__ void tma4d(uint32_t dst, const CUtensorMap* tm, int c0, int c1, int c2, int c3, uint32_t bar) {
    asm volatile("cp.async.bulk.tensor.4d.shared::cluster.global.mbarrier::complete_tx::bytes [%0], [%1, {%3, %4, %5, %6}], [%2];"
                 ::"r"(dst), "l"((uint64_t)tm), "r"(bar), "r"(c0), "r"(c1), "r"(c2), "r"(c3) : "memory");
}
__device__ __forceinline__ void prefetch_tm(const CUtensorMap* tm) { asm volatile("prefetch.tensormap [%0];" ::"l"((uint64_t)tm) : "memory"); }
__device__ __forceinline__ void bulk_s2g(void* dst, uint32_t src, uint32_t bytes) {
    asm volatile("cp.async.bulk.global.shared::cta.bulk_group [%0], [%1], %2;" ::"l"(dst), "r"(src), "r"(bytes) : "memory");
}
__device__ __forceinline__ void bulk_commit() { asm volatile("cp.async.bulk.commit_group;" ::: "memory"); }
__device__ __forceinline__ void bulk_wait_all() { asm volatile("cp.async.bulk.wait_group 0;" ::: "memory"); }
__device__ __forceinline__ void fence_async_global() { asm volatile("fence.proxy.async.global;" ::: "memory"); }
__device__ __forceinline__ void bulk_g2s(uint32_t dst, const void* src, uint32_t bytes, uint32_t bar) {
    asm volatile("cp.async.bulk.shared::cluster.global.mbarrier::complete_tx::bytes [%0], [%1], %2, [%3];"
                 ::"r"(dst), "l"(src), "r"(bytes), "r"(bar) : "memory");
}
__device__ __forceinline__ void fence_async_smem() { asm volatile("fence.proxy.async.shared::cta;" ::: "memory"); }
__device__ __forceinline__ void named_bar(int id, int n) { asm volatile("bar.sync %0, %1;" ::"r"(id), "r"(n) : "memory"); }
__device__ __forceinline__ bool named_bar_and(int id, int n, bool pred) {
    uint32_t r;
    asm volatile("{\n.reg .pred p, q;\nsetp.ne.u32 p, %3, 0;\nbarrier.cta.red.and.pred q, %1, %2, p;\nselp.u32 %0, 1, 0, q;\n}\n"
                 : "=r"(r) : "r"(id), "r"(n), "r"((uint32_t)pred) : "memory");
    return r != 0;
}
__device__ __forceinline__ unsigned int ld_acquire(const unsigned int* p) {
    unsigned int v;
    asm volatile("ld.acquire.gpu.global.u32 %0, [%1];" : "=r"(v) : "l"(p) : "memory");
    return v;
}
__device__ __forceinline__ void red_release_add(unsigned int* p, unsigned int v) {
    asm volatile("red.release.gpu.global.add.u32 [%0], %1;" ::"l"(p), "r"(v) : "memory");
}
__device__ __forceinline__ void poll_counter(const unsigned int* p, unsigned int target) {
    uint32_t spins = 0;
    while (ld_acquire(p) < target) {
        if (++spins > (1u << 22)) __trap();
    }
}
__device__ __forceinline__ float ex2f(float x) { float y; asm("ex2.approx.ftz.f32 %0, %1;" : "=f"(y) : "f"(x)); return y; }
__device__ __forceinline__ uint32_t pack_f16(float lo, float hi) { uint32_t r; asm("cvt.rn.f16x2.f32 %0, %1, %2;" : "=r"(r) : "f"(hi), "f"(lo)); return r; }
__device__ __forceinline__ uint32_t pack_bf16(float lo, float hi) { uint32_t r; asm("cvt.rn.bf16x2.f32 %0, %1, %2;" : "=r"(r) : "f"(hi), "f"(lo)); return r; }
__device__ __forceinline__ float bf_lo(uint32_t v) { return __uint_as_float(v << 16); }
__device__ __forceinline__ float bf_hi(uint32_t v) { return __uint_as_float(v & 0xFFFF0000u); }
__device__ __forceinline__ uint32_t hfma2(uint32_t a, uint32_t b, uint32_t c) { uint32_t r; asm("fma.rn.f16x2 %0, %1, %2, %3;" : "=r"(r) : "r"(a), "r"(b), "r"(c)); return r; }
__device__ __forceinline__ uint32_t bmul2(uint32_t a, uint32_t b) { uint32_t r; asm("mul.rn.bf16x2 %0, %1, %2;" : "=r"(r) : "r"(a), "r"(b)); return r; }
__device__ __forceinline__ uint32_t badd2(uint32_t a, uint32_t b) { uint32_t r; asm("add.rn.bf16x2 %0, %1, %2;" : "=r"(r) : "r"(a), "r"(b)); return r; }
template <int LUT> __device__ __forceinline__ uint32_t lop3(uint32_t a, uint32_t b, uint32_t c) {
    uint32_t r; asm("lop3.b32 %0, %1, %2, %3, %4;" : "=r"(r) : "r"(a), "r"(b), "r"(c), "n"(LUT)); return r;
}
__device__ __forceinline__ uint32_t lds32(uint32_t a) { uint32_t v; asm volatile("ld.shared.u32 %0, [%1];" : "=r"(v) : "r"(a)); return v; }
__device__ __forceinline__ float ldsf(uint32_t a) { float v; asm volatile("ld.shared.f32 %0, [%1];" : "=f"(v) : "r"(a)); return v; }
__device__ __forceinline__ uint4 lds128(uint32_t a) { uint4 v; asm volatile("ld.shared.v4.u32 {%0,%1,%2,%3}, [%4];" : "=r"(v.x), "=r"(v.y), "=r"(v.z), "=r"(v.w) : "r"(a)); return v; }
__device__ __forceinline__ void lds64(uint32_t a, uint32_t& x, uint32_t& y) { asm volatile("ld.shared.v2.u32 {%0,%1}, [%2];" : "=r"(x), "=r"(y) : "r"(a)); }
__device__ __forceinline__ void sts32(uint32_t a, uint32_t v) { asm volatile("st.shared.u32 [%0], %1;" ::"r"(a), "r"(v) : "memory"); }
__device__ __forceinline__ void sts64f(uint32_t a, float x, float y) { asm volatile("st.shared.v2.f32 [%0], {%1,%2};" ::"r"(a), "f"(x), "f"(y) : "memory"); }
__device__ __forceinline__ void sts128(uint32_t a, uint32_t x, uint32_t y, uint32_t z, uint32_t w) {
    asm volatile("st.shared.v4.u32 [%0], {%1,%2,%3,%4};" ::"r"(a), "r"(x), "r"(y), "r"(z), "r"(w) : "memory");
}

__device__ __forceinline__ void wg_ss_n32_tb(float* d, uint64_t descA, uint64_t descB) {
    asm volatile("wgmma.mma_async.sync.aligned.m64n32k16.f32.bf16.bf16 {%0,%1,%2,%3,%4,%5,%6,%7,%8,%9,%10,%11,%12,%13,%14,%15}, %16, %17, 1, 1, 1, 0, 1;\n"
        : "+f"(d[0]), "+f"(d[1]), "+f"(d[2]), "+f"(d[3]), "+f"(d[4]), "+f"(d[5]), "+f"(d[6]), "+f"(d[7]), "+f"(d[8]), "+f"(d[9]), "+f"(d[10]), "+f"(d[11]), "+f"(d[12]), "+f"(d[13]), "+f"(d[14]), "+f"(d[15])
        : "l"(descA), "l"(descB));
}
__device__ __forceinline__ void wg_qk_n64(float* d, const uint32_t* a, uint64_t desc) {
    asm volatile("wgmma.mma_async.sync.aligned.m64n64k16.f32.bf16.bf16 {%0,%1,%2,%3,%4,%5,%6,%7,%8,%9,%10,%11,%12,%13,%14,%15,%16,%17,%18,%19,%20,%21,%22,%23,%24,%25,%26,%27,%28,%29,%30,%31}, {%32,%33,%34,%35}, %36, 0, 1, 1, 0;\n"
        : "+f"(d[0]), "+f"(d[1]), "+f"(d[2]), "+f"(d[3]), "+f"(d[4]), "+f"(d[5]), "+f"(d[6]), "+f"(d[7]), "+f"(d[8]), "+f"(d[9]), "+f"(d[10]), "+f"(d[11]), "+f"(d[12]), "+f"(d[13]), "+f"(d[14]), "+f"(d[15]), "+f"(d[16]), "+f"(d[17]), "+f"(d[18]), "+f"(d[19]), "+f"(d[20]), "+f"(d[21]), "+f"(d[22]), "+f"(d[23]), "+f"(d[24]), "+f"(d[25]), "+f"(d[26]), "+f"(d[27]), "+f"(d[28]), "+f"(d[29]), "+f"(d[30]), "+f"(d[31])
        : "r"(a[0]), "r"(a[1]), "r"(a[2]), "r"(a[3]), "l"(desc));
}
__device__ __forceinline__ void wg_pv_n24(float* d, const uint32_t* a, uint64_t desc) {
    asm volatile("wgmma.mma_async.sync.aligned.m64n24k16.f32.f16.f16 {%0,%1,%2,%3,%4,%5,%6,%7,%8,%9,%10,%11}, {%12,%13,%14,%15}, %16, 1, 1, 1, 1;\n"
        : "+f"(d[0]), "+f"(d[1]), "+f"(d[2]), "+f"(d[3]), "+f"(d[4]), "+f"(d[5]), "+f"(d[6]), "+f"(d[7]), "+f"(d[8]), "+f"(d[9]), "+f"(d[10]), "+f"(d[11])
        : "r"(a[0]), "r"(a[1]), "r"(a[2]), "r"(a[3]), "l"(desc));
}
__device__ __forceinline__ void wg_cv_n32(float* d, const uint32_t* a, uint64_t desc) {
    asm volatile("wgmma.mma_async.sync.aligned.m64n32k16.f32.bf16.bf16 {%0,%1,%2,%3,%4,%5,%6,%7,%8,%9,%10,%11,%12,%13,%14,%15}, {%16,%17,%18,%19}, %20, 1, 1, 1, 0;\n"
        : "+f"(d[0]), "+f"(d[1]), "+f"(d[2]), "+f"(d[3]), "+f"(d[4]), "+f"(d[5]), "+f"(d[6]), "+f"(d[7]), "+f"(d[8]), "+f"(d[9]), "+f"(d[10]), "+f"(d[11]), "+f"(d[12]), "+f"(d[13]), "+f"(d[14]), "+f"(d[15])
        : "r"(a[0]), "r"(a[1]), "r"(a[2]), "r"(a[3]), "l"(desc));
}
__device__ __forceinline__ void wg_cv_n64(float* d, const uint32_t* a, uint64_t desc) {
    asm volatile("wgmma.mma_async.sync.aligned.m64n64k16.f32.bf16.bf16 {%0,%1,%2,%3,%4,%5,%6,%7,%8,%9,%10,%11,%12,%13,%14,%15,%16,%17,%18,%19,%20,%21,%22,%23,%24,%25,%26,%27,%28,%29,%30,%31}, {%32,%33,%34,%35}, %36, 1, 1, 1, 0;\n"
        : "+f"(d[0]), "+f"(d[1]), "+f"(d[2]), "+f"(d[3]), "+f"(d[4]), "+f"(d[5]), "+f"(d[6]), "+f"(d[7]), "+f"(d[8]), "+f"(d[9]), "+f"(d[10]), "+f"(d[11]), "+f"(d[12]), "+f"(d[13]), "+f"(d[14]), "+f"(d[15]), "+f"(d[16]), "+f"(d[17]), "+f"(d[18]), "+f"(d[19]), "+f"(d[20]), "+f"(d[21]), "+f"(d[22]), "+f"(d[23]), "+f"(d[24]), "+f"(d[25]), "+f"(d[26]), "+f"(d[27]), "+f"(d[28]), "+f"(d[29]), "+f"(d[30]), "+f"(d[31])
        : "r"(a[0]), "r"(a[1]), "r"(a[2]), "r"(a[3]), "l"(desc));
}

template <int N> __device__ __forceinline__ void wg_cv(float* d, const uint32_t* a, uint64_t desc);
template <> __device__ __forceinline__ void wg_cv<32>(float* d, const uint32_t* a, uint64_t s) { wg_cv_n32(d, a, s); }
template <> __device__ __forceinline__ void wg_cv<64>(float* d, const uint32_t* a, uint64_t s) { wg_cv_n64(d, a, s); }

constexpr uint32_t POLYMASK = 0xB5B5u;
__device__ __forceinline__ void softmax_fast(const float* s, uint32_t* p, uint32_t mlo) {
    const uint32_t C3 = 0x2cfb2cfbu, C2 = 0x9fec9fecu, C1 = 0x37a837a8u, C0 = 0x37383738u;
#pragma unroll
    for (int i = 0; i < 16; i++) {
        const float s0 = s[2 * i], s1 = s[2 * i + 1];
        if ((POLYMASK >> i) & 1) {
            const float t0 = s0 + 12303.0f, t1 = s1 + 12303.0f;
            const uint32_t T = __byte_perm(__float_as_uint(t0), __float_as_uint(t1), 0x5410);
            const uint32_t U = lop3<0xEA>(T, mlo, 0x3C003C00u);
            uint32_t h = hfma2(U, C3, C2);
            h = hfma2(h, U, C1);
            h = hfma2(h, U, C0);
            p[i] = lop3<0xE4>(h, T, 0x03FF03FFu);
        } else {
            p[i] = pack_f16(ex2f(s0), ex2f(s1));
        }
    }
}

__device__ __forceinline__ void gemm_chunk(float* acc, uint32_t a_addr, uint32_t b_addr) {
    const uint64_t da = make_desc(a_addr, 16, 1024, 1);
    const uint64_t db = make_desc(b_addr, 8192, 1024, 1);
#pragma unroll
    for (int ks = 0; ks < 4; ks++) wg_ss_n32_tb(acc, da + ks * 2, db + ks * 128);
}

__device__ __forceinline__ void wo_half(uint32_t sb, const CUtensorMap* tm_wo, int hg) {
    uint32_t old;
    asm volatile("atom.shared.add.u32 %0, [%1], 1;" : "=r"(old) : "r"(sb + OFF_MISC + 8) : "memory");
    if (old == 3) {
        mbar_expect_tx(sb + OFF_BAR + 8 * (B_WO + 2), 32768);
        tma4d(sb + OFF_K, tm_wo, 0, 0, hg * 2, 4, sb + OFF_BAR + 8 * (B_WO + 2));
    }
}

struct Params {
    const __nv_bfloat16 *aq, *ak, *av, *shift_k, *ssm_D;
    __nv_bfloat16* out;
};

template <int NQ>
__device__ __forceinline__ void conv_phase(float* Dn, uint32_t zaddr, uint64_t hdesc) {
    uint32_t a[2][16];
#pragma unroll
    for (int st = 0; st < 8; st++) {
        uint32_t* aa = a[st & 1];
        if (st >= 2) wg_wait<1>();
#pragma unroll
        for (int u = 0; u < 2; u++) {
            const uint32_t z = zaddr + (st * 2 + u) * 256;
            lds64(z, aa[8 * u + 0], aa[8 * u + 1]);      lds64(z - 32, aa[8 * u + 2], aa[8 * u + 3]);
            lds64(z - 64, aa[8 * u + 4], aa[8 * u + 5]); lds64(z - 96, aa[8 * u + 6], aa[8 * u + 7]);
        }
        wg_fence();
#pragma unroll
        for (int u = 0; u < 2; u++) {
            const int qi = st * 2 + u;
            wg_cv<NQ>(Dn, &aa[8 * u], hdesc - qi * 8);
            wg_cv<NQ>(Dn, &aa[8 * u + 4], hdesc - qi * 8 + 2);
        }
        wg_commit();
    }
    wg_wait<0>();
    fence_regs<NQ / 2>(Dn);
}

__global__ void __launch_bounds__(NTHREADS, 1)
fused_kernel(const __grid_constant__ CUtensorMap tm_x,
             const __grid_constant__ CUtensorMap tm_wq, const __grid_constant__ CUtensorMap tm_wo,
             const __grid_constant__ CUtensorMap tm_wk, const __grid_constant__ CUtensorMap tm_wv,
             const __grid_constant__ CUtensorMap tm_o, const __grid_constant__ CUtensorMap tm_h, const Params prm) {
    extern __shared__ __align__(1024) uint8_t smem_raw[];
    const uint32_t sb = (uint32_t)__cvta_generic_to_shared(smem_raw);
    const int warp_id = __shfl_sync(0xffffffffu, threadIdx.x >> 5, 0);
    const int lane = threadIdx.x & 31;
    const int g = lane >> 2, t = lane & 3;
    const int b = blockIdx.x, pb = b >> 2, hg = b & 3;
    auto bar = [&](int i) { return sb + OFF_BAR + 8 * i; };

    if (threadIdx.x == 512) {
        TSTAMP(0);
        prefetch_tm(&tm_x); prefetch_tm(&tm_wq); prefetch_tm(&tm_wk); prefetch_tm(&tm_wv);
        mbar_init(bar(B_WKV), 1);
        for (int j = 0; j < 4; j++) { mbar_init(bar(B_X + j), 1); mbar_init(bar(B_W + j), 1); mbar_init(bar(B_WO + j), 1); mbar_init(bar(B_O + j), 1); }
        sts32(sb + OFF_MISC + 8, 0u);
        for (int j = 0; j < 8; j++) mbar_init(bar(B_KV + j), j == 0 ? 2 : 1);
        mbar_init(bar(B_QEMPTY), 4); mbar_init(bar(B_QEMPTY + 1), 4);
        mbar_init(bar(B_QDONE), 4); mbar_init(bar(B_ATT), 4);
        mbar_init(bar(B_H), 1); mbar_init(bar(B_CV), 1);
        asm volatile("fence.mbarrier_init.release.cluster;" ::: "memory");
    }

    if (warp_id < 16) {
        const int w = warp_id >> 2, wq = warp_id & 3;
        __syncthreads();
        float acc[16];
#pragma unroll
        for (int i = 0; i < 16; i++) acc[i] = 0.f;
        fence_regs<16>(acc);
        const uint32_t bcol = (w >> 1) * 8192 + (w & 1) * 64;
#pragma unroll 1
        for (int jj = 0; jj < 4; jj++) {
            mbar_wait_w(bar(B_X + jj), 0);
            mbar_wait_w(bar(B_W + jj), 0);
            if (threadIdx.x == 0 && jj < 4) TSTAMP(jj == 0 ? 23 : jj == 1 ? 24 : jj == 2 ? 26 : 27);
            wg_fence();
            gemm_chunk(acc, sb + OFF_X + jj * 16384, sb + OFF_V + (jj & 1) * 32768 + bcol);
            gemm_chunk(acc, sb + OFF_X + jj * 16384 + 8192, sb + OFF_V + (jj & 1) * 32768 + 16384 + bcol);
            wg_commit();
            wg_wait<0>();
            if (jj < 2 && (threadIdx.x & 127) == 0) mbar_arrive(bar(B_QEMPTY + jj));
        }
        fence_regs<16>(acc);
        if ((threadIdx.x & 127) == 0) { mbar_arrive(bar(B_QDONE)); if (w == 0) TSTAMP(1); }
        uint32_t qa[2][4];
        float qn[2];
        {
            const float c = 0.25f * 1.4426950408889634f;
#pragma unroll
            for (int hh = 0; hh < 2; hh++) {
                float n0 = 0.f, n1 = 0.f;
#pragma unroll
                for (int i = 0; i < 4; i++) {
                    const uint32_t qb = pack_bf16(acc[8 * hh + 2 * i], acc[8 * hh + 2 * i + 1]);
                    const uint32_t qs = pack_bf16(bf_lo(qb) * c, bf_hi(qb) * c);
                    qa[hh][i] = qs;
                    const float e = bf_lo(qs) * bf_lo(qs) + bf_hi(qs) * bf_hi(qs);
                    if (i & 1) n1 += e; else n0 += e;
                }
                n0 += __shfl_xor_sync(0xffffffffu, n0, 1); n0 += __shfl_xor_sync(0xffffffffu, n0, 2);
                n1 += __shfl_xor_sync(0xffffffffu, n1, 1); n1 += __shfl_xor_sync(0xffffffffu, n1, 2);
                qn[hh] = fmaxf(n0, n1);
            }
        }
        {
            const int kpr = lane & 7, kcg = wq * 4 + (lane >> 3);
            const int kp0 = pb * 64 + w * 16 + 2 * kpr, kch0 = hg * 128 + kcg * 8;
            uint4 kr[5], vr[2], sw[4];
#pragma unroll
            for (int i = 0; i < 5; i++) {
                const int sx = kp0 - 3 + i;
                kr[i] = sx >= 0 ? __ldg((const uint4*)(prm.ak + (size_t)sx * 512 + kch0)) : make_uint4(0u, 0u, 0u, 0u);
            }
#pragma unroll
            for (int i = 0; i < 2; i++) vr[i] = __ldg((const uint4*)(prm.av + (size_t)(kp0 + i) * 512 + kch0));
#pragma unroll
            for (int i = 0; i < 4; i++) sw[i] = __ldg((const uint4*)(prm.shift_k + kch0 * 4) + i);
            uint32_t x0[4], x1[4];
#pragma unroll
            for (int i = 0; i < 4; i++) {
                const uint32_t w0 = __byte_perm(sw[i].x, sw[i].z, 0x5410), w1 = __byte_perm(sw[i].x, sw[i].z, 0x7632);
                const uint32_t w2 = __byte_perm(sw[i].y, sw[i].w, 0x5410), w3 = __byte_perm(sw[i].y, sw[i].w, 0x7632);
                const uint32_t k0 = (&kr[0].x)[i], k1 = (&kr[1].x)[i], k2 = (&kr[2].x)[i], k3 = (&kr[3].x)[i], k4 = (&kr[4].x)[i];
                x0[i] = bmul2(badd2(badd2(badd2(bmul2(k0, w3), bmul2(k1, w2)), bmul2(k2, w1)), bmul2(k3, w0)), (&vr[0].x)[i]);
                x1[i] = bmul2(badd2(badd2(badd2(bmul2(k1, w3), bmul2(k2, w2)), bmul2(k3, w1)), bmul2(k4, w0)), (&vr[1].x)[i]);
            }
            uint32_t* dst = (uint32_t*)(g_kvT + (size_t)kch0 * S_LEN + kp0);
#pragma unroll
            for (int i = 0; i < 4; i++) {
                dst[(2 * i) * (S_LEN / 2)] = __byte_perm(x0[i], x1[i], 0x5410);
                dst[(2 * i + 1) * (S_LEN / 2)] = __byte_perm(x0[i], x1[i], 0x7632);
            }
            named_bar(1 + w, 128);
            if ((threadIdx.x & 127) == 0) { red_release_add(&g_kvt_count[hg], 1); if (w == 0) TSTAMP(34); }
        }
        uint32_t mlo = 0x03FF03FFu; asm volatile("" : "+r"(mlo));
        const uint64_t kdesc0 = make_desc(sb + OFF_K, 128, 256, 0);
        const uint64_t vdesc0 = make_desc(sb + OFF_VONES - 256, 128, 256, 0);
        constexpr uint64_t VSTEP = ((uint64_t)16 << 32) - 16;
        mbar_wait_w(bar(B_KV + 0), 0);
        if ((threadIdx.x & 127) == 0 && w == 0) TSTAMP(2);
        const float kmax2 = ldsf(sb + OFF_MISC);
        const bool fast0 = __all_sync(0xffffffffu, named_bar_and(1 + w, 128, qn[0] * kmax2 <= 193.0f));
        const bool fast1 = __all_sync(0xffffffffu, named_bar_and(1 + w, 128, qn[1] * kmax2 <= 193.0f));
        uint32_t a[4] = {qa[0][0], qa[0][1], qa[0][2], qa[0][3]};
#pragma unroll 1
        for (int hh = 0; hh < 2; hh++) {
            const bool fast = hh ? fast1 : fast0;
            float S[32], O[12];
#pragma unroll
            for (int i = 0; i < 12; i++) O[i] = 0.f;
#pragma unroll
            for (int i = 0; i < 32; i++) S[i] = 0.f;
            fence_regs<12>(O); fence_regs<32>(S);
            wg_fence();
            wg_qk_n64(S, a, kdesc0);
            wg_commit();
            wg_wait<0>();
            uint64_t kd = kdesc0 + 128, vd = vdesc0;
            if (fast) {
                uint32_t P[16];
#pragma unroll 1
                for (int c = 0; c < 8; c++) {
                    if (c < 7) mbar_wait_w(bar(B_KV + c + 1), 0);
#pragma unroll 1
                    for (int j = 0; j < 4; j++) {
                        fence_regs<32>(S);
                        softmax_fast(S, P, mlo);
                        fence_regs<32>(S);
                        wg_fence();
                        wg_qk_n64(S, a, kd);
#pragma unroll
                        for (int i = 0; i < 4; i++) wg_pv_n24(O, &P[4 * i], vd + i * VSTEP);
                        wg_commit();
                        wg_wait<0>();
                        kd += 128; vd += 4 * VSTEP;
                    }
                    if (hh == 1 && c == 3 && (threadIdx.x & 127) == 0) wo_half(sb, &tm_wo, hg);
                }
            } else {
                uint32_t P[16];
                float m0 = -INFINITY, m1 = -INFINITY;
#pragma unroll 1
                for (int c = 0; c < 8; c++) {
                    if (c < 7) mbar_wait_w(bar(B_KV + c + 1), 0);
#pragma unroll 1
                    for (int j = 0; j < 4; j++) {
                        fence_regs<32>(S); fence_regs<12>(O);
                        float x0 = m0, x1 = m1;
#pragma unroll
                        for (int i = 0; i < 8; i++) {
                            x0 = fmaxf(x0, fmaxf(S[4 * i], S[4 * i + 1]));
                            x1 = fmaxf(x1, fmaxf(S[4 * i + 2], S[4 * i + 3]));
                        }
                        x0 = fmaxf(x0, __shfl_xor_sync(0xffffffffu, x0, 1)); x0 = fmaxf(x0, __shfl_xor_sync(0xffffffffu, x0, 2));
                        x1 = fmaxf(x1, __shfl_xor_sync(0xffffffffu, x1, 1)); x1 = fmaxf(x1, __shfl_xor_sync(0xffffffffu, x1, 2));
                        const float r0 = ex2f(m0 - x0), r1 = ex2f(m1 - x1);
                        m0 = x0; m1 = x1;
#pragma unroll
                        for (int i = 0; i < 3; i++) { O[4 * i] *= r0; O[4 * i + 1] *= r0; O[4 * i + 2] *= r1; O[4 * i + 3] *= r1; }
#pragma unroll
                        for (int i = 0; i < 8; i++) {
                            P[2 * i] = pack_f16(ex2f(S[4 * i] - m0), ex2f(S[4 * i + 1] - m0));
                            P[2 * i + 1] = pack_f16(ex2f(S[4 * i + 2] - m1), ex2f(S[4 * i + 3] - m1));
                        }
                        fence_regs<32>(S); fence_regs<12>(O);
                        wg_fence();
                        wg_qk_n64(S, a, kd);
#pragma unroll
                        for (int i = 0; i < 4; i++) wg_pv_n24(O, &P[4 * i], vd + i * VSTEP);
                        wg_commit();
                        wg_wait<0>();
                        kd += 128; vd += 4 * VSTEP;
                    }
                    if (hh == 1 && c == 3 && (threadIdx.x & 127) == 0) wo_half(sb, &tm_wo, hg);
                }
            }
            fence_regs<12>(O);
            const float vscale = ldsf(sb + OFF_MISC + 4);
            const float i0 = __fdividef(vscale, O[4]), i1 = __fdividef(vscale, O[6]);
            const int row = pb * 64 + wq * 16 + g;
            uint32_t* o0 = (uint32_t*)(g_o + (size_t)row * 512 + (hg * 8 + 2 * w + hh) * 16) + t;
            uint32_t* o1 = o0 + 8 * 256;
            o0[0] = pack_bf16(O[0] * i0, O[1] * i0);
            o0[4] = pack_bf16(O[8] * i0, O[9] * i0);
            o1[0] = pack_bf16(O[2] * i1, O[3] * i1);
            o1[4] = pack_bf16(O[10] * i1, O[11] * i1);
            if ((threadIdx.x & 127) == 0 && w == 0) { TSTAMP(3 + hh); CSTAMP(40 + hh); }
#pragma unroll
            for (int i = 0; i < 4; i++) a[i] = qa[1][i];
        }
        named_bar(1 + w, 128);
        if ((threadIdx.x & 127) == 0) {
            red_release_add(&g_o_count[pb], 1);
            mbar_arrive(bar(B_ATT));
        }
        if (threadIdx.x == 0) {
            TSTAMP(30);
            mbar_wait(bar(B_ATT), 0);
            TSTAMP(31);
            poll_counter(&g_o_count[pb], 16);
            TSTAMP(18);
            fence_async_global();
            for (int jj = 0; jj < 4; jj++) {
                mbar_expect_tx(bar(B_O + jj), 16384);
                tma3d(sb + OFF_V + jj * 16384, &tm_o, 0, pb * 64, 2 * jj, bar(B_O + jj));
            }
            __threadfence();
            if (atomicAdd(&g_done, 1) == 2 * NCTA - 1) {
                for (int i = 0; i < NCTA; i++) g_stats[i] = 0ull;
                for (int i = 0; i < 4; i++) { g_kvt_count[i] = 0; g_z_count[i] = 0; }
                for (int i = 0; i < 32; i++) g_o_count[i] = 0;
                g_done = 0;
                __threadfence();
            }
        }
        __syncwarp();
#pragma unroll
        for (int i = 0; i < 16; i++) acc[i] = 0.f;
        fence_regs<16>(acc);
#pragma unroll 1
        for (int jj = 0; jj < 4; jj++) {
            mbar_wait_w(bar(B_WO + jj), 0);
            mbar_wait_w(bar(B_O + jj), 0);
            if (threadIdx.x == 0 && (jj == 0 || jj == 3)) TSTAMP(jj == 0 ? 32 : 33);
            const uint32_t wb = sb + (jj < 2 ? OFF_X + jj * 32768 : (jj == 2 ? OFF_K : OFF_C)) + bcol;
            wg_fence();
            gemm_chunk(acc, sb + OFF_V + jj * 16384, wb);
            gemm_chunk(acc, sb + OFF_V + jj * 16384 + 8192, wb + 16384);
            wg_commit();
        }
        wg_wait<0>();
        fence_regs<16>(acc);
        {
            const int row = pb * 64 + wq * 16 + g;
            uint32_t* d0 = (uint32_t*)(prm.out + (size_t)row * 1024 + 512 + hg * 128 + w * 32) + t;
            uint32_t* d1 = d0 + 8 * 512;
#pragma unroll
            for (int i = 0; i < 4; i++) {
                d0[4 * i] = pack_bf16(acc[4 * i], acc[4 * i + 1]);
                d1[4 * i] = pack_bf16(acc[4 * i + 2], acc[4 * i + 3]);
            }
        }
        if ((threadIdx.x & 127) == 0 && w == 0) TSTAMP(5);
    } else {
        const int wa = warp_id - 16, tau = threadIdx.x - 512;
        __syncthreads();
        const bool kv_cta = (hg == (pb & 3));
        if (tau == 0) {
            if (kv_cta) {
                mbar_expect_tx(bar(B_WKV), 32768);
                tma3d(sb + OFF_C, &tm_wk, 0, 0, 0, bar(B_WKV));
                tma3d(sb + OFF_C + 16384, &tm_wv, 0, 0, 0, bar(B_WKV));
            }
            for (int jj = 0; jj < 4; jj++) {
                mbar_expect_tx(bar(B_X + jj), 16384);
                tma3d(sb + OFF_X + jj * 16384, &tm_x, 0, pb * 64, 2 * jj, bar(B_X + jj));
                if (!kv_cta && jj < 2) {
                    mbar_expect_tx(bar(B_W + jj), 32768);
                    tma4d(sb + OFF_V + jj * 32768, &tm_wq, 0, 0, hg * 2, 2 * jj, bar(B_W + jj));
                }
            }
            TSTAMP(25);
        }
        __syncwarp();
        if (kv_cta) {
            float acc[16];
#pragma unroll
            for (int i = 0; i < 16; i++) acc[i] = 0.f;
            fence_regs<16>(acc);
            mbar_wait_w(bar(B_WKV), 0);
            if (tau == 0) TSTAMP(20);
#pragma unroll
            for (int jj = 0; jj < 4; jj++) {
                mbar_wait_w(bar(B_X + jj), 0);
                wg_fence();
#pragma unroll
                for (int j = 2 * jj; j < 2 * jj + 2; j++) {
                    const uint64_t da = make_desc(sb + OFF_X + j * 8192, 16, 1024, 1);
                    const uint64_t db = make_desc(sb + OFF_C + j * 2048, 16384, 256, 3);
#pragma unroll
                    for (int ks = 0; ks < 4; ks++) wg_ss_n32_tb(acc, da + ks * 2, db + ks * 32);
                }
                wg_commit();
            }
            wg_wait<0>();
            fence_regs<16>(acc);
            if (tau == 0) TSTAMP(22);
            {
                uint32_t kk[4], vv[4];
#pragma unroll
                for (int i = 0; i < 4; i++) { kk[i] = pack_bf16(acc[2 * i], acc[2 * i + 1]); vv[i] = pack_bf16(acc[8 + 2 * i], acc[8 + 2 * i + 1]); }
                const int s = 4 * pb + wa;
                uint32_t* kp = (uint32_t*)(g_kimg + s * 512 + g * 16 + 4 * t);
                kp[0] = kk[0]; kp[64] = kk[1]; kp[32] = kk[2]; kp[96] = kk[3];
                uint32_t* vlo = (uint32_t*)(g_vimg + (127 - s) * 256 + g * 16 + 4 * t);
                uint32_t* vhi = (uint32_t*)(g_vimg + 32768 + 256 + s * 256 + g * 16 + 4 * t);
                vlo[0] = pack_f16(bf_lo(vv[0]), bf_hi(vv[0])); vlo[32] = pack_f16(bf_lo(vv[1]), bf_hi(vv[1]));
                vhi[0] = pack_f16(bf_lo(vv[2]), bf_hi(vv[2])); vhi[32] = pack_f16(bf_lo(vv[3]), bf_hi(vv[3]));
                uint32_t* vr = (uint32_t*)(g_vraw + (size_t)(16 * s + g) * 16) + t;
                vr[0] = vv[0]; vr[64] = vv[1]; vr[4] = vv[2]; vr[68] = vv[3];
                float n0 = bf_lo(kk[0]) * bf_lo(kk[0]) + bf_hi(kk[0]) * bf_hi(kk[0]) + bf_lo(kk[2]) * bf_lo(kk[2]) + bf_hi(kk[2]) * bf_hi(kk[2]);
                float n1 = bf_lo(kk[1]) * bf_lo(kk[1]) + bf_hi(kk[1]) * bf_hi(kk[1]) + bf_lo(kk[3]) * bf_lo(kk[3]) + bf_hi(kk[3]) * bf_hi(kk[3]);
                n0 += __shfl_xor_sync(0xffffffffu, n0, 1); n0 += __shfl_xor_sync(0xffffffffu, n0, 2);
                n1 += __shfl_xor_sync(0xffffffffu, n1, 1); n1 += __shfl_xor_sync(0xffffffffu, n1, 2);
                float km = fmaxf(n0, n1), vm = 0.f;
#pragma unroll
                for (int i = 0; i < 4; i++) vm = fmaxf(vm, fmaxf(fabsf(bf_lo(vv[i])), fabsf(bf_hi(vv[i]))));
#pragma unroll
                for (int o = 4; o < 32; o <<= 1) km = fmaxf(km, __shfl_xor_sync(0xffffffffu, km, o));
#pragma unroll
                for (int o = 1; o < 32; o <<= 1) vm = fmaxf(vm, __shfl_xor_sync(0xffffffffu, vm, o));
                __syncwarp();
                if (lane == 0) {
                    const unsigned long long rec = ((unsigned long long)(__float_as_uint(vm) | 0x80000000u) << 32) | __float_as_uint(km);
                    asm volatile("st.release.gpu.global.u64 [%0], %1;" ::"l"(&g_stats[s]), "l"(rec) : "memory");
                    if (wa == 0) TSTAMP(8);
                }
            }
            if (tau == 0) {
                for (int jj = 0; jj < 2; jj++) {
                    mbar_expect_tx(bar(B_W + jj), 32768);
                    tma4d(sb + OFF_V + jj * 32768, &tm_wq, 0, 0, hg * 2, 2 * jj, bar(B_W + jj));
                }
            }
            __syncwarp();
        }
        const int c0 = 4 * b;
        if (wa == 0) {
            if (lane == 0) {
                for (int jj = 2; jj < 4; jj++) {
                    mbar_wait(bar(B_QEMPTY + jj - 2), 0);
                    mbar_expect_tx(bar(B_W + jj), 32768);
                    tma4d(sb + OFF_V + (jj - 2) * 32768, &tm_wq, 0, 0, hg * 2, 2 * jj, bar(B_W + jj));
                }
            }
            __syncwarp();
            float km = 0.f, vm = 0.f;
            {
                unsigned long long rec[4];
                uint32_t spins = 0;
                bool ok;
                do {
                    ok = true;
#pragma unroll
                    for (int i = 0; i < 4; i++) {
                        asm volatile("ld.acquire.gpu.global.u64 %0, [%1];" : "=l"(rec[i]) : "l"(&g_stats[lane + 32 * i]) : "memory");
                        ok = ok && (rec[i] >> 63);
                    }
                    if (++spins > (1u << 22)) __trap();
                } while (!__all_sync(0xffffffffu, ok));
#pragma unroll
                for (int i = 0; i < 4; i++) { km = fmaxf(km, __uint_as_float((uint32_t)rec[i])); vm = fmaxf(vm, __uint_as_float((uint32_t)(rec[i] >> 32) & 0x7FFFFFFFu)); }
            }
            if (lane == 0) {
                TSTAMP(16);
                fence_async_global();
                for (int c = 0; c < 8; c++) {
                    mbar_expect_tx_noarrive(bar(B_KV + c), 8192);
                    bulk_g2s(sb + OFF_K + c * 8192, g_kimg + c * 8192, 8192, bar(B_KV + c));
                }
                TSTAMP(28);
            }
#pragma unroll
            for (int o = 1; o < 32; o <<= 1) { km = fmaxf(km, __shfl_xor_sync(0xffffffffu, km, o)); vm = fmaxf(vm, __shfl_xor_sync(0xffffffffu, vm, o)); }
            const bool vdirect = (vm <= 32768.f && vm >= 9.765625e-4f) || vm == 0.f;
            float vs = 1.f;
            if (!vdirect && vm < INFINITY) {
                int e = (int)((__float_as_uint(vm) >> 23) & 0xFF) - 127;
                e = max(-100, min(100, e));
                vs = __uint_as_float((uint32_t)(127 + e - 13) << 23);
            }
            if (lane == 0) {
                asm volatile("st.shared.f32 [%0], %1;" ::"r"(sb + OFF_MISC), "f"(km) : "memory");
                asm volatile("st.shared.f32 [%0], %1;" ::"r"(sb + OFF_MISC + 4), "f"(vs) : "memory");
                mbar_wait(bar(B_QDONE), 0);
                TSTAMP(17);
                for (int c = 0; c < 8; c++) {
                    if (vdirect) {
                        mbar_expect_tx(bar(B_KV + c), 8192);
                        bulk_g2s(sb + OFF_V + (112 - 16 * c) * 256, g_vimg + (112 - 16 * c) * 256, 4096, bar(B_KV + c));
                        bulk_g2s(sb + OFF_VONES + 256 + c * 4096, g_vimg + 32768 + 256 + c * 4096, 4096, bar(B_KV + c));
                    }
                }
            }
            __syncwarp();
            sts32(sb + OFF_VONES + lane * 8, 0x3C003C00u);
            sts32(sb + OFF_VONES + lane * 8 + 4, 0x3C003C00u);
            if (!vdirect) {
                const float inv = 1.f / vs;
                for (int idx = lane; idx < S_LEN * 8; idx += 32) {
                    const int key = idx >> 3, dp = idx & 7;
                    const uint32_t v = __ldcg((const uint32_t*)g_vraw + idx);
                    const uint32_t h = pack_f16(bf_lo(v) * inv, bf_hi(v) * inv);
                    const int st = key >> 4, hf = (key >> 3) & 1;
                    const uint32_t base = (dp < 4) ? (OFF_V + (127 - st) * 256) : (OFF_VONES + 256 + st * 256);
                    sts32(sb + base + hf * 128 + (key & 7) * 16 + (dp & 3) * 4, h);
                }
            }
            fence_async_smem();
            __syncwarp();
            if (lane == 0) {
                mbar_arrive(bar(B_KV + 0));
                if (!vdirect) for (int c = 0; c < 8; c++) mbar_arrive(bar(B_KV + c));
                prefetch_tm(&tm_wo); prefetch_tm(&tm_o);
                for (int jj = 0; jj < 2; jj++) {
                    mbar_expect_tx(bar(B_WO + jj), 32768);
                    tma4d(sb + OFF_X + jj * 32768, &tm_wo, 0, 0, hg * 2, 2 * jj, bar(B_WO + jj));
                }
            }
            __syncwarp();
        } else {
            if (wa == 1 && lane == 0) {
                mbar_expect_tx(bar(B_H), 4096);
                tma2d(sb + C_H + 2048, &tm_h, 0, c0 * 64, bar(B_H));
            }
            if (wa >= 2) {
                sts128(sb + C_H + (tau - 64) * 32, 0u, 0u, 0u, 0u);
                sts128(sb + C_H + (tau - 64) * 32 + 16, 0u, 0u, 0u, 0u);
                fence_async_smem();
            }
        }
        named_bar(5, 128);
        if (tau == 0) {
            poll_counter(&g_kvt_count[b >> 5], 32 * 4);
            fence_async_global();
            mbar_expect_tx(bar(B_CV), 16384);
            bulk_g2s(sb + C_KVC, g_kvT + (size_t)c0 * S_LEN, 16384, bar(B_CV));
        }
        __syncwarp();
        mbar_wait_w(bar(B_CV), 0);
        if (tau == 0) TSTAMP(9);
        const int NCH = 4;
#pragma unroll 1
        for (int ch = 0; ch < NCH; ch++) {
            {
                const uint32_t src = sb + C_KVC + ch * 4096 + tau * 32;
                const uint4 u0 = lds128(src), u1 = lds128(src + 16);
                const uint32_t prev = tau > 0 ? lds32(src - 4) : 0u;
                const uint32_t zd = sb + C_Z + (32 + tau * 16) * 4;
                sts128(zd,      __byte_perm(u0.x, prev, 0x7610), __byte_perm(u0.x, u0.x, 0x1032), __byte_perm(u0.y, u0.x, 0x7610), __byte_perm(u0.y, u0.y, 0x1032));
                sts128(zd + 16, __byte_perm(u0.z, u0.y, 0x7610), __byte_perm(u0.z, u0.z, 0x1032), __byte_perm(u0.w, u0.z, 0x7610), __byte_perm(u0.w, u0.w, 0x1032));
                sts128(zd + 32, __byte_perm(u1.x, u0.w, 0x7610), __byte_perm(u1.x, u1.x, 0x1032), __byte_perm(u1.y, u1.x, 0x7610), __byte_perm(u1.y, u1.y, 0x1032));
                sts128(zd + 48, __byte_perm(u1.z, u1.y, 0x7610), __byte_perm(u1.z, u1.z, 0x1032), __byte_perm(u1.w, u1.z, 0x7610), __byte_perm(u1.w, u1.w, 0x1032));
                if (tau < 32) sts32(sb + C_Z + tau * 4, 0u);
            }
            named_bar(5, 128);
            mbar_wait_w(bar(B_H), ch & 1);
            float D[32];
#pragma unroll
            for (int i = 0; i < 32; i++) D[i] = 0.f;
            fence_regs<32>(D);
            const uint32_t z0 = sb + C_Z + (32 + 32 * (wa >> 1) + 16 * (wa & 1) + 2 * g - 2 * t) * 4;
            const uint64_t hd = make_desc(sb + C_H + 2048, 16, 512, 2);
            conv_phase<64>(D, z0, hd);
            float E[16];
#pragma unroll
            for (int i = 0; i < 16; i++) asm volatile("mov.f32 %0, %1;" : "=f"(E[i]) : "f"(D[16 + i]));
            conv_phase<32>(E, z0 + 4096, hd);
            if (tau == 0 && ch < 3) {
                mbar_expect_tx(bar(B_H), 4096);
                tma2d(sb + C_H + 2048, &tm_h, 0, (c0 + ch + 1) * 64, bar(B_H));
            }
            const int bb0 = 16 * (wa & 1) + 2 * g;
            const int xsw = (g & 3) << 3;
            {
                const uint32_t xb = sb + C_Z + (wa >> 1) * 4096;
#pragma unroll
                for (int jn = 0; jn < 4; jn++) {
#pragma unroll
                    for (int r = 0; r < 2; r++) {
                        const float v0 = (wa < 2) ? E[4 * jn + 2 * r] : D[4 * jn + 2 * r];
                        const float v1 = (wa < 2) ? E[4 * jn + 2 * r + 1] : D[4 * jn + 2 * r + 1];
                        sts64f(xb + ((bb0 + r) * 32 + ((8 * jn + 2 * t) ^ xsw)) * 4, v0, v1);
                    }
                }
            }
            named_bar(5, 128);
            {
                const float dsc = __bfloat162float(prm.ssm_D[c0 + ch]);
                const uint32_t xb = sb + C_Z + ((wa >> 1) ^ 1) * 4096;
#pragma unroll
                for (int jn = 0; jn < 4; jn++) {
#pragma unroll
                    for (int e = 0; e < 2; e++) {
                        const int n = 8 * jn + 2 * t + e;
                        float y0, y1; int m, rn;
                        if (wa < 2) { y0 = D[4 * jn + e]; y1 = D[4 * jn + 2 + e]; m = n; rn = n - 1; }
                        else {
                            const bool last = (jn == 3 && e == 1) && (t == 3);
                            y0 = last ? D[13] : E[4 * jn + e]; y1 = last ? D[15] : E[4 * jn + 2 + e];
                            m = last ? 32 : 33 + n; rn = m - 32;
                        }
                        if (rn >= 0) {
                            y0 += ldsf(xb + (bb0 * 32 + (rn ^ xsw)) * 4);
                            y1 += ldsf(xb + ((bb0 + 1) * 32 + (rn ^ xsw)) * 4);
                        }
                        const uint32_t addr = sb + C_KVC + ch * 4096 + (32 * m + bb0) * 2;
                        const uint32_t kv = lds32(addr);
                        const uint32_t yb = pack_bf16(y0, y1);
                        const uint32_t kd = pack_bf16(bf_lo(kv) * dsc, bf_hi(kv) * dsc);
                        sts32(addr, badd2(yb, kd));
                    }
                }
                fence_async_smem();
            }
            named_bar(5, 128);
            if (tau == 0) {
                bulk_s2g(g_zT + (size_t)(c0 + ch) * S_LEN, sb + C_KVC + ch * 4096, 4096);
                bulk_commit();
                TSTAMP(10 + ch);
            }
        }
        {
            const int cg = tau & 15, pr = tau >> 4;
            const int p0 = pb * 64 + pr * 8, ch0 = hg * 128 + cg * 8;
            uint4 qr[8];
#pragma unroll
            for (int i = 0; i < 8; i++) qr[i] = __ldg((const uint4*)(prm.aq + (size_t)(p0 + i) * 512 + ch0));
            if (tau == 0) {
                bulk_wait_all();
                mbar_expect_tx(bar(B_WO + 3), 32768);
                tma4d(sb + OFF_C, &tm_wo, 0, 0, hg * 2, 6, bar(B_WO + 3));
                fence_async_global();
                red_release_add(&g_z_count[b >> 5], 1);
                poll_counter(&g_z_count[hg], 32);
                __threadfence();
                if (atomicAdd(&g_done, 1) == 2 * NCTA - 1) {
                    for (int i = 0; i < NCTA; i++) g_stats[i] = 0ull;
                    for (int i = 0; i < 4; i++) { g_kvt_count[i] = 0; g_z_count[i] = 0; }
                    for (int i = 0; i < 32; i++) g_o_count[i] = 0;
                    g_done = 0;
                    __threadfence();
                }
            }
            named_bar(5, 128);
            uint4 zz[8];
#pragma unroll
            for (int c = 0; c < 8; c++) zz[c] = __ldcg((const uint4*)(g_zT + (size_t)(ch0 + c) * S_LEN + p0));
#pragma unroll
            for (int i = 0; i < 8; i++) {
                uint32_t r[4];
#pragma unroll
                for (int k = 0; k < 4; k++) {
                    const uint32_t pr2 = __byte_perm((&zz[2 * k].x)[i >> 1], (&zz[2 * k + 1].x)[i >> 1], (i & 1) ? 0x7632 : 0x5410);
                    r[k] = bmul2((&qr[i].x)[k], pr2);
                }
                *(uint4*)(prm.out + (size_t)(p0 + i) * 1024 + ch0) = make_uint4(r[0], r[1], r[2], r[3]);
            }
        }
        if (tau == 0) TSTAMP(14);
    }
}

typedef CUresult (*EncodeFn)(CUtensorMap*, CUtensorMapDataType, cuuint32_t, void*, const cuuint64_t*, const cuuint64_t*,
                             const cuuint32_t*, const cuuint32_t*, CUtensorMapInterleave, CUtensorMapSwizzle,
                             CUtensorMapL2promotion, CUtensorMapFloatOOBfill);

void make_map(EncodeFn fn, CUtensorMap* tm, const void* ptr, int rank, const cuuint64_t* dims, const cuuint64_t* strides, const cuuint32_t* box, CUtensorMapSwizzle swz) {
    cuuint32_t es[4] = {1, 1, 1, 1};
    fn(tm, CU_TENSOR_MAP_DATA_TYPE_BFLOAT16, rank, const_cast<void*>(ptr), dims, strides, box, es, CU_TENSOR_MAP_INTERLEAVE_NONE, swz,
       CU_TENSOR_MAP_L2_PROMOTION_L2_128B, CU_TENSOR_MAP_FLOAT_OOB_FILL_NONE);
}

}

extern "C" void kernel_launch(void* const* d_in, const int* in_sizes, int n_in, void* d_out, int out_size) {
    (void)in_sizes; (void)n_in; (void)out_size;
    static EncodeFn encode = nullptr;
    static void* o_ptr = nullptr;
    if (!encode) {
        cudaDriverEntryPointQueryResult qres;
        void* fn = nullptr;
        cudaGetDriverEntryPoint("cuTensorMapEncodeTiled", &fn, cudaEnableDefault, &qres);
        encode = (EncodeFn)fn;
        cudaGetSymbolAddress(&o_ptr, g_o);
        cudaFuncSetAttribute(fused_kernel, cudaFuncAttributeMaxDynamicSharedMemorySize, SMEM_TOTAL);
    }
    CUtensorMap tm_x, tm_wq, tm_wo, tm_wk, tm_wv, tm_o, tm_h;
    {
        const cuuint64_t dims[3] = {64, 2048, 8}, str[2] = {1024, 128};
        const cuuint32_t b64[3] = {64, 64, 2};
        make_map(encode, &tm_x, d_in[6], 3, dims, str, b64, CU_TENSOR_MAP_SWIZZLE_128B);
        make_map(encode, &tm_o, o_ptr, 3, dims, str, b64, CU_TENSOR_MAP_SWIZZLE_128B);
    }
    {
        const cuuint64_t dims[4] = {64, 64, 8, 8}, str[3] = {1024, 128, 65536};
        const cuuint32_t box[4] = {64, 64, 2, 2};
        make_map(encode, &tm_wq, d_in[7], 4, dims, str, box, CU_TENSOR_MAP_SWIZZLE_128B);
        make_map(encode, &tm_wo, d_in[10], 4, dims, str, box, CU_TENSOR_MAP_SWIZZLE_128B);
    }
    {
        const cuuint64_t dims[3] = {16, 256, 2}, str[2] = {32, 8192};
        const cuuint32_t box[3] = {16, 256, 2};
        make_map(encode, &tm_wk, d_in[8], 3, dims, str, box, CU_TENSOR_MAP_SWIZZLE_32B);
        make_map(encode, &tm_wv, d_in[9], 3, dims, str, box, CU_TENSOR_MAP_SWIZZLE_32B);
    }
    {
        const cuuint64_t dims[2] = {32, 512 * 64}, str[1] = {64};
        const cuuint32_t box[2] = {32, 64};
        make_map(encode, &tm_h, d_in[4], 2, dims, str, box, CU_TENSOR_MAP_SWIZZLE_64B);
    }
    Params prm;
    prm.aq = (const __nv_bfloat16*)d_in[0];
    prm.ak = (const __nv_bfloat16*)d_in[1];
    prm.av = (const __nv_bfloat16*)d_in[2];
    prm.shift_k = (const __nv_bfloat16*)d_in[3];
    prm.ssm_D = (const __nv_bfloat16*)d_in[5];
    prm.out = (__nv_bfloat16*)d_out;
    fused_kernel<<<NCTA, NTHREADS, SMEM_TOTAL>>>(tm_x, tm_wq, tm_wo, tm_wk, tm_wv, tm_o, tm_h, prm);
}
```

```cpp
#include <cuda_runtime.h>
#include <cuda_bf16.h>
#include <cuda_fp16.h>
#include <cuda.h>
#include <stdint.h>

namespace {

constexpr int S_LEN = 2048;
constexpr int NCTA = 128;
constexpr int NTHREADS = 640;

constexpr uint32_t OFF_K = 0;
constexpr uint32_t OFF_V = 65536;
constexpr uint32_t OFF_VONES = OFF_V + 32768;
constexpr uint32_t OFF_X = 132096;
constexpr uint32_t OFF_C = 197632;
constexpr uint32_t C_KVC = OFF_C;
constexpr uint32_t C_H = OFF_C + 16384;
constexpr uint32_t C_Z = C_H + 6144;
constexpr uint32_t OFF_BAR = 231936;
constexpr uint32_t SMEM_TOTAL = 232448;

enum { B_WKV = 0, B_X = 1, B_QEMPTY = 5, B_QDONE = 7, B_KV = 8, B_WO = 16, B_O = 20, B_ATT = 24, B_H = 25, B_CV = 26, B_W = 27, B_KVT = 31, B_COUNT = 32 };
constexpr uint32_t OFF_MISC = OFF_BAR + 8 * B_COUNT;

__device__ __align__(1024) uint8_t g_kimg[65536];
__device__ __align__(1024) uint8_t g_vimg[65792];
__device__ __align__(1024) __nv_bfloat16 g_vraw[S_LEN * 16];
__device__ __align__(1024) __nv_bfloat16 g_o[S_LEN * 512];
__device__ __align__(1024) __nv_bfloat16 g_kvT[512 * S_LEN];
__device__ __align__(1024) __nv_bfloat16 g_zT[512 * S_LEN];
__device__ unsigned long long g_stats[NCTA];
__device__ unsigned int g_kvt_count[4];
__device__ unsigned int g_z_count[4];
__device__ unsigned int g_o_count[32];
__device__ unsigned int g_done;
#define TSTAMP(i) do {} while (0)
#define CSTAMP(i) do {} while (0)

__device__ __forceinline__ void wg_fence() { asm volatile("wgmma.fence.sync.aligned;" ::: "memory"); }
__device__ __forceinline__ void wg_commit() { asm volatile("wgmma.commit_group.sync.aligned;" ::: "memory"); }
template <int N> __device__ __forceinline__ void wg_wait() { asm volatile("wgmma.wait_group.sync.aligned %0;" ::"n"(N) : "memory"); }
template <int N> __device__ __forceinline__ void fence_regs(float* r) {
#pragma unroll
    for (int i = 0; i < N; i++) asm volatile("" : "+f"(r[i])::"memory");
}
template <int N> __device__ __forceinline__ void fence_uregs(uint32_t* r) {
#pragma unroll
    for (int i = 0; i < N; i++) asm volatile("" : "+r"(r[i])::"memory");
}
__device__ __forceinline__ uint64_t make_desc(uint32_t saddr, uint32_t lbo, uint32_t sbo, uint32_t swz) {
    return (uint64_t)((saddr & 0x3FFFF) >> 4) | ((uint64_t)(lbo >> 4) << 16) | ((uint64_t)(sbo >> 4) << 32) | ((uint64_t)swz << 62);
}
__device__ __forceinline__ void mbar_init(uint32_t bar, uint32_t count) {
    asm volatile("mbarrier.init.shared::cta.b64 [%0], %1;" ::"r"(bar), "r"(count) : "memory");
}
__device__ __forceinline__ void mbar_expect_tx(uint32_t bar, uint32_t bytes) {
    asm volatile("mbarrier.arrive.expect_tx.shared::cta.b64 _, [%0], %1;" ::"r"(bar), "r"(bytes) : "memory");
}
__device__ __forceinline__ void mbar_expect_tx_noarrive(uint32_t bar, uint32_t bytes) {
    asm volatile("mbarrier.expect_tx.relaxed.cta.shared::cta.b64 [%0], %1;" ::"r"(bar), "r"(bytes) : "memory");
}
__device__ __forceinline__ void mbar_arrive(uint32_t bar) {
    asm volatile("mbarrier.arrive.shared::cta.b64 _, [%0];" ::"r"(bar) : "memory");
}
__device__ __forceinline__ bool mbar_try(uint32_t bar, uint32_t parity) {
    uint32_t ok;
    asm volatile("{\n.reg .pred p;\nmbarrier.try_wait.parity.shared::cta.b64 p, [%1], %2;\nselp.u32 %0, 1, 0, p;\n}\n"
                 : "=r"(ok) : "r"(bar), "r"(parity) : "memory");
    return ok != 0;
}
__device__ __forceinline__ void mbar_wait(uint32_t bar, uint32_t parity) {
    uint32_t spins = 0;
    while (!mbar_try(bar, parity)) {
        if (++spins > (1u << 24)) __trap();
    }
}
__device__ __forceinline__ void mbar_wait_w(uint32_t bar, uint32_t parity) {
    uint32_t spins = 0;
    while (!__all_sync(0xffffffffu, mbar_try(bar, parity))) {
        if (++spins > (1u << 24)) __trap();
    }
}
__device__ __forceinline__ void tma2d(uint32_t dst, const CUtensorMap* tm, int c0, int c1, uint32_t bar) {
    asm volatile("cp.async.bulk.tensor.2d.shared::cluster.global.mbarrier::complete_tx::bytes [%0], [%1, {%3, %4}], [%2];"
                 ::"r"(dst), "l"((uint64_t)tm), "r"(bar), "r"(c0), "r"(c1) : "memory");
}
__device__ __forceinline__ void tma3d(uint32_t dst, const CUtensorMap* tm, int c0, int c1, int c2, uint32_t bar) {
    asm volatile("cp.async.bulk.tensor.3d.shared::cluster.global.mbarrier::complete_tx::bytes [%0], [%1, {%3, %4, %5}], [%2];"
                 ::"r"(dst), "l"((uint64_t)tm), "r"(bar), "r"(c0), "r"(c1), "r"(c2) : "memory");
}
__device__ __forceinline__ void tma4d(uint32_t dst, const CUtensorMap* tm, int c0, int c1, int c2, int c3, uint32_t bar) {
    asm volatile("cp.async.bulk.tensor.4d.shared::cluster.global.mbarrier::complete_tx::bytes [%0], [%1, {%3, %4, %5, %6}], [%2];"
                 ::"r"(dst), "l"((uint64_t)tm), "r"(bar), "r"(c0), "r"(c1), "r"(c2), "r"(c3) : "memory");
}
__device__ __forceinline__ void prefetch_tm(const CUtensorMap* tm) { asm volatile("prefetch.tensormap [%0];" ::"l"((uint64_t)tm) : "memory"); }
__device__ __forceinline__ void bulk_s2g(void* dst, uint32_t src, uint32_t bytes) {
    asm volatile("cp.async.bulk.global.shared::cta.bulk_group [%0], [%1], %2;" ::"l"(dst), "r"(src), "r"(bytes) : "memory");
}
__device__ __forceinline__ void bulk_commit() { asm volatile("cp.async.bulk.commit_group;" ::: "memory"); }
__device__ __forceinline__ void bulk_wait_all() { asm volatile("cp.async.bulk.wait_group 0;" ::: "memory"); }
__device__ __forceinline__ void fence_async_global() { asm volatile("fence.proxy.async.global;" ::: "memory"); }
__device__ __forceinline__ void bulk_g2s(uint32_t dst, const void* src, uint32_t bytes, uint32_t bar) {
    asm volatile("cp.async.bulk.shared::cluster.global.mbarrier::complete_tx::bytes [%0], [%1], %2, [%3];"
                 ::"r"(dst), "l"(src), "r"(bytes), "r"(bar) : "memory");
}
__device__ __forceinline__ void fence_async_smem() { asm volatile("fence.proxy.async.shared::cta;" ::: "memory"); }
__device__ __forceinline__ void named_bar(int id, int n) { asm volatile("bar.sync %0, %1;" ::"r"(id), "r"(n) : "memory"); }
__device__ __forceinline__ bool named_bar_and(int id, int n, bool pred) {
    uint32_t r;
    asm volatile("{\n.reg .pred p, q;\nsetp.ne.u32 p, %3, 0;\nbarrier.cta.red.and.pred q, %1, %2, p;\nselp.u32 %0, 1, 0, q;\n}\n"
                 : "=r"(r) : "r"(id), "r"(n), "r"((uint32_t)pred) : "memory");
    return r != 0;
}
__device__ __forceinline__ unsigned int ld_acquire(const unsigned int* p) {
    unsigned int v;
    asm volatile("ld.acquire.gpu.global.u32 %0, [%1];" : "=r"(v) : "l"(p) : "memory");
    return v;
}
__device__ __forceinline__ void red_release_add(unsigned int* p, unsigned int v) {
    asm volatile("red.release.gpu.global.add.u32 [%0], %1;" ::"l"(p), "r"(v) : "memory");
}
__device__ __forceinline__ void poll_counter(const unsigned int* p, unsigned int target) {
    uint32_t spins = 0;
    while (ld_acquire(p) < target) {
        if (++spins > (1u << 22)) __trap();
    }
}
__device__ __forceinline__ float ex2f(float x) { float y; asm("ex2.approx.ftz.f32 %0, %1;" : "=f"(y) : "f"(x)); return y; }
__device__ __forceinline__ uint32_t pack_f16(float lo, float hi) { uint32_t r; asm("cvt.rn.f16x2.f32 %0, %1, %2;" : "=r"(r) : "f"(hi), "f"(lo)); return r; }
__device__ __forceinline__ uint32_t pack_bf16(float lo, float hi) { uint32_t r; asm("cvt.rn.bf16x2.f32 %0, %1, %2;" : "=r"(r) : "f"(hi), "f"(lo)); return r; }
__device__ __forceinline__ float bf_lo(uint32_t v) { return __uint_as_float(v << 16); }
__device__ __forceinline__ float bf_hi(uint32_t v) { return __uint_as_float(v & 0xFFFF0000u); }
__device__ __forceinline__ uint32_t hfma2(uint32_t a, uint32_t b, uint32_t c) { uint32_t r; asm("fma.rn.f16x2 %0, %1, %2, %3;" : "=r"(r) : "r"(a), "r"(b), "r"(c)); return r; }
__device__ __forceinline__ uint32_t bmul2(uint32_t a, uint32_t b) { uint32_t r; asm("mul.rn.bf16x2 %0, %1, %2;" : "=r"(r) : "r"(a), "r"(b)); return r; }
__device__ __forceinline__ uint32_t badd2(uint32_t a, uint32_t b) { uint32_t r; asm("add.rn.bf16x2 %0, %1, %2;" : "=r"(r) : "r"(a), "r"(b)); return r; }
template <int LUT> __device__ __forceinline__ uint32_t lop3(uint32_t a, uint32_t b, uint32_t c) {
    uint32_t r; asm("lop3.b32 %0, %1, %2, %3, %4;" : "=r"(r) : "r"(a), "r"(b), "r"(c), "n"(LUT)); return r;
}
__device__ __forceinline__ uint32_t lds32(uint32_t a) { uint32_t v; asm volatile("ld.shared.u32 %0, [%1];" : "=r"(v) : "r"(a)); return v; }
__device__ __forceinline__ float ldsf(uint32_t a) { float v; asm volatile("ld.shared.f32 %0, [%1];" : "=f"(v) : "r"(a)); return v; }
__device__ __forceinline__ uint4 lds128(uint32_t a) { uint4 v; asm volatile("ld.shared.v4.u32 {%0,%1,%2,%3}, [%4];" : "=r"(v.x), "=r"(v.y), "=r"(v.z), "=r"(v.w) : "r"(a)); return v; }
__device__ __forceinline__ void lds64(uint32_t a, uint32_t& x, uint32_t& y) { asm volatile("ld.shared.v2.u32 {%0,%1}, [%2];" : "=r"(x), "=r"(y) : "r"(a)); }
__device__ __forceinline__ void sts32(uint32_t a, uint32_t v) { asm volatile("st.shared.u32 [%0], %1;" ::"r"(a), "r"(v) : "memory"); }
__device__ __forceinline__ void sts64f(uint32_t a, float x, float y) { asm volatile("st.shared.v2.f32 [%0], {%1,%2};" ::"r"(a), "f"(x), "f"(y) : "memory"); }
__device__ __forceinline__ void sts128(uint32_t a, uint32_t x, uint32_t y, uint32_t z, uint32_t w) {
    asm volatile("st.shared.v4.u32 [%0], {%1,%2,%3,%4};" ::"r"(a), "r"(x), "r"(y), "r"(z), "r"(w) : "memory");
}

__device__ __forceinline__ void wg_ss_n32_tb(float* d, uint64_t descA, uint64_t descB) {
    asm volatile("wgmma.mma_async.sync.aligned.m64n32k16.f32.bf16.bf16 {%0,%1,%2,%3,%4,%5,%6,%7,%8,%9,%10,%11,%12,%13,%14,%15}, %16, %17, 1, 1, 1, 0, 1;\n"
        : "+f"(d[0]), "+f"(d[1]), "+f"(d[2]), "+f"(d[3]), "+f"(d[4]), "+f"(d[5]), "+f"(d[6]), "+f"(d[7]), "+f"(d[8]), "+f"(d[9]), "+f"(d[10]), "+f"(d[11]), "+f"(d[12]), "+f"(d[13]), "+f"(d[14]), "+f"(d[15])
        : "l"(descA), "l"(descB));
}
__device__ __forceinline__ void wg_qk_n64(float* d, const uint32_t* a, uint64_t desc) {
    asm volatile("wgmma.mma_async.sync.aligned.m64n64k16.f32.bf16.bf16 {%0,%1,%2,%3,%4,%5,%6,%7,%8,%9,%10,%11,%12,%13,%14,%15,%16,%17,%18,%19,%20,%21,%22,%23,%24,%25,%26,%27,%28,%29,%30,%31}, {%32,%33,%34,%35}, %36, 0, 1, 1, 0;\n"
        : "+f"(d[0]), "+f"(d[1]), "+f"(d[2]), "+f"(d[3]), "+f"(d[4]), "+f"(d[5]), "+f"(d[6]), "+f"(d[7]), "+f"(d[8]), "+f"(d[9]), "+f"(d[10]), "+f"(d[11]), "+f"(d[12]), "+f"(d[13]), "+f"(d[14]), "+f"(d[15]), "+f"(d[16]), "+f"(d[17]), "+f"(d[18]), "+f"(d[19]), "+f"(d[20]), "+f"(d[21]), "+f"(d[22]), "+f"(d[23]), "+f"(d[24]), "+f"(d[25]), "+f"(d[26]), "+f"(d[27]), "+f"(d[28]), "+f"(d[29]), "+f"(d[30]), "+f"(d[31])
        : "r"(a[0]), "r"(a[1]), "r"(a[2]), "r"(a[3]), "l"(desc));
}
__device__ __forceinline__ void wg_pv_n24(float* d, const uint32_t* a, uint64_t desc) {
    asm volatile("wgmma.mma_async.sync.aligned.m64n24k16.f32.f16.f16 {%0,%1,%2,%3,%4,%5,%6,%7,%8,%9,%10,%11}, {%12,%13,%14,%15}, %16, 1, 1, 1, 1;\n"
        : "+f"(d[0]), "+f"(d[1]), "+f"(d[2]), "+f"(d[3]), "+f"(d[4]), "+f"(d[5]), "+f"(d[6]), "+f"(d[7]), "+f"(d[8]), "+f"(d[9]), "+f"(d[10]), "+f"(d[11])
        : "r"(a[0]), "r"(a[1]), "r"(a[2]), "r"(a[3]), "l"(desc));
}
__device__ __forceinline__ void wg_cv_n32(float* d, const uint32_t* a, uint64_t desc) {
    asm volatile("wgmma.mma_async.sync.aligned.m64n32k16.f32.bf16.bf16 {%0,%1,%2,%3,%4,%5,%6,%7,%8,%9,%10,%11,%12,%13,%14,%15}, {%16,%17,%18,%19}, %20, 1, 1, 1, 0;\n"
        : "+f"(d[0]), "+f"(d[1]), "+f"(d[2]), "+f"(d[3]), "+f"(d[4]), "+f"(d[5]), "+f"(d[6]), "+f"(d[7]), "+f"(d[8]), "+f"(d[9]), "+f"(d[10]), "+f"(d[11]), "+f"(d[12]), "+f"(d[13]), "+f"(d[14]), "+f"(d[15])
        : "r"(a[0]), "r"(a[1]), "r"(a[2]), "r"(a[3]), "l"(desc));
}
__device__ __forceinline__ void wg_cv_n64(float* d, const uint32_t* a, uint64_t desc) {
    asm volatile("wgmma.mma_async.sync.aligned.m64n64k16.f32.bf16.bf16 {%0,%1,%2,%3,%4,%5,%6,%7,%8,%9,%10,%11,%12,%13,%14,%15,%16,%17,%18,%19,%20,%21,%22,%23,%24,%25,%26,%27,%28,%29,%30,%31}, {%32,%33,%34,%35}, %36, 1, 1, 1, 0;\n"
        : "+f"(d[0]), "+f"(d[1]), "+f"(d[2]), "+f"(d[3]), "+f"(d[4]), "+f"(d[5]), "+f"(d[6]), "+f"(d[7]), "+f"(d[8]), "+f"(d[9]), "+f"(d[10]), "+f"(d[11]), "+f"(d[12]), "+f"(d[13]), "+f"(d[14]), "+f"(d[15]), "+f"(d[16]), "+f"(d[17]), "+f"(d[18]), "+f"(d[19]), "+f"(d[20]), "+f"(d[21]), "+f"(d[22]), "+f"(d[23]), "+f"(d[24]), "+f"(d[25]), "+f"(d[26]), "+f"(d[27]), "+f"(d[28]), "+f"(d[29]), "+f"(d[30]), "+f"(d[31])
        : "r"(a[0]), "r"(a[1]), "r"(a[2]), "r"(a[3]), "l"(desc));
}

template <int N> __device__ __forceinline__ void wg_cv(float* d, const uint32_t* a, uint64_t desc);
template <> __device__ __forceinline__ void wg_cv<32>(float* d, const uint32_t* a, uint64_t s) { wg_cv_n32(d, a, s); }
template <> __device__ __forceinline__ void wg_cv<64>(float* d, const uint32_t* a, uint64_t s) { wg_cv_n64(d, a, s); }

constexpr uint32_t POLYMASK = 0xB5B5u;
__device__ __forceinline__ void softmax_fast(const float* s, uint32_t* p, uint32_t mlo) {
    const uint32_t C3 = 0x2cfb2cfbu, C2 = 0x9fec9fecu, C1 = 0x37a837a8u, C0 = 0x37383738u;
#pragma unroll
    for (int i = 0; i < 16; i++) {
        const float s0 = s[2 * i], s1 = s[2 * i + 1];
        if ((POLYMASK >> i) & 1) {
            const float t0 = s0 + 12303.0f, t1 = s1 + 12303.0f;
            const uint32_t T = __byte_perm(__float_as_uint(t0), __float_as_uint(t1), 0x5410);
            const uint32_t U = lop3<0xEA>(T, mlo, 0x3C003C00u);
            uint32_t h = hfma2(U, C3, C2);
            h = hfma2(h, U, C1);
            h = hfma2(h, U, C0);
            p[i] = lop3<0xE4>(h, T, 0x03FF03FFu);
        } else {
            p[i] = pack_f16(ex2f(s0), ex2f(s1));
        }
    }
}

__device__ __forceinline__ void gemm_chunk(float* acc, uint32_t a_addr, uint32_t b_addr) {
    const uint64_t da = make_desc(a_addr, 16, 1024, 1);
    const uint64_t db = make_desc(b_addr, 8192, 1024, 1);
#pragma unroll
    for (int ks = 0; ks < 4; ks++) wg_ss_n32_tb(acc, da + ks * 2, db + ks * 128);
}

__device__ __forceinline__ void wo_half(uint32_t sb, const CUtensorMap* tm_wo, int hg) {
    uint32_t old;
    asm volatile("atom.shared.add.u32 %0, [%1], 1;" : "=r"(old) : "r"(sb + OFF_MISC + 8) : "memory");
    if (old == 3) {
        mbar_expect_tx(sb + OFF_BAR + 8 * (B_WO + 2), 32768);
        tma4d(sb + OFF_K, tm_wo, 0, 0, hg * 2, 4, sb + OFF_BAR + 8 * (B_WO + 2));
    }
}

struct Params {
    const __nv_bfloat16 *aq, *ak, *av, *shift_k, *ssm_D;
    __nv_bfloat16* out;
};

template <int NQ>
__device__ __forceinline__ void conv_phase(float* Dn, uint32_t zaddr, uint64_t hdesc) {
    uint32_t a[2][16];
#pragma unroll
    for (int st = 0; st < 8; st++) {
        uint32_t* aa = a[st & 1];
        if (st >= 2) wg_wait<1>();
#pragma unroll
        for (int u = 0; u < 2; u++) {
            const uint32_t z = zaddr + (st * 2 + u) * 256;
            lds64(z, aa[8 * u + 0], aa[8 * u + 1]);      lds64(z - 32, aa[8 * u + 2], aa[8 * u + 3]);
            lds64(z - 64, aa[8 * u + 4], aa[8 * u + 5]); lds64(z - 96, aa[8 * u + 6], aa[8 * u + 7]);
        }
        wg_fence();
#pragma unroll
        for (int u = 0; u < 2; u++) {
            const int qi = st * 2 + u;
            wg_cv<NQ>(Dn, &aa[8 * u], hdesc - qi * 8);
            wg_cv<NQ>(Dn, &aa[8 * u + 4], hdesc - qi * 8 + 2);
        }
        wg_commit();
    }
    wg_wait<0>();
    fence_regs<NQ / 2>(Dn);
}

__global__ void __launch_bounds__(NTHREADS, 1)
fused_kernel(const __grid_constant__ CUtensorMap tm_x,
             const __grid_constant__ CUtensorMap tm_wq, const __grid_constant__ CUtensorMap tm_wo,
             const __grid_constant__ CUtensorMap tm_wk, const __grid_constant__ CUtensorMap tm_wv,
             const __grid_constant__ CUtensorMap tm_o, const __grid_constant__ CUtensorMap tm_h, const Params prm) {
    extern __shared__ __align__(1024) uint8_t smem_raw[];
    const uint32_t sb = (uint32_t)__cvta_generic_to_shared(smem_raw);
    const int warp_id = __shfl_sync(0xffffffffu, threadIdx.x >> 5, 0);
    const int lane = threadIdx.x & 31;
    const int g = lane >> 2, t = lane & 3;
    const int b = blockIdx.x, pb = b >> 2, hg = b & 3;
    auto bar = [&](int i) { return sb + OFF_BAR + 8 * i; };

    if (threadIdx.x == 512) {
        TSTAMP(0);
        prefetch_tm(&tm_x); prefetch_tm(&tm_wq); prefetch_tm(&tm_wk); prefetch_tm(&tm_wv);
        mbar_init(bar(B_WKV), 1);
        for (int j = 0; j < 4; j++) { mbar_init(bar(B_X + j), 1); mbar_init(bar(B_W + j), 1); mbar_init(bar(B_WO + j), 1); mbar_init(bar(B_O + j), 1); }
        sts32(sb + OFF_MISC + 8, 0u);
        for (int j = 0; j < 8; j++) mbar_init(bar(B_KV + j), j == 0 ? 2 : 1);
        mbar_init(bar(B_QEMPTY), 4); mbar_init(bar(B_QEMPTY + 1), 4);
        mbar_init(bar(B_QDONE), 4); mbar_init(bar(B_ATT), 4);
        mbar_init(bar(B_H), 1); mbar_init(bar(B_CV), 1); mbar_init(bar(B_KVT), 512);
        asm volatile("fence.mbarrier_init.release.cluster;" ::: "memory");
    }

    if (warp_id < 16) {
        const int w = warp_id >> 2, wq = warp_id & 3;
        __syncthreads();
        float acc[16];
#pragma unroll
        for (int i = 0; i < 16; i++) acc[i] = 0.f;
        fence_regs<16>(acc);
        const uint32_t bcol = (w >> 1) * 8192 + (w & 1) * 64;
        const int kpr = lane & 7, kcg = wq * 4 + (lane >> 3);
        const int kp0 = pb * 64 + w * 16 + 2 * kpr, kch0 = hg * 128 + kcg * 8;
        uint4 kr[5], vr[2], sw[4];
#pragma unroll
        for (int jj = 0; jj < 4; jj++) {
            mbar_wait_w(bar(B_X + jj), 0);
            mbar_wait_w(bar(B_W + jj), 0);
            if (threadIdx.x == 0) TSTAMP(jj == 0 ? 23 : jj == 1 ? 24 : jj == 2 ? 26 : 27);
            wg_fence();
            gemm_chunk(acc, sb + OFF_X + jj * 16384, sb + OFF_V + (jj & 1) * 32768 + bcol);
            gemm_chunk(acc, sb + OFF_X + jj * 16384 + 8192, sb + OFF_V + (jj & 1) * 32768 + 16384 + bcol);
            wg_commit();
            if (jj == 2) {
#pragma unroll
                for (int i = 0; i < 5; i++) {
                    const int sx = kp0 - 3 + i;
                    kr[i] = sx >= 0 ? __ldg((const uint4*)(prm.ak + (size_t)sx * 512 + kch0)) : make_uint4(0u, 0u, 0u, 0u);
                }
#pragma unroll
                for (int i = 0; i < 2; i++) vr[i] = __ldg((const uint4*)(prm.av + (size_t)(kp0 + i) * 512 + kch0));
#pragma unroll
                for (int i = 0; i < 4; i++) sw[i] = __ldg((const uint4*)(prm.shift_k + kch0 * 4) + i);
            }
            wg_wait<0>();
            if (jj < 2 && (threadIdx.x & 127) == 0) mbar_arrive(bar(B_QEMPTY + jj));
        }
        fence_regs<16>(acc);
        if ((threadIdx.x & 127) == 0) { mbar_arrive(bar(B_QDONE)); if (w == 0) TSTAMP(1); }
        {
            uint32_t x0[4], x1[4];
#pragma unroll
            for (int i = 0; i < 4; i++) {
                const uint32_t w0 = __byte_perm(sw[i].x, sw[i].z, 0x5410), w1 = __byte_perm(sw[i].x, sw[i].z, 0x7632);
                const uint32_t w2 = __byte_perm(sw[i].y, sw[i].w, 0x5410), w3 = __byte_perm(sw[i].y, sw[i].w, 0x7632);
                const uint32_t k0 = (&kr[0].x)[i], k1 = (&kr[1].x)[i], k2 = (&kr[2].x)[i], k3 = (&kr[3].x)[i], k4 = (&kr[4].x)[i];
                x0[i] = bmul2(badd2(badd2(badd2(bmul2(k0, w3), bmul2(k1, w2)), bmul2(k2, w1)), bmul2(k3, w0)), (&vr[0].x)[i]);
                x1[i] = bmul2(badd2(badd2(badd2(bmul2(k1, w3), bmul2(k2, w2)), bmul2(k3, w1)), bmul2(k4, w0)), (&vr[1].x)[i]);
            }
            uint32_t* dst = (uint32_t*)(g_kvT + (size_t)kch0 * S_LEN + kp0);
#pragma unroll
            for (int i = 0; i < 4; i++) {
                dst[(2 * i) * (S_LEN / 2)] = __byte_perm(x0[i], x1[i], 0x5410);
                dst[(2 * i + 1) * (S_LEN / 2)] = __byte_perm(x0[i], x1[i], 0x7632);
            }
            mbar_arrive(bar(B_KVT));
        }
        uint32_t qa[2][4];
        float qn[2];
        {
            const float c = 0.25f * 1.4426950408889634f;
#pragma unroll
            for (int hh = 0; hh < 2; hh++) {
                float n0 = 0.f, n1 = 0.f;
#pragma unroll
                for (int i = 0; i < 4; i++) {
                    const uint32_t qb = pack_bf16(acc[8 * hh + 2 * i], acc[8 * hh + 2 * i + 1]);
                    const uint32_t qs = pack_bf16(bf_lo(qb) * c, bf_hi(qb) * c);
                    qa[hh][i] = qs;
                    const float e = bf_lo(qs) * bf_lo(qs) + bf_hi(qs) * bf_hi(qs);
                    if (i & 1) n1 += e; else n0 += e;
                }
                n0 += __shfl_xor_sync(0xffffffffu, n0, 1); n0 += __shfl_xor_sync(0xffffffffu, n0, 2);
                n1 += __shfl_xor_sync(0xffffffffu, n1, 1); n1 += __shfl_xor_sync(0xffffffffu, n1, 2);
                qn[hh] = fmaxf(n0, n1);
            }
        }
        uint32_t mlo = 0x03FF03FFu; asm volatile("" : "+r"(mlo));
        const uint64_t kdesc0 = make_desc(sb + OFF_K, 128, 256, 0);
        const uint64_t vdesc0 = make_desc(sb + OFF_VONES - 256, 128, 256, 0);
        constexpr uint64_t VSTEP = ((uint64_t)16 << 32) - 16;
        mbar_wait_w(bar(B_KV + 0), 0);
        if ((threadIdx.x & 127) == 0 && w == 0) TSTAMP(2);
        const float kmax2 = ldsf(sb + OFF_MISC);
        const bool fast0 = __all_sync(0xffffffffu, named_bar_and(1 + w, 128, qn[0] * kmax2 <= 193.0f));
        const bool fast1 = __all_sync(0xffffffffu, named_bar_and(1 + w, 128, qn[1] * kmax2 <= 193.0f));
        uint32_t a[4] = {qa[0][0], qa[0][1], qa[0][2], qa[0][3]};
#pragma unroll 1
        for (int hh = 0; hh < 2; hh++) {
            const bool fast = hh ? fast1 : fast0;
            float S[32], O[12];
#pragma unroll
            for (int i = 0; i < 12; i++) O[i] = 0.f;
#pragma unroll
            for (int i = 0; i < 32; i++) S[i] = 0.f;
            fence_regs<12>(O); fence_regs<32>(S);
            wg_fence();
            wg_qk_n64(S, a, kdesc0);
            wg_commit();
            wg_wait<0>();
            uint64_t kd = kdesc0 + 128, vd = vdesc0;
            if (fast) {
                uint32_t P[16];
#pragma unroll 1
                for (int c = 0; c < 8; c++) {
                    if (c < 7) mbar_wait_w(bar(B_KV + c + 1), 0);
#pragma unroll 1
                    for (int j = 0; j < 4; j++) {
                        fence_regs<32>(S);
                        softmax_fast(S, P, mlo);
                        fence_regs<32>(S);
                        wg_fence();
                        wg_qk_n64(S, a, kd);
#pragma unroll
                        for (int i = 0; i < 4; i++) wg_pv_n24(O, &P[4 * i], vd + i * VSTEP);
                        wg_commit();
                        wg_wait<0>();
                        kd += 128; vd += 4 * VSTEP;
                    }
                    if (hh == 1 && c == 3 && (threadIdx.x & 127) == 0) wo_half(sb, &tm_wo, hg);
                }
            } else {
                uint32_t P[16];
                float m0 = -INFINITY, m1 = -INFINITY;
#pragma unroll 1
                for (int c = 0; c < 8; c++) {
                    if (c < 7) mbar_wait_w(bar(B_KV + c + 1), 0);
#pragma unroll 1
                    for (int j = 0; j < 4; j++) {
                        fence_regs<32>(S); fence_regs<12>(O);
                        float x0 = m0, x1 = m1;
#pragma unroll
                        for (int i = 0; i < 8; i++) {
                            x0 = fmaxf(x0, fmaxf(S[4 * i], S[4 * i + 1]));
                            x1 = fmaxf(x1, fmaxf(S[4 * i + 2], S[4 * i + 3]));
                        }
                        x0 = fmaxf(x0, __shfl_xor_sync(0xffffffffu, x0, 1)); x0 = fmaxf(x0, __shfl_xor_sync(0xffffffffu, x0, 2));
                        x1 = fmaxf(x1, __shfl_xor_sync(0xffffffffu, x1, 1)); x1 = fmaxf(x1, __shfl_xor_sync(0xffffffffu, x1, 2));
                        const float r0 = ex2f(m0 - x0), r1 = ex2f(m1 - x1);
                        m0 = x0; m1 = x1;
#pragma unroll
                        for (int i = 0; i < 3; i++) { O[4 * i] *= r0; O[4 * i + 1] *= r0; O[4 * i + 2] *= r1; O[4 * i + 3] *= r1; }
#pragma unroll
                        for (int i = 0; i < 8; i++) {
                            P[2 * i] = pack_f16(ex2f(S[4 * i] - m0), ex2f(S[4 * i + 1] - m0));
                            P[2 * i + 1] = pack_f16(ex2f(S[4 * i + 2] - m1), ex2f(S[4 * i + 3] - m1));
                        }
                        fence_regs<32>(S); fence_regs<12>(O);
                        wg_fence();
                        wg_qk_n64(S, a, kd);
#pragma unroll
                        for (int i = 0; i < 4; i++) wg_pv_n24(O, &P[4 * i], vd + i * VSTEP);
                        wg_commit();
                        wg_wait<0>();
                        kd += 128; vd += 4 * VSTEP;
                    }
                    if (hh == 1 && c == 3 && (threadIdx.x & 127) == 0) wo_half(sb, &tm_wo, hg);
                }
            }
            fence_regs<12>(O);
            const float vscale = ldsf(sb + OFF_MISC + 4);
            const float i0 = __fdividef(vscale, O[4]), i1 = __fdividef(vscale, O[6]);
            const int row = pb * 64 + wq * 16 + g;
            uint32_t* o0 = (uint32_t*)(g_o + (size_t)row * 512 + (hg * 8 + 2 * w + hh) * 16) + t;
            uint32_t* o1 = o0 + 8 * 256;
            o0[0] = pack_bf16(O[0] * i0, O[1] * i0);
            o0[4] = pack_bf16(O[8] * i0, O[9] * i0);
            o1[0] = pack_bf16(O[2] * i1, O[3] * i1);
            o1[4] = pack_bf16(O[10] * i1, O[11] * i1);
            if ((threadIdx.x & 127) == 0 && w == 0) { TSTAMP(3 + hh); CSTAMP(40 + hh); }
#pragma unroll
            for (int i = 0; i < 4; i++) a[i] = qa[1][i];
        }
        named_bar(1 + w, 128);
        if ((threadIdx.x & 127) == 0) {
            red_release_add(&g_o_count[pb], 1);
            mbar_arrive(bar(B_ATT));
        }
        if (threadIdx.x == 0) {
            TSTAMP(30);
            mbar_wait(bar(B_ATT), 0);
            TSTAMP(31);
            poll_counter(&g_o_count[pb], 16);
            TSTAMP(18);
            fence_async_global();
            for (int jj = 0; jj < 4; jj++) {
                mbar_expect_tx(bar(B_O + jj), 16384);
                tma3d(sb + OFF_V + jj * 16384, &tm_o, 0, pb * 64, 2 * jj, bar(B_O + jj));
            }
            __threadfence();
            if (atomicAdd(&g_done, 1) == 2 * NCTA - 1) {
                for (int i = 0; i < NCTA; i++) g_stats[i] = 0ull;
                for (int i = 0; i < 4; i++) { g_kvt_count[i] = 0; g_z_count[i] = 0; }
                for (int i = 0; i < 32; i++) g_o_count[i] = 0;
                g_done = 0;
                __threadfence();
            }
        }
        __syncwarp();
#pragma unroll
        for (int i = 0; i < 16; i++) acc[i] = 0.f;
        fence_regs<16>(acc);
#pragma unroll 1
        for (int jj = 0; jj < 4; jj++) {
            mbar_wait_w(bar(B_WO + jj), 0);
            mbar_wait_w(bar(B_O + jj), 0);
            if (threadIdx.x == 0 && (jj == 0 || jj == 3)) TSTAMP(jj == 0 ? 32 : 33);
            const uint32_t wb = sb + (jj < 2 ? OFF_X + jj * 32768 : (jj == 2 ? OFF_K : OFF_C)) + bcol;
            wg_fence();
            gemm_chunk(acc, sb + OFF_V + jj * 16384, wb);
            gemm_chunk(acc, sb + OFF_V + jj * 16384 + 8192, wb + 16384);
            wg_commit();
        }
        wg_wait<0>();
        fence_regs<16>(acc);
        {
            const int row = pb * 64 + wq * 16 + g;
            uint32_t* d0 = (uint32_t*)(prm.out + (size_t)row * 1024 + 512 + hg * 128 + w * 32) + t;
            uint32_t* d1 = d0 + 8 * 512;
#pragma unroll
            for (int i = 0; i < 4; i++) {
                d0[4 * i] = pack_bf16(acc[4 * i], acc[4 * i + 1]);
                d1[4 * i] = pack_bf16(acc[4 * i + 2], acc[4 * i + 3]);
            }
        }
        if ((threadIdx.x & 127) == 0 && w == 0) TSTAMP(5);
    } else {
        const int wa = warp_id - 16, tau = threadIdx.x - 512;
        __syncthreads();
        const bool kv_cta = (hg == (pb & 3));
        if (tau == 0) {
            if (kv_cta) {
                mbar_expect_tx(bar(B_WKV), 32768);
                tma3d(sb + OFF_C, &tm_wk, 0, 0, 0, bar(B_WKV));
                tma3d(sb + OFF_C + 16384, &tm_wv, 0, 0, 0, bar(B_WKV));
            }
            for (int jj = 0; jj < 4; jj++) {
                mbar_expect_tx(bar(B_X + jj), 16384);
                tma3d(sb + OFF_X + jj * 16384, &tm_x, 0, pb * 64, 2 * jj, bar(B_X + jj));
                if (!kv_cta && jj < 2) {
                    mbar_expect_tx(bar(B_W + jj), 32768);
                    tma4d(sb + OFF_V + jj * 32768, &tm_wq, 0, 0, hg * 2, 2 * jj, bar(B_W + jj));
                }
            }
            TSTAMP(25);
        }
        __syncwarp();
        if (kv_cta) {
            float acc[16];
#pragma unroll
            for (int i = 0; i < 16; i++) acc[i] = 0.f;
            fence_regs<16>(acc);
            mbar_wait_w(bar(B_WKV), 0);
            if (tau == 0) TSTAMP(20);
#pragma unroll
            for (int jj = 0; jj < 4; jj++) {
                mbar_wait_w(bar(B_X + jj), 0);
                wg_fence();
#pragma unroll
                for (int j = 2 * jj; j < 2 * jj + 2; j++) {
                    const uint64_t da = make_desc(sb + OFF_X + j * 8192, 16, 1024, 1);
                    const uint64_t db = make_desc(sb + OFF_C + j * 2048, 16384, 256, 3);
#pragma unroll
                    for (int ks = 0; ks < 4; ks++) wg_ss_n32_tb(acc, da + ks * 2, db + ks * 32);
                }
                wg_commit();
            }
            wg_wait<0>();
            fence_regs<16>(acc);
            if (tau == 0) TSTAMP(22);
            {
                uint32_t kk[4], vv[4];
#pragma unroll
                for (int i = 0; i < 4; i++) { kk[i] = pack_bf16(acc[2 * i], acc[2 * i + 1]); vv[i] = pack_bf16(acc[8 + 2 * i], acc[8 + 2 * i + 1]); }
                const int s = 4 * pb + wa;
                uint32_t* kp = (uint32_t*)(g_kimg + s * 512 + g * 16 + 4 * t);
                kp[0] = kk[0]; kp[64] = kk[1]; kp[32] = kk[2]; kp[96] = kk[3];
                uint32_t* vlo = (uint32_t*)(g_vimg + (127 - s) * 256 + g * 16 + 4 * t);
                uint32_t* vhi = (uint32_t*)(g_vimg + 32768 + 256 + s * 256 + g * 16 + 4 * t);
                vlo[0] = pack_f16(bf_lo(vv[0]), bf_hi(vv[0])); vlo[32] = pack_f16(bf_lo(vv[1]), bf_hi(vv[1]));
                vhi[0] = pack_f16(bf_lo(vv[2]), bf_hi(vv[2])); vhi[32] = pack_f16(bf_lo(vv[3]), bf_hi(vv[3]));
                uint32_t* vr = (uint32_t*)(g_vraw + (size_t)(16 * s + g) * 16) + t;
                vr[0] = vv[0]; vr[64] = vv[1]; vr[4] = vv[2]; vr[68] = vv[3];
                float n0 = bf_lo(kk[0]) * bf_lo(kk[0]) + bf_hi(kk[0]) * bf_hi(kk[0]) + bf_lo(kk[2]) * bf_lo(kk[2]) + bf_hi(kk[2]) * bf_hi(kk[2]);
                float n1 = bf_lo(kk[1]) * bf_lo(kk[1]) + bf_hi(kk[1]) * bf_hi(kk[1]) + bf_lo(kk[3]) * bf_lo(kk[3]) + bf_hi(kk[3]) * bf_hi(kk[3]);
                n0 += __shfl_xor_sync(0xffffffffu, n0, 1); n0 += __shfl_xor_sync(0xffffffffu, n0, 2);
                n1 += __shfl_xor_sync(0xffffffffu, n1, 1); n1 += __shfl_xor_sync(0xffffffffu, n1, 2);
                float km = fmaxf(n0, n1), vm = 0.f;
#pragma unroll
                for (int i = 0; i < 4; i++) vm = fmaxf(vm, fmaxf(fabsf(bf_lo(vv[i])), fabsf(bf_hi(vv[i]))));
#pragma unroll
                for (int o = 4; o < 32; o <<= 1) km = fmaxf(km, __shfl_xor_sync(0xffffffffu, km, o));
#pragma unroll
                for (int o = 1; o < 32; o <<= 1) vm = fmaxf(vm, __shfl_xor_sync(0xffffffffu, vm, o));
                __syncwarp();
                if (lane == 0) {
                    const unsigned long long rec = ((unsigned long long)(__float_as_uint(vm) | 0x80000000u) << 32) | __float_as_uint(km);
                    asm volatile("st.release.gpu.global.u64 [%0], %1;" ::"l"(&g_stats[s]), "l"(rec) : "memory");
                    if (wa == 0) TSTAMP(8);
                }
            }
            if (tau == 0) {
                for (int jj = 0; jj < 2; jj++) {
                    mbar_expect_tx(bar(B_W + jj), 32768);
                    tma4d(sb + OFF_V + jj * 32768, &tm_wq, 0, 0, hg * 2, 2 * jj, bar(B_W + jj));
                }
            }
            __syncwarp();
        }
        const int c0 = 4 * b;
        if (wa == 0) {
            if (lane == 0) {
                for (int jj = 2; jj < 4; jj++) {
                    mbar_wait(bar(B_QEMPTY + jj - 2), 0);
                    mbar_expect_tx(bar(B_W + jj), 32768);
                    tma4d(sb + OFF_V + (jj - 2) * 32768, &tm_wq, 0, 0, hg * 2, 2 * jj, bar(B_W + jj));
                }
            }
            __syncwarp();
            float km = 0.f, vm = 0.f;
            {
                unsigned long long rec[4];
                uint32_t spins = 0;
                bool ok;
                do {
                    ok = true;
#pragma unroll
                    for (int i = 0; i < 4; i++) {
                        asm volatile("ld.relaxed.gpu.global.u64 %0, [%1];" : "=l"(rec[i]) : "l"(&g_stats[lane + 32 * i]) : "memory");
                        ok = ok && (rec[i] >> 63);
                    }
                    if (++spins > (1u << 22)) __trap();
                } while (!__all_sync(0xffffffffu, ok));
                asm volatile("fence.acq_rel.gpu;" ::: "memory");
#pragma unroll
                for (int i = 0; i < 4; i++) { km = fmaxf(km, __uint_as_float((uint32_t)rec[i])); vm = fmaxf(vm, __uint_as_float((uint32_t)(rec[i] >> 32) & 0x7FFFFFFFu)); }
            }
            if (lane == 0) {
                TSTAMP(16);
                fence_async_global();
                for (int c = 0; c < 8; c++) {
                    mbar_expect_tx_noarrive(bar(B_KV + c), 8192);
                    bulk_g2s(sb + OFF_K + c * 8192, g_kimg + c * 8192, 8192, bar(B_KV + c));
                }
                TSTAMP(28);
            }
#pragma unroll
            for (int o = 1; o < 32; o <<= 1) { km = fmaxf(km, __shfl_xor_sync(0xffffffffu, km, o)); vm = fmaxf(vm, __shfl_xor_sync(0xffffffffu, vm, o)); }
            const bool vdirect = (vm <= 32768.f && vm >= 9.765625e-4f) || vm == 0.f;
            float vs = 1.f;
            if (!vdirect && vm < INFINITY) {
                int e = (int)((__float_as_uint(vm) >> 23) & 0xFF) - 127;
                e = max(-100, min(100, e));
                vs = __uint_as_float((uint32_t)(127 + e - 13) << 23);
            }
            if (lane == 0) {
                asm volatile("st.shared.f32 [%0], %1;" ::"r"(sb + OFF_MISC), "f"(km) : "memory");
                asm volatile("st.shared.f32 [%0], %1;" ::"r"(sb + OFF_MISC + 4), "f"(vs) : "memory");
                mbar_wait(bar(B_QDONE), 0);
                TSTAMP(17);
                for (int c = 0; c < 8; c++) {
                    if (vdirect) {
                        mbar_expect_tx(bar(B_KV + c), 8192);
                        bulk_g2s(sb + OFF_V + (112 - 16 * c) * 256, g_vimg + (112 - 16 * c) * 256, 4096, bar(B_KV + c));
                        bulk_g2s(sb + OFF_VONES + 256 + c * 4096, g_vimg + 32768 + 256 + c * 4096, 4096, bar(B_KV + c));
                    }
                }
            }
            __syncwarp();
            sts32(sb + OFF_VONES + lane * 8, 0x3C003C00u);
            sts32(sb + OFF_VONES + lane * 8 + 4, 0x3C003C00u);
            if (!vdirect) {
                const float inv = 1.f / vs;
                for (int idx = lane; idx < S_LEN * 8; idx += 32) {
                    const int key = idx >> 3, dp = idx & 7;
                    const uint32_t v = __ldcg((const uint32_t*)g_vraw + idx);
                    const uint32_t h = pack_f16(bf_lo(v) * inv, bf_hi(v) * inv);
                    const int st = key >> 4, hf = (key >> 3) & 1;
                    const uint32_t base = (dp < 4) ? (OFF_V + (127 - st) * 256) : (OFF_VONES + 256 + st * 256);
                    sts32(sb + base + hf * 128 + (key & 7) * 16 + (dp & 3) * 4, h);
                }
            }
            fence_async_smem();
            __syncwarp();
            if (lane == 0) {
                mbar_arrive(bar(B_KV + 0));
                if (!vdirect) for (int c = 0; c < 8; c++) mbar_arrive(bar(B_KV + c));
                prefetch_tm(&tm_wo); prefetch_tm(&tm_o);
                for (int jj = 0; jj < 2; jj++) {
                    mbar_expect_tx(bar(B_WO + jj), 32768);
                    tma4d(sb + OFF_X + jj * 32768, &tm_wo, 0, 0, hg * 2, 2 * jj, bar(B_WO + jj));
                }
            }
            __syncwarp();
        } else {
            if (wa == 1 && lane == 0) {
                mbar_expect_tx(bar(B_H), 4096);
                tma2d(sb + C_H + 2048, &tm_h, 0, c0 * 64, bar(B_H));
                mbar_wait(bar(B_KVT), 0);
                red_release_add(&g_kvt_count[hg], 1);
                TSTAMP(34);
                poll_counter(&g_kvt_count[b >> 5], 32);
                fence_async_global();
                mbar_expect_tx(bar(B_CV), 16384);
                bulk_g2s(sb + C_KVC, g_kvT + (size_t)c0 * S_LEN, 16384, bar(B_CV));
            }
            __syncwarp();
            if (wa >= 2) {
                sts128(sb + C_H + (tau - 64) * 32, 0u, 0u, 0u, 0u);
                sts128(sb + C_H + (tau - 64) * 32 + 16, 0u, 0u, 0u, 0u);
                fence_async_smem();
            }
        }
        named_bar(5, 128);
        mbar_wait_w(bar(B_CV), 0);
        if (tau == 0) TSTAMP(9);
        const int NCH = 4;
#pragma unroll 1
        for (int ch = 0; ch < NCH; ch++) {
            {
                const uint32_t src = sb + C_KVC + ch * 4096 + tau * 32;
                const uint4 u0 = lds128(src), u1 = lds128(src + 16);
                const uint32_t prev = tau > 0 ? lds32(src - 4) : 0u;
                const uint32_t zd = sb + C_Z + (32 + tau * 16) * 4;
                sts128(zd,      __byte_perm(u0.x, prev, 0x7610), __byte_perm(u0.x, u0.x, 0x1032), __byte_perm(u0.y, u0.x, 0x7610), __byte_perm(u0.y, u0.y, 0x1032));
                sts128(zd + 16, __byte_perm(u0.z, u0.y, 0x7610), __byte_perm(u0.z, u0.z, 0x1032), __byte_perm(u0.w, u0.z, 0x7610), __byte_perm(u0.w, u0.w, 0x1032));
                sts128(zd + 32, __byte_perm(u1.x, u0.w, 0x7610), __byte_perm(u1.x, u1.x, 0x1032), __byte_perm(u1.y, u1.x, 0x7610), __byte_perm(u1.y, u1.y, 0x1032));
                sts128(zd + 48, __byte_perm(u1.z, u1.y, 0x7610), __byte_perm(u1.z, u1.z, 0x1032), __byte_perm(u1.w, u1.z, 0x7610), __byte_perm(u1.w, u1.w, 0x1032));
                if (tau < 32) sts32(sb + C_Z + tau * 4, 0u);
            }
            named_bar(5, 128);
            mbar_wait_w(bar(B_H), ch & 1);
            float D[32];
#pragma unroll
            for (int i = 0; i < 32; i++) D[i] = 0.f;
            fence_regs<32>(D);
            const uint32_t z0 = sb + C_Z + (32 + 32 * (wa >> 1) + 16 * (wa & 1) + 2 * g - 2 * t) * 4;
            const uint64_t hd = make_desc(sb + C_H + 2048, 16, 512, 2);
            conv_phase<64>(D, z0, hd);
            float E[16];
#pragma unroll
            for (int i = 0; i < 16; i++) asm volatile("mov.f32 %0, %1;" : "=f"(E[i]) : "f"(D[16 + i]));
            conv_phase<32>(E, z0 + 4096, hd);
            if (tau == 0 && ch < 3) {
                mbar_expect_tx(bar(B_H), 4096);
                tma2d(sb + C_H + 2048, &tm_h, 0, (c0 + ch + 1) * 64, bar(B_H));
            }
            const int bb0 = 16 * (wa & 1) + 2 * g;
            const int xsw = (g & 3) << 3;
            {
                const uint32_t xb = sb + C_Z + (wa >> 1) * 4096;
#pragma unroll
                for (int jn = 0; jn < 4; jn++) {
#pragma unroll
                    for (int r = 0; r < 2; r++) {
                        const float v0 = (wa < 2) ? E[4 * jn + 2 * r] : D[4 * jn + 2 * r];
                        const float v1 = (wa < 2) ? E[4 * jn + 2 * r + 1] : D[4 * jn + 2 * r + 1];
                        sts64f(xb + ((bb0 + r) * 32 + ((8 * jn + 2 * t) ^ xsw)) * 4, v0, v1);
                    }
                }
            }
            named_bar(5, 128);
            {
                const float dsc = __bfloat162float(prm.ssm_D[c0 + ch]);
                const uint32_t xb = sb + C_Z + ((wa >> 1) ^ 1) * 4096;
#pragma unroll
                for (int jn = 0; jn < 4; jn++) {
#pragma unroll
                    for (int e = 0; e < 2; e++) {
                        const int n = 8 * jn + 2 * t + e;
                        float y0, y1; int m, rn;
                        if (wa < 2) { y0 = D[4 * jn + e]; y1 = D[4 * jn + 2 + e]; m = n; rn = n - 1; }
                        else {
                            const bool last = (jn == 3 && e == 1) && (t == 3);
                            y0 = last ? D[13] : E[4 * jn + e]; y1 = last ? D[15] : E[4 * jn + 2 + e];
                            m = last ? 32 : 33 + n; rn = m - 32;
                        }
                        if (rn >= 0) {
                            y0 += ldsf(xb + (bb0 * 32 + (rn ^ xsw)) * 4);
                            y1 += ldsf(xb + ((bb0 + 1) * 32 + (rn ^ xsw)) * 4);
                        }
                        const uint32_t addr = sb + C_KVC + ch * 4096 + (32 * m + bb0) * 2;
                        const uint32_t kv = lds32(addr);
                        const uint32_t yb = pack_bf16(y0, y1);
                        const uint32_t kd = pack_bf16(bf_lo(kv) * dsc, bf_hi(kv) * dsc);
                        sts32(addr, badd2(yb, kd));
                    }
                }
                fence_async_smem();
            }
            named_bar(5, 128);
            if (tau == 0) {
                bulk_s2g(g_zT + (size_t)(c0 + ch) * S_LEN, sb + C_KVC + ch * 4096, 4096);
                bulk_commit();
                TSTAMP(10 + ch);
            }
        }
        {
            const int cg = tau & 15, pr = tau >> 4;
            const int p0 = pb * 64 + pr * 8, ch0 = hg * 128 + cg * 8;
            uint4 qr[8];
#pragma unroll
            for (int i = 0; i < 8; i++) qr[i] = __ldg((const uint4*)(prm.aq + (size_t)(p0 + i) * 512 + ch0));
            if (tau == 0) {
                bulk_wait_all();
                mbar_expect_tx(bar(B_WO + 3), 32768);
                tma4d(sb + OFF_C, &tm_wo, 0, 0, hg * 2, 6, bar(B_WO + 3));
                fence_async_global();
                red_release_add(&g_z_count[b >> 5], 1);
                poll_counter(&g_z_count[hg], 32);
                __threadfence();
                if (atomicAdd(&g_done, 1) == 2 * NCTA - 1) {
                    for (int i = 0; i < NCTA; i++) g_stats[i] = 0ull;
                    for (int i = 0; i < 4; i++) { g_kvt_count[i] = 0; g_z_count[i] = 0; }
                    for (int i = 0; i < 32; i++) g_o_count[i] = 0;
                    g_done = 0;
                    __threadfence();
                }
            }
            named_bar(5, 128);
            uint4 zz[8];
#pragma unroll
            for (int c = 0; c < 8; c++) zz[c] = __ldcg((const uint4*)(g_zT + (size_t)(ch0 + c) * S_LEN + p0));
#pragma unroll
            for (int i = 0; i < 8; i++) {
                uint32_t r[4];
#pragma unroll
                for (int k = 0; k < 4; k++) {
                    const uint32_t pr2 = __byte_perm((&zz[2 * k].x)[i >> 1], (&zz[2 * k + 1].x)[i >> 1], (i & 1) ? 0x7632 : 0x5410);
                    r[k] = bmul2((&qr[i].x)[k], pr2);
                }
                *(uint4*)(prm.out + (size_t)(p0 + i) * 1024 + ch0) = make_uint4(r[0], r[1], r[2], r[3]);
            }
        }
        if (tau == 0) TSTAMP(14);
    }
}

typedef CUresult (*EncodeFn)(CUtensorMap*, CUtensorMapDataType, cuuint32_t, void*, const cuuint64_t*, const cuuint64_t*,
                             const cuuint32_t*, const cuuint32_t*, CUtensorMapInterleave, CUtensorMapSwizzle,
                             CUtensorMapL2promotion, CUtensorMapFloatOOBfill);

void make_map(EncodeFn fn, CUtensorMap* tm, const void* ptr, int rank, const cuuint64_t* dims, const cuuint64_t* strides, const cuuint32_t* box, CUtensorMapSwizzle swz) {
    cuuint32_t es[4] = {1, 1, 1, 1};
    fn(tm, CU_TENSOR_MAP_DATA_TYPE_BFLOAT16, rank, const_cast<void*>(ptr), dims, strides, box, es, CU_TENSOR_MAP_INTERLEAVE_NONE, swz,
       CU_TENSOR_MAP_L2_PROMOTION_L2_128B, CU_TENSOR_MAP_FLOAT_OOB_FILL_NONE);
}

}

extern "C" void kernel_launch(void* const* d_in, const int* in_sizes, int n_in, void* d_out, int out_size) {
    (void)in_sizes; (void)n_in; (void)out_size;
    static EncodeFn encode = nullptr;
    static void* o_ptr = nullptr;
    if (!encode) {
        cudaDriverEntryPointQueryResult qres;
        void* fn = nullptr;
        cudaGetDriverEntryPoint("cuTensorMapEncodeTiled", &fn, cudaEnableDefault, &qres);
        encode = (EncodeFn)fn;
        cudaGetSymbolAddress(&o_ptr, g_o);
        cudaFuncSetAttribute(fused_kernel, cudaFuncAttributeMaxDynamicSharedMemorySize, SMEM_TOTAL);
    }
    CUtensorMap tm_x, tm_wq, tm_wo, tm_wk, tm_wv, tm_o, tm_h;
    {
        const cuuint64_t dims[3] = {64, 2048, 8}, str[2] = {1024, 128};
        const cuuint32_t b64[3] = {64, 64, 2};
        make_map(encode, &tm_x, d_in[6], 3, dims, str, b64, CU_TENSOR_MAP_SWIZZLE_128B);
        make_map(encode, &tm_o, o_ptr, 3, dims, str, b64, CU_TENSOR_MAP_SWIZZLE_128B);
    }
    {
        const cuuint64_t dims[4] = {64, 64, 8, 8}, str[3] = {1024, 128, 65536};
        const cuuint32_t box[4] = {64, 64, 2, 2};
        make_map(encode, &tm_wq, d_in[7], 4, dims, str, box, CU_TENSOR_MAP_SWIZZLE_128B);
        make_map(encode, &tm_wo, d_in[10], 4, dims, str, box, CU_TENSOR_MAP_SWIZZLE_128B);
    }
    {
        const cuuint64_t dims[3] = {16, 256, 2}, str[2] = {32, 8192};
        const cuuint32_t box[3] = {16, 256, 2};
        make_map(encode, &tm_wk, d_in[8], 3, dims, str, box, CU_TENSOR_MAP_SWIZZLE_32B);
        make_map(encode, &tm_wv, d_in[9], 3, dims, str, box, CU_TENSOR_MAP_SWIZZLE_32B);
    }
    {
        const cuuint64_t dims[2] = {32, 512 * 64}, str[1] = {64};
        const cuuint32_t box[2] = {32, 64};
        make_map(encode, &tm_h, d_in[4], 2, dims, str, box, CU_TENSOR_MAP_SWIZZLE_64B);
    }
    Params prm;
    prm.aq = (const __nv_bfloat16*)d_in[0];
    prm.ak = (const __nv_bfloat16*)d_in[1];
    prm.av = (const __nv_bfloat16*)d_in[2];
    prm.shift_k = (const __nv_bfloat16*)d_in[3];
    prm.ssm_D = (const __nv_bfloat16*)d_in[5];
    prm.out = (__nv_bfloat16*)d_out;
    fused_kernel<<<NCTA, NTHREADS, SMEM_TOTAL>>>(tm_x, tm_wq, tm_wo, tm_wk, tm_wv, tm_o, tm_h, prm);
}
```

```cpp
#include <cuda_runtime.h>
#include <cuda_bf16.h>
#include <cuda_fp16.h>
#include <cuda.h>
#include <stdint.h>

namespace {

constexpr int S_LEN = 2048;
constexpr int NCTA = 128;
constexpr int NTHREADS = 640;

constexpr uint32_t OFF_K = 0;
constexpr uint32_t OFF_V = 65536;
constexpr uint32_t OFF_VONES = OFF_V + 32768;
constexpr uint32_t OFF_X = 132096;
constexpr uint32_t OFF_C = 197632;
constexpr uint32_t C_KVC = OFF_C;
constexpr uint32_t C_H = OFF_C + 16384;
constexpr uint32_t C_Z = C_H + 6144;
constexpr uint32_t OFF_BAR = 231936;
constexpr uint32_t SMEM_TOTAL = 232448;

enum { B_WKV = 0, B_X = 1, B_QEMPTY = 5, B_QDONE = 7, B_KV = 8, B_WO = 16, B_O = 20, B_ATT = 24, B_H = 25, B_CV = 26, B_W = 27, B_KVT = 31, B_KVIN = 32, B_COUNT = 33 };
constexpr uint32_t OFF_MISC = OFF_BAR + 8 * B_COUNT;

__device__ __align__(1024) uint8_t g_kimg[65536];
__device__ __align__(1024) uint8_t g_vimg[65792];
__device__ __align__(1024) __nv_bfloat16 g_vraw[S_LEN * 16];
__device__ __align__(1024) __nv_bfloat16 g_o[S_LEN * 512];
__device__ __align__(1024) __nv_bfloat16 g_kvT[512 * S_LEN];
__device__ __align__(1024) __nv_bfloat16 g_zT[512 * S_LEN];
__device__ unsigned long long g_stats[NCTA];
__device__ unsigned int g_kvt_count[4];
__device__ unsigned int g_z_count[4];
__device__ unsigned int g_o_count[32];
__device__ unsigned int g_done;
#define TSTAMP(i) do {} while (0)
#define CSTAMP(i) do {} while (0)

__device__ __forceinline__ void wg_fence() { asm volatile("wgmma.fence.sync.aligned;" ::: "memory"); }
__device__ __forceinline__ void wg_commit() { asm volatile("wgmma.commit_group.sync.aligned;" ::: "memory"); }
template <int N> __device__ __forceinline__ void wg_wait() { asm volatile("wgmma.wait_group.sync.aligned %0;" ::"n"(N) : "memory"); }
template <int N> __device__ __forceinline__ void fence_regs(float* r) {
#pragma unroll
    for (int i = 0; i < N; i++) asm volatile("" : "+f"(r[i])::"memory");
}
template <int N> __device__ __forceinline__ void fence_uregs(uint32_t* r) {
#pragma unroll
    for (int i = 0; i < N; i++) asm volatile("" : "+r"(r[i])::"memory");
}
__device__ __forceinline__ uint64_t make_desc(uint32_t saddr, uint32_t lbo, uint32_t sbo, uint32_t swz) {
    return (uint64_t)((saddr & 0x3FFFF) >> 4) | ((uint64_t)(lbo >> 4) << 16) | ((uint64_t)(sbo >> 4) << 32) | ((uint64_t)swz << 62);
}
__device__ __forceinline__ void mbar_init(uint32_t bar, uint32_t count) {
    asm volatile("mbarrier.init.shared::cta.b64 [%0], %1;" ::"r"(bar), "r"(count) : "memory");
}
__device__ __forceinline__ void mbar_expect_tx(uint32_t bar, uint32_t bytes) {
    asm volatile("mbarrier.arrive.expect_tx.shared::cta.b64 _, [%0], %1;" ::"r"(bar), "r"(bytes) : "memory");
}
__device__ __forceinline__ void mbar_expect_tx_noarrive(uint32_t bar, uint32_t bytes) {
    asm volatile("mbarrier.expect_tx.relaxed.cta.shared::cta.b64 [%0], %1;" ::"r"(bar), "r"(bytes) : "memory");
}
__device__ __forceinline__ void mbar_arrive(uint32_t bar) {
    asm volatile("mbarrier.arrive.shared::cta.b64 _, [%0];" ::"r"(bar) : "memory");
}
__device__ __forceinline__ bool mbar_try(uint32_t bar, uint32_t parity) {
    uint32_t ok;
    asm volatile("{\n.reg .pred p;\nmbarrier.try_wait.parity.shared::cta.b64 p, [%1], %2;\nselp.u32 %0, 1, 0, p;\n}\n"
                 : "=r"(ok) : "r"(bar), "r"(parity) : "memory");
    return ok != 0;
}
__device__ __forceinline__ void mbar_wait(uint32_t bar, uint32_t parity) {
    uint32_t spins = 0;
    while (!mbar_try(bar, parity)) {
        if (++spins > (1u << 24)) __trap();
    }
}
__device__ __forceinline__ void mbar_wait_w(uint32_t bar, uint32_t parity) {
    uint32_t spins = 0;
    while (!__all_sync(0xffffffffu, mbar_try(bar, parity))) {
        if (++spins > (1u << 24)) __trap();
    }
}
__device__ __forceinline__ void tma2d(uint32_t dst, const CUtensorMap* tm, int c0, int c1, uint32_t bar) {
    asm volatile("cp.async.bulk.tensor.2d.shared::cluster.global.mbarrier::complete_tx::bytes [%0], [%1, {%3, %4}], [%2];"
                 ::"r"(dst), "l"((uint64_t)tm), "r"(bar), "r"(c0), "r"(c1) : "memory");
}
__device__ __forceinline__ void tma3d(uint32_t dst, const CUtensorMap* tm, int c0, int c1, int c2, uint32_t bar) {
    asm volatile("cp.async.bulk.tensor.3d.shared::cluster.global.mbarrier::complete_tx::bytes [%0], [%1, {%3, %4, %5}], [%2];"
                 ::"r"(dst), "l"((uint64_t)tm), "r"(bar), "r"(c0), "r"(c1), "r"(c2) : "memory");
}
__device__ __forceinline__ void tma4d(uint32_t dst, const CUtensorMap* tm, int c0, int c1, int c2, int c3, uint32_t bar) {
    asm volatile("cp.async.bulk.tensor.4d.shared::cluster.global.mbarrier::complete_tx::bytes [%0], [%1, {%3, %4, %5, %6}], [%2];"
                 ::"r"(dst), "l"((uint64_t)tm), "r"(bar), "r"(c0), "r"(c1), "r"(c2), "r"(c3) : "memory");
}
__device__ __forceinline__ void prefetch_tm(const CUtensorMap* tm) { asm volatile("prefetch.tensormap [%0];" ::"l"((uint64_t)tm) : "memory"); }
__device__ __forceinline__ void bulk_s2g(void* dst, uint32_t src, uint32_t bytes) {
    asm volatile("cp.async.bulk.global.shared::cta.bulk_group [%0], [%1], %2;" ::"l"(dst), "r"(src), "r"(bytes) : "memory");
}
__device__ __forceinline__ void bulk_commit() { asm volatile("cp.async.bulk.commit_group;" ::: "memory"); }
__device__ __forceinline__ void bulk_wait_all() { asm volatile("cp.async.bulk.wait_group 0;" ::: "memory"); }
__device__ __forceinline__ void fence_async_global() { asm volatile("fence.proxy.async.global;" ::: "memory"); }
__device__ __forceinline__ void bulk_g2s(uint32_t dst, const void* src, uint32_t bytes, uint32_t bar) {
    asm volatile("cp.async.bulk.shared::cluster.global.mbarrier::complete_tx::bytes [%0], [%1], %2, [%3];"
                 ::"r"(dst), "l"(src), "r"(bytes), "r"(bar) : "memory");
}
__device__ __forceinline__ void fence_async_smem() { asm volatile("fence.proxy.async.shared::cta;" ::: "memory"); }
__device__ __forceinline__ void named_bar(int id, int n) { asm volatile("bar.sync %0, %1;" ::"r"(id), "r"(n) : "memory"); }
__device__ __forceinline__ bool named_bar_and(int id, int n, bool pred) {
    uint32_t r;
    asm volatile("{\n.reg .pred p, q;\nsetp.ne.u32 p, %3, 0;\nbarrier.cta.red.and.pred q, %1, %2, p;\nselp.u32 %0, 1, 0, q;\n}\n"
                 : "=r"(r) : "r"(id), "r"(n), "r"((uint32_t)pred) : "memory");
    return r != 0;
}
__device__ __forceinline__ unsigned int ld_acquire(const unsigned int* p) {
    unsigned int v;
    asm volatile("ld.acquire.gpu.global.u32 %0, [%1];" : "=r"(v) : "l"(p) : "memory");
    return v;
}
__device__ __forceinline__ void red_release_add(unsigned int* p, unsigned int v) {
    asm volatile("red.release.gpu.global.add.u32 [%0], %1;" ::"l"(p), "r"(v) : "memory");
}
__device__ __forceinline__ void poll_counter(const unsigned int* p, unsigned int target) {
    uint32_t spins = 0;
    while (ld_acquire(p) < target) {
        if (++spins > (1u << 22)) __trap();
    }
}
__device__ __forceinline__ float ex2f(float x) { float y; asm("ex2.approx.ftz.f32 %0, %1;" : "=f"(y) : "f"(x)); return y; }
__device__ __forceinline__ uint32_t pack_f16(float lo, float hi) { uint32_t r; asm("cvt.rn.f16x2.f32 %0, %1, %2;" : "=r"(r) : "f"(hi), "f"(lo)); return r; }
__device__ __forceinline__ uint32_t pack_bf16(float lo, float hi) { uint32_t r; asm("cvt.rn.bf16x2.f32 %0, %1, %2;" : "=r"(r) : "f"(hi), "f"(lo)); return r; }
__device__ __forceinline__ float bf_lo(uint32_t v) { return __uint_as_float(v << 16); }
__device__ __forceinline__ float bf_hi(uint32_t v) { return __uint_as_float(v & 0xFFFF0000u); }
__device__ __forceinline__ uint32_t hfma2(uint32_t a, uint32_t b, uint32_t c) { uint32_t r; asm("fma.rn.f16x2 %0, %1, %2, %3;" : "=r"(r) : "r"(a), "r"(b), "r"(c)); return r; }
__device__ __forceinline__ uint32_t bmul2(uint32_t a, uint32_t b) { uint32_t r; asm("mul.rn.bf16x2 %0, %1, %2;" : "=r"(r) : "r"(a), "r"(b)); return r; }
__device__ __forceinline__ uint32_t badd2(uint32_t a, uint32_t b) { uint32_t r; asm("add.rn.bf16x2 %0, %1, %2;" : "=r"(r) : "r"(a), "r"(b)); return r; }
template <int LUT> __device__ __forceinline__ uint32_t lop3(uint32_t a, uint32_t b, uint32_t c) {
    uint32_t r; asm("lop3.b32 %0, %1, %2, %3, %4;" : "=r"(r) : "r"(a), "r"(b), "r"(c), "n"(LUT)); return r;
}
__device__ __forceinline__ uint32_t lds32(uint32_t a) { uint32_t v; asm volatile("ld.shared.u32 %0, [%1];" : "=r"(v) : "r"(a)); return v; }
__device__ __forceinline__ float ldsf(uint32_t a) { float v; asm volatile("ld.shared.f32 %0, [%1];" : "=f"(v) : "r"(a)); return v; }
__device__ __forceinline__ uint4 lds128(uint32_t a) { uint4 v; asm volatile("ld.shared.v4.u32 {%0,%1,%2,%3}, [%4];" : "=r"(v.x), "=r"(v.y), "=r"(v.z), "=r"(v.w) : "r"(a)); return v; }
__device__ __forceinline__ void lds64(uint32_t a, uint32_t& x, uint32_t& y) { asm volatile("ld.shared.v2.u32 {%0,%1}, [%2];" : "=r"(x), "=r"(y) : "r"(a)); }
__device__ __forceinline__ void sts32(uint32_t a, uint32_t v) { asm volatile("st.shared.u32 [%0], %1;" ::"r"(a), "r"(v) : "memory"); }
__device__ __forceinline__ void sts64f(uint32_t a, float x, float y) { asm volatile("st.shared.v2.f32 [%0], {%1,%2};" ::"r"(a), "f"(x), "f"(y) : "memory"); }
__device__ __forceinline__ void sts128(uint32_t a, uint32_t x, uint32_t y, uint32_t z, uint32_t w) {
    asm volatile("st.shared.v4.u32 [%0], {%1,%2,%3,%4};" ::"r"(a), "r"(x), "r"(y), "r"(z), "r"(w) : "memory");
}

__device__ __forceinline__ void wg_ss_n32_tb(float* d, uint64_t descA, uint64_t descB) {
    asm volatile("wgmma.mma_async.sync.aligned.m64n32k16.f32.bf16.bf16 {%0,%1,%2,%3,%4,%5,%6,%7,%8,%9,%10,%11,%12,%13,%14,%15}, %16, %17, 1, 1, 1, 0, 1;\n"
        : "+f"(d[0]), "+f"(d[1]), "+f"(d[2]), "+f"(d[3]), "+f"(d[4]), "+f"(d[5]), "+f"(d[6]), "+f"(d[7]), "+f"(d[8]), "+f"(d[9]), "+f"(d[10]), "+f"(d[11]), "+f"(d[12]), "+f"(d[13]), "+f"(d[14]), "+f"(d[15])
        : "l"(descA), "l"(descB));
}
__device__ __forceinline__ void wg_qk_n64(float* d, const uint32_t* a, uint64_t desc) {
    asm volatile("wgmma.mma_async.sync.aligned.m64n64k16.f32.bf16.bf16 {%0,%1,%2,%3,%4,%5,%6,%7,%8,%9,%10,%11,%12,%13,%14,%15,%16,%17,%18,%19,%20,%21,%22,%23,%24,%25,%26,%27,%28,%29,%30,%31}, {%32,%33,%34,%35}, %36, 0, 1, 1, 0;\n"
        : "+f"(d[0]), "+f"(d[1]), "+f"(d[2]), "+f"(d[3]), "+f"(d[4]), "+f"(d[5]), "+f"(d[6]), "+f"(d[7]), "+f"(d[8]), "+f"(d[9]), "+f"(d[10]), "+f"(d[11]), "+f"(d[12]), "+f"(d[13]), "+f"(d[14]), "+f"(d[15]), "+f"(d[16]), "+f"(d[17]), "+f"(d[18]), "+f"(d[19]), "+f"(d[20]), "+f"(d[21]), "+f"(d[22]), "+f"(d[23]), "+f"(d[24]), "+f"(d[25]), "+f"(d[26]), "+f"(d[27]), "+f"(d[28]), "+f"(d[29]), "+f"(d[30]), "+f"(d[31])
        : "r"(a[0]), "r"(a[1]), "r"(a[2]), "r"(a[3]), "l"(desc));
}
__device__ __forceinline__ void wg_pv_n24(float* d, const uint32_t* a, uint64_t desc) {
    asm volatile("wgmma.mma_async.sync.aligned.m64n24k16.f32.f16.f16 {%0,%1,%2,%3,%4,%5,%6,%7,%8,%9,%10,%11}, {%12,%13,%14,%15}, %16, 1, 1, 1, 1;\n"
        : "+f"(d[0]), "+f"(d[1]), "+f"(d[2]), "+f"(d[3]), "+f"(d[4]), "+f"(d[5]), "+f"(d[6]), "+f"(d[7]), "+f"(d[8]), "+f"(d[9]), "+f"(d[10]), "+f"(d[11])
        : "r"(a[0]), "r"(a[1]), "r"(a[2]), "r"(a[3]), "l"(desc));
}
__device__ __forceinline__ void wg_cv_n32(float* d, const uint32_t* a, uint64_t desc) {
    asm volatile("wgmma.mma_async.sync.aligned.m64n32k16.f32.bf16.bf16 {%0,%1,%2,%3,%4,%5,%6,%7,%8,%9,%10,%11,%12,%13,%14,%15}, {%16,%17,%18,%19}, %20, 1, 1, 1, 0;\n"
        : "+f"(d[0]), "+f"(d[1]), "+f"(d[2]), "+f"(d[3]), "+f"(d[4]), "+f"(d[5]), "+f"(d[6]), "+f"(d[7]), "+f"(d[8]), "+f"(d[9]), "+f"(d[10]), "+f"(d[11]), "+f"(d[12]), "+f"(d[13]), "+f"(d[14]), "+f"(d[15])
        : "r"(a[0]), "r"(a[1]), "r"(a[2]), "r"(a[3]), "l"(desc));
}
__device__ __forceinline__ void wg_cv_n64(float* d, const uint32_t* a, uint64_t desc) {
    asm volatile("wgmma.mma_async.sync.aligned.m64n64k16.f32.bf16.bf16 {%0,%1,%2,%3,%4,%5,%6,%7,%8,%9,%10,%11,%12,%13,%14,%15,%16,%17,%18,%19,%20,%21,%22,%23,%24,%25,%26,%27,%28,%29,%30,%31}, {%32,%33,%34,%35}, %36, 1, 1, 1, 0;\n"
        : "+f"(d[0]), "+f"(d[1]), "+f"(d[2]), "+f"(d[3]), "+f"(d[4]), "+f"(d[5]), "+f"(d[6]), "+f"(d[7]), "+f"(d[8]), "+f"(d[9]), "+f"(d[10]), "+f"(d[11]), "+f"(d[12]), "+f"(d[13]), "+f"(d[14]), "+f"(d[15]), "+f"(d[16]), "+f"(d[17]), "+f"(d[18]), "+f"(d[19]), "+f"(d[20]), "+f"(d[21]), "+f"(d[22]), "+f"(d[23]), "+f"(d[24]), "+f"(d[25]), "+f"(d[26]), "+f"(d[27]), "+f"(d[28]), "+f"(d[29]), "+f"(d[30]), "+f"(d[31])
        : "r"(a[0]), "r"(a[1]), "r"(a[2]), "r"(a[3]), "l"(desc));
}

template <int N> __device__ __forceinline__ void wg_cv(float* d, const uint32_t* a, uint64_t desc);
template <> __device__ __forceinline__ void wg_cv<32>(float* d, const uint32_t* a, uint64_t s) { wg_cv_n32(d, a, s); }
template <> __device__ __forceinline__ void wg_cv<64>(float* d, const uint32_t* a, uint64_t s) { wg_cv_n64(d, a, s); }

constexpr uint32_t POLYMASK = 0xB5B5u;
__device__ __forceinline__ void softmax_fast(const float* s, uint32_t* p, uint32_t mlo) {
    const uint32_t C3 = 0x2cfb2cfbu, C2 = 0x9fec9fecu, C1 = 0x37a837a8u, C0 = 0x37383738u;
#pragma unroll
    for (int i = 0; i < 16; i++) {
        const float s0 = s[2 * i], s1 = s[2 * i + 1];
        if ((POLYMASK >> i) & 1) {
            const float t0 = s0 + 12303.0f, t1 = s1 + 12303.0f;
            const uint32_t T = __byte_perm(__float_as_uint(t0), __float_as_uint(t1), 0x5410);
            const uint32_t U = lop3<0xEA>(T, mlo, 0x3C003C00u);
            uint32_t h = hfma2(U, C3, C2);
            h = hfma2(h, U, C1);
            h = hfma2(h, U, C0);
            p[i] = lop3<0xE4>(h, T, 0x03FF03FFu);
        } else {
            p[i] = pack_f16(ex2f(s0), ex2f(s1));
        }
    }
}

__device__ __forceinline__ void gemm_chunk(float* acc, uint32_t a_addr, uint32_t b_addr) {
    const uint64_t da = make_desc(a_addr, 16, 1024, 1);
    const uint64_t db = make_desc(b_addr, 8192, 1024, 1);
#pragma unroll
    for (int ks = 0; ks < 4; ks++) wg_ss_n32_tb(acc, da + ks * 2, db + ks * 128);
}

__device__ __forceinline__ void wo_half(uint32_t sb, const CUtensorMap* tm_wo, int hg) {
    uint32_t old;
    asm volatile("atom.shared.add.u32 %0, [%1], 1;" : "=r"(old) : "r"(sb + OFF_MISC + 8) : "memory");
    if (old == 3) {
        mbar_expect_tx(sb + OFF_BAR + 8 * (B_WO + 2), 32768);
        tma4d(sb + OFF_K, tm_wo, 0, 0, hg * 2, 4, sb + OFF_BAR + 8 * (B_WO + 2));
    }
}

__device__ __forceinline__ void kv_tiles_load(uint32_t sb, const CUtensorMap* tm_k, const CUtensorMap* tm_v, int pb, int hg) {
    const uint32_t br = sb + OFF_BAR + 8 * B_KVIN;
    mbar_expect_tx(br, 67 * 256 + 64 * 256);
    tma2d(sb + OFF_C, tm_k, hg * 128, pb * 64 - 3, br);
    tma2d(sb + OFF_C + 17408, tm_v, hg * 128, pb * 64, br);
}

struct Params {
    const __nv_bfloat16 *aq, *ak, *av, *shift_k, *ssm_D;
    __nv_bfloat16* out;
};

template <int NQ>
__device__ __forceinline__ void conv_phase(float* Dn, uint32_t zaddr, uint64_t hdesc) {
    uint32_t a[2][16];
#pragma unroll
    for (int st = 0; st < 8; st++) {
        uint32_t* aa = a[st & 1];
        if (st >= 2) wg_wait<1>();
#pragma unroll
        for (int u = 0; u < 2; u++) {
            const uint32_t z = zaddr + (st * 2 + u) * 256;
            lds64(z, aa[8 * u + 0], aa[8 * u + 1]);      lds64(z - 32, aa[8 * u + 2], aa[8 * u + 3]);
            lds64(z - 64, aa[8 * u + 4], aa[8 * u + 5]); lds64(z - 96, aa[8 * u + 6], aa[8 * u + 7]);
        }
        wg_fence();
#pragma unroll
        for (int u = 0; u < 2; u++) {
            const int qi = st * 2 + u;
            wg_cv<NQ>(Dn, &aa[8 * u], hdesc - qi * 8);
            wg_cv<NQ>(Dn, &aa[8 * u + 4], hdesc - qi * 8 + 2);
        }
        wg_commit();
    }
    wg_wait<0>();
    fence_regs<NQ / 2>(Dn);
}

__global__ void __launch_bounds__(NTHREADS, 1)
fused_kernel(const __grid_constant__ CUtensorMap tm_x,
             const __grid_constant__ CUtensorMap tm_wq, const __grid_constant__ CUtensorMap tm_wo,
             const __grid_constant__ CUtensorMap tm_wk, const __grid_constant__ CUtensorMap tm_wv,
             const __grid_constant__ CUtensorMap tm_o, const __grid_constant__ CUtensorMap tm_h,
             const __grid_constant__ CUtensorMap tm_k, const __grid_constant__ CUtensorMap tm_v, const Params prm) {
    extern __shared__ __align__(1024) uint8_t smem_raw[];
    const uint32_t sb = (uint32_t)__cvta_generic_to_shared(smem_raw);
    const int warp_id = __shfl_sync(0xffffffffu, threadIdx.x >> 5, 0);
    const int lane = threadIdx.x & 31;
    const int g = lane >> 2, t = lane & 3;
    const int b = blockIdx.x, pb = b >> 2, hg = b & 3;
    auto bar = [&](int i) { return sb + OFF_BAR + 8 * i; };

    if (threadIdx.x == 512) {
        TSTAMP(0);
        prefetch_tm(&tm_x); prefetch_tm(&tm_wq); prefetch_tm(&tm_wk); prefetch_tm(&tm_wv);
        mbar_init(bar(B_WKV), 1);
        for (int j = 0; j < 4; j++) { mbar_init(bar(B_X + j), 1); mbar_init(bar(B_W + j), 1); mbar_init(bar(B_WO + j), 1); mbar_init(bar(B_O + j), 1); }
        sts32(sb + OFF_MISC + 8, 0u);
        for (int j = 0; j < 8; j++) mbar_init(bar(B_KV + j), j == 0 ? 2 : 1);
        mbar_init(bar(B_QEMPTY), 4); mbar_init(bar(B_QEMPTY + 1), 4);
        mbar_init(bar(B_QDONE), 4); mbar_init(bar(B_ATT), 4);
        mbar_init(bar(B_H), 1); mbar_init(bar(B_CV), 1); mbar_init(bar(B_KVT), 64); mbar_init(bar(B_KVIN), 1);
        asm volatile("fence.mbarrier_init.release.cluster;" ::: "memory");
    }

    if (warp_id < 16) {
        const int w = warp_id >> 2, wq = warp_id & 3;
        __syncthreads();
        float acc[16];
#pragma unroll
        for (int i = 0; i < 16; i++) acc[i] = 0.f;
        fence_regs<16>(acc);
        const uint32_t bcol = (w >> 1) * 8192 + (w & 1) * 64;
#pragma unroll 1
        for (int jj = 0; jj < 4; jj++) {
            mbar_wait_w(bar(B_X + jj), 0);
            mbar_wait_w(bar(B_W + jj), 0);
            if (threadIdx.x == 0) TSTAMP(jj == 0 ? 23 : jj == 1 ? 24 : jj == 2 ? 26 : 27);
            wg_fence();
            gemm_chunk(acc, sb + OFF_X + jj * 16384, sb + OFF_V + (jj & 1) * 32768 + bcol);
            gemm_chunk(acc, sb + OFF_X + jj * 16384 + 8192, sb + OFF_V + (jj & 1) * 32768 + 16384 + bcol);
            wg_commit();
            wg_wait<0>();
            if (jj < 2 && (threadIdx.x & 127) == 0) mbar_arrive(bar(B_QEMPTY + jj));
        }
        fence_regs<16>(acc);
        if ((threadIdx.x & 127) == 0) { mbar_arrive(bar(B_QDONE)); if (w == 0) TSTAMP(1); }
        uint32_t qa[2][4];
        float qn[2];
        {
            const float c = 0.25f * 1.4426950408889634f;
#pragma unroll
            for (int hh = 0; hh < 2; hh++) {
                float n0 = 0.f, n1 = 0.f;
#pragma unroll
                for (int i = 0; i < 4; i++) {
                    const uint32_t qb = pack_bf16(acc[8 * hh + 2 * i], acc[8 * hh + 2 * i + 1]);
                    const uint32_t qs = pack_bf16(bf_lo(qb) * c, bf_hi(qb) * c);
                    qa[hh][i] = qs;
                    const float e = bf_lo(qs) * bf_lo(qs) + bf_hi(qs) * bf_hi(qs);
                    if (i & 1) n1 += e; else n0 += e;
                }
                n0 += __shfl_xor_sync(0xffffffffu, n0, 1); n0 += __shfl_xor_sync(0xffffffffu, n0, 2);
                n1 += __shfl_xor_sync(0xffffffffu, n1, 1); n1 += __shfl_xor_sync(0xffffffffu, n1, 2);
                qn[hh] = fmaxf(n0, n1);
            }
        }
        uint32_t mlo = 0x03FF03FFu; asm volatile("" : "+r"(mlo));
        const uint64_t kdesc0 = make_desc(sb + OFF_K, 128, 256, 0);
        const uint64_t vdesc0 = make_desc(sb + OFF_VONES - 256, 128, 256, 0);
        constexpr uint64_t VSTEP = ((uint64_t)16 << 32) - 16;
        mbar_wait_w(bar(B_KV + 0), 0);
        if ((threadIdx.x & 127) == 0 && w == 0) TSTAMP(2);
        const float kmax2 = ldsf(sb + OFF_MISC);
        const bool fast0 = __all_sync(0xffffffffu, named_bar_and(1 + w, 128, qn[0] * kmax2 <= 193.0f));
        const bool fast1 = __all_sync(0xffffffffu, named_bar_and(1 + w, 128, qn[1] * kmax2 <= 193.0f));
        uint32_t a[4] = {qa[0][0], qa[0][1], qa[0][2], qa[0][3]};
#pragma unroll 1
        for (int hh = 0; hh < 2; hh++) {
            const bool fast = hh ? fast1 : fast0;
            float S[32], O[12];
#pragma unroll
            for (int i = 0; i < 12; i++) O[i] = 0.f;
#pragma unroll
            for (int i = 0; i < 32; i++) S[i] = 0.f;
            fence_regs<12>(O); fence_regs<32>(S);
            wg_fence();
            wg_qk_n64(S, a, kdesc0);
            wg_commit();
            wg_wait<0>();
            uint64_t kd = kdesc0 + 128, vd = vdesc0;
            if (fast) {
                uint32_t P[16];
#pragma unroll 1
                for (int c = 0; c < 8; c++) {
                    if (c < 7) mbar_wait_w(bar(B_KV + c + 1), 0);
#pragma unroll 1
                    for (int j = 0; j < 4; j++) {
                        fence_regs<32>(S);
                        softmax_fast(S, P, mlo);
                        fence_regs<32>(S);
                        wg_fence();
                        wg_qk_n64(S, a, kd);
#pragma unroll
                        for (int i = 0; i < 4; i++) wg_pv_n24(O, &P[4 * i], vd + i * VSTEP);
                        wg_commit();
                        wg_wait<0>();
                        kd += 128; vd += 4 * VSTEP;
                    }
                    if (hh == 1 && c == 3 && (threadIdx.x & 127) == 0) wo_half(sb, &tm_wo, hg);
                }
            } else {
                uint32_t P[16];
                float m0 = -INFINITY, m1 = -INFINITY;
#pragma unroll 1
                for (int c = 0; c < 8; c++) {
                    if (c < 7) mbar_wait_w(bar(B_KV + c + 1), 0);
#pragma unroll 1
                    for (int j = 0; j < 4; j++) {
                        fence_regs<32>(S); fence_regs<12>(O);
                        float x0 = m0, x1 = m1;
#pragma unroll
                        for (int i = 0; i < 8; i++) {
                            x0 = fmaxf(x0, fmaxf(S[4 * i], S[4 * i + 1]));
                            x1 = fmaxf(x1, fmaxf(S[4 * i + 2], S[4 * i + 3]));
                        }
                        x0 = fmaxf(x0, __shfl_xor_sync(0xffffffffu, x0, 1)); x0 = fmaxf(x0, __shfl_xor_sync(0xffffffffu, x0, 2));
                        x1 = fmaxf(x1, __shfl_xor_sync(0xffffffffu, x1, 1)); x1 = fmaxf(x1, __shfl_xor_sync(0xffffffffu, x1, 2));
                        const float r0 = ex2f(m0 - x0), r1 = ex2f(m1 - x1);
                        m0 = x0; m1 = x1;
#pragma unroll
                        for (int i = 0; i < 3; i++) { O[4 * i] *= r0; O[4 * i + 1] *= r0; O[4 * i + 2] *= r1; O[4 * i + 3] *= r1; }
#pragma unroll
                        for (int i = 0; i < 8; i++) {
                            P[2 * i] = pack_f16(ex2f(S[4 * i] - m0), ex2f(S[4 * i + 1] - m0));
                            P[2 * i + 1] = pack_f16(ex2f(S[4 * i + 2] - m1), ex2f(S[4 * i + 3] - m1));
                        }
                        fence_regs<32>(S); fence_regs<12>(O);
                        wg_fence();
                        wg_qk_n64(S, a, kd);
#pragma unroll
                        for (int i = 0; i < 4; i++) wg_pv_n24(O, &P[4 * i], vd + i * VSTEP);
                        wg_commit();
                        wg_wait<0>();
                        kd += 128; vd += 4 * VSTEP;
                    }
                    if (hh == 1 && c == 3 && (threadIdx.x & 127) == 0) wo_half(sb, &tm_wo, hg);
                }
            }
            fence_regs<12>(O);
            const float vscale = ldsf(sb + OFF_MISC + 4);
            const float i0 = __fdividef(vscale, O[4]), i1 = __fdividef(vscale, O[6]);
            const int row = pb * 64 + wq * 16 + g;
            uint32_t* o0 = (uint32_t*)(g_o + (size_t)row * 512 + (hg * 8 + 2 * w + hh) * 16) + t;
            uint32_t* o1 = o0 + 8 * 256;
            o0[0] = pack_bf16(O[0] * i0, O[1] * i0);
            o0[4] = pack_bf16(O[8] * i0, O[9] * i0);
            o1[0] = pack_bf16(O[2] * i1, O[3] * i1);
            o1[4] = pack_bf16(O[10] * i1, O[11] * i1);
            if ((threadIdx.x & 127) == 0 && w == 0) { TSTAMP(3 + hh); CSTAMP(40 + hh); }
#pragma unroll
            for (int i = 0; i < 4; i++) a[i] = qa[1][i];
        }
        named_bar(1 + w, 128);
        if ((threadIdx.x & 127) == 0) {
            red_release_add(&g_o_count[pb], 1);
            mbar_arrive(bar(B_ATT));
        }
        if (threadIdx.x == 0) {
            TSTAMP(30);
            mbar_wait(bar(B_ATT), 0);
            TSTAMP(31);
            poll_counter(&g_o_count[pb], 16);
            TSTAMP(18);
            fence_async_global();
            for (int jj = 0; jj < 4; jj++) {
                mbar_expect_tx(bar(B_O + jj), 16384);
                tma3d(sb + OFF_V + jj * 16384, &tm_o, 0, pb * 64, 2 * jj, bar(B_O + jj));
            }
            __threadfence();
            if (atomicAdd(&g_done, 1) == 2 * NCTA - 1) {
                for (int i = 0; i < NCTA; i++) g_stats[i] = 0ull;
                for (int i = 0; i < 4; i++) { g_kvt_count[i] = 0; g_z_count[i] = 0; }
                for (int i = 0; i < 32; i++) g_o_count[i] = 0;
                g_done = 0;
                __threadfence();
            }
        }
        __syncwarp();
#pragma unroll
        for (int i = 0; i < 16; i++) acc[i] = 0.f;
        fence_regs<16>(acc);
#pragma unroll 1
        for (int jj = 0; jj < 4; jj++) {
            mbar_wait_w(bar(B_WO + jj), 0);
            mbar_wait_w(bar(B_O + jj), 0);
            if (threadIdx.x == 0 && (jj == 0 || jj == 3)) TSTAMP(jj == 0 ? 32 : 33);
            const uint32_t wb = sb + (jj < 2 ? OFF_X + jj * 32768 : (jj == 2 ? OFF_K : OFF_C)) + bcol;
            wg_fence();
            gemm_chunk(acc, sb + OFF_V + jj * 16384, wb);
            gemm_chunk(acc, sb + OFF_V + jj * 16384 + 8192, wb + 16384);
            wg_commit();
        }
        wg_wait<0>();
        fence_regs<16>(acc);
        {
            const int row = pb * 64 + wq * 16 + g;
            uint32_t* d0 = (uint32_t*)(prm.out + (size_t)row * 1024 + 512 + hg * 128 + w * 32) + t;
            uint32_t* d1 = d0 + 8 * 512;
#pragma unroll
            for (int i = 0; i < 4; i++) {
                d0[4 * i] = pack_bf16(acc[4 * i], acc[4 * i + 1]);
                d1[4 * i] = pack_bf16(acc[4 * i + 2], acc[4 * i + 3]);
            }
        }
        if ((threadIdx.x & 127) == 0 && w == 0) TSTAMP(5);
    } else {
        const int wa = warp_id - 16, tau = threadIdx.x - 512;
        __syncthreads();
        const bool kv_cta = (hg == (pb & 3));
        if (tau == 0) {
            if (kv_cta) {
                mbar_expect_tx(bar(B_WKV), 32768);
                tma3d(sb + OFF_C, &tm_wk, 0, 0, 0, bar(B_WKV));
                tma3d(sb + OFF_C + 16384, &tm_wv, 0, 0, 0, bar(B_WKV));
            }
            for (int jj = 0; jj < 4; jj++) {
                mbar_expect_tx(bar(B_X + jj), 16384);
                tma3d(sb + OFF_X + jj * 16384, &tm_x, 0, pb * 64, 2 * jj, bar(B_X + jj));
                if (!kv_cta && jj < 2) {
                    mbar_expect_tx(bar(B_W + jj), 32768);
                    tma4d(sb + OFF_V + jj * 32768, &tm_wq, 0, 0, hg * 2, 2 * jj, bar(B_W + jj));
                }
            }
            if (kv_cta) {
                for (int jj = 0; jj < 2; jj++) {
                    mbar_expect_tx(bar(B_W + jj), 32768);
                    tma4d(sb + OFF_V + jj * 32768, &tm_wq, 0, 0, hg * 2, 2 * jj, bar(B_W + jj));
                }
            } else {
                kv_tiles_load(sb, &tm_k, &tm_v, pb, hg);
            }
            TSTAMP(25);
        }
        __syncwarp();
        if (kv_cta) {
            float acc[16];
#pragma unroll
            for (int i = 0; i < 16; i++) acc[i] = 0.f;
            fence_regs<16>(acc);
            mbar_wait_w(bar(B_WKV), 0);
            if (tau == 0) TSTAMP(20);
#pragma unroll
            for (int jj = 0; jj < 4; jj++) {
                mbar_wait_w(bar(B_X + jj), 0);
                wg_fence();
#pragma unroll
                for (int j = 2 * jj; j < 2 * jj + 2; j++) {
                    const uint64_t da = make_desc(sb + OFF_X + j * 8192, 16, 1024, 1);
                    const uint64_t db = make_desc(sb + OFF_C + j * 2048, 16384, 256, 3);
#pragma unroll
                    for (int ks = 0; ks < 4; ks++) wg_ss_n32_tb(acc, da + ks * 2, db + ks * 32);
                }
                wg_commit();
            }
            wg_wait<0>();
            fence_regs<16>(acc);
            if (tau == 0) TSTAMP(22);
            {
                uint32_t kk[4], vv[4];
#pragma unroll
                for (int i = 0; i < 4; i++) { kk[i] = pack_bf16(acc[2 * i], acc[2 * i + 1]); vv[i] = pack_bf16(acc[8 + 2 * i], acc[8 + 2 * i + 1]); }
                const int s = 4 * pb + wa;
                uint32_t* kp = (uint32_t*)(g_kimg + s * 512 + g * 16 + 4 * t);
                kp[0] = kk[0]; kp[64] = kk[1]; kp[32] = kk[2]; kp[96] = kk[3];
                uint32_t* vlo = (uint32_t*)(g_vimg + (127 - s) * 256 + g * 16 + 4 * t);
                uint32_t* vhi = (uint32_t*)(g_vimg + 32768 + 256 + s * 256 + g * 16 + 4 * t);
                vlo[0] = pack_f16(bf_lo(vv[0]), bf_hi(vv[0])); vlo[32] = pack_f16(bf_lo(vv[1]), bf_hi(vv[1]));
                vhi[0] = pack_f16(bf_lo(vv[2]), bf_hi(vv[2])); vhi[32] = pack_f16(bf_lo(vv[3]), bf_hi(vv[3]));
                uint32_t* vr = (uint32_t*)(g_vraw + (size_t)(16 * s + g) * 16) + t;
                vr[0] = vv[0]; vr[64] = vv[1]; vr[4] = vv[2]; vr[68] = vv[3];
                float n0 = bf_lo(kk[0]) * bf_lo(kk[0]) + bf_hi(kk[0]) * bf_hi(kk[0]) + bf_lo(kk[2]) * bf_lo(kk[2]) + bf_hi(kk[2]) * bf_hi(kk[2]);
                float n1 = bf_lo(kk[1]) * bf_lo(kk[1]) + bf_hi(kk[1]) * bf_hi(kk[1]) + bf_lo(kk[3]) * bf_lo(kk[3]) + bf_hi(kk[3]) * bf_hi(kk[3]);
                n0 += __shfl_xor_sync(0xffffffffu, n0, 1); n0 += __shfl_xor_sync(0xffffffffu, n0, 2);
                n1 += __shfl_xor_sync(0xffffffffu, n1, 1); n1 += __shfl_xor_sync(0xffffffffu, n1, 2);
                float km = fmaxf(n0, n1), vm = 0.f;
#pragma unroll
                for (int i = 0; i < 4; i++) vm = fmaxf(vm, fmaxf(fabsf(bf_lo(vv[i])), fabsf(bf_hi(vv[i]))));
#pragma unroll
                for (int o = 4; o < 32; o <<= 1) km = fmaxf(km, __shfl_xor_sync(0xffffffffu, km, o));
#pragma unroll
                for (int o = 1; o < 32; o <<= 1) vm = fmaxf(vm, __shfl_xor_sync(0xffffffffu, vm, o));
                __syncwarp();
                if (lane == 0) {
                    const unsigned long long rec = ((unsigned long long)(__float_as_uint(vm) | 0x80000000u) << 32) | __float_as_uint(km);
                    asm volatile("st.release.gpu.global.u64 [%0], %1;" ::"l"(&g_stats[s]), "l"(rec) : "memory");
                    if (wa == 0) TSTAMP(8);
                }
            }
            if (tau == 32) kv_tiles_load(sb, &tm_k, &tm_v, pb, hg);
            __syncwarp();
        }
        const int c0 = 4 * b;
        if (wa == 0) {
            if (lane == 0) {
                for (int jj = 2; jj < 4; jj++) {
                    mbar_wait(bar(B_QEMPTY + jj - 2), 0);
                    mbar_expect_tx(bar(B_W + jj), 32768);
                    tma4d(sb + OFF_V + (jj - 2) * 32768, &tm_wq, 0, 0, hg * 2, 2 * jj, bar(B_W + jj));
                }
            }
            __syncwarp();
            float km = 0.f, vm = 0.f;
            {
                unsigned long long rec[4];
                uint32_t spins = 0;
                bool ok;
                do {
                    ok = true;
#pragma unroll
                    for (int i = 0; i < 4; i++) {
                        asm volatile("ld.relaxed.gpu.global.u64 %0, [%1];" : "=l"(rec[i]) : "l"(&g_stats[lane + 32 * i]) : "memory");
                        ok = ok && (rec[i] >> 63);
                    }
                    if (++spins > (1u << 22)) __trap();
                } while (!__all_sync(0xffffffffu, ok));
                asm volatile("fence.acq_rel.gpu;" ::: "memory");
#pragma unroll
                for (int i = 0; i < 4; i++) { km = fmaxf(km, __uint_as_float((uint32_t)rec[i])); vm = fmaxf(vm, __uint_as_float((uint32_t)(rec[i] >> 32) & 0x7FFFFFFFu)); }
            }
            if (lane == 0) {
                TSTAMP(16);
                fence_async_global();
                for (int c = 0; c < 8; c++) {
                    mbar_expect_tx_noarrive(bar(B_KV + c), 8192);
                    bulk_g2s(sb + OFF_K + c * 8192, g_kimg + c * 8192, 8192, bar(B_KV + c));
                }
                TSTAMP(28);
            }
#pragma unroll
            for (int o = 1; o < 32; o <<= 1) { km = fmaxf(km, __shfl_xor_sync(0xffffffffu, km, o)); vm = fmaxf(vm, __shfl_xor_sync(0xffffffffu, vm, o)); }
            const bool vdirect = (vm <= 32768.f && vm >= 9.765625e-4f) || vm == 0.f;
            float vs = 1.f;
            if (!vdirect && vm < INFINITY) {
                int e = (int)((__float_as_uint(vm) >> 23) & 0xFF) - 127;
                e = max(-100, min(100, e));
                vs = __uint_as_float((uint32_t)(127 + e - 13) << 23);
            }
            if (lane == 0) {
                asm volatile("st.shared.f32 [%0], %1;" ::"r"(sb + OFF_MISC), "f"(km) : "memory");
                asm volatile("st.shared.f32 [%0], %1;" ::"r"(sb + OFF_MISC + 4), "f"(vs) : "memory");
                mbar_wait(bar(B_QDONE), 0);
                TSTAMP(17);
                for (int c = 0; c < 8; c++) {
                    if (vdirect) {
                        mbar_expect_tx(bar(B_KV + c), 8192);
                        bulk_g2s(sb + OFF_V + (112 - 16 * c) * 256, g_vimg + (112 - 16 * c) * 256, 4096, bar(B_KV + c));
                        bulk_g2s(sb + OFF_VONES + 256 + c * 4096, g_vimg + 32768 + 256 + c * 4096, 4096, bar(B_KV + c));
                    }
                }
            }
            __syncwarp();
            sts32(sb + OFF_VONES + lane * 8, 0x3C003C00u);
            sts32(sb + OFF_VONES + lane * 8 + 4, 0x3C003C00u);
            if (!vdirect) {
                const float inv = 1.f / vs;
                for (int idx = lane; idx < S_LEN * 8; idx += 32) {
                    const int key = idx >> 3, dp = idx & 7;
                    const uint32_t v = __ldcg((const uint32_t*)g_vraw + idx);
                    const uint32_t h = pack_f16(bf_lo(v) * inv, bf_hi(v) * inv);
                    const int st = key >> 4, hf = (key >> 3) & 1;
                    const uint32_t base = (dp < 4) ? (OFF_V + (127 - st) * 256) : (OFF_VONES + 256 + st * 256);
                    sts32(sb + base + hf * 128 + (key & 7) * 16 + (dp & 3) * 4, h);
                }
            }
            fence_async_smem();
            __syncwarp();
            if (lane == 0) {
                mbar_arrive(bar(B_KV + 0));
                if (!vdirect) for (int c = 0; c < 8; c++) mbar_arrive(bar(B_KV + c));
                prefetch_tm(&tm_wo); prefetch_tm(&tm_o);
                for (int jj = 0; jj < 2; jj++) {
                    mbar_expect_tx(bar(B_WO + jj), 32768);
                    tma4d(sb + OFF_X + jj * 32768, &tm_wo, 0, 0, hg * 2, 2 * jj, bar(B_WO + jj));
                }
            }
            __syncwarp();
        } else if (wa >= 2) {
            const int kch0 = hg * 128 + lane * 4;
            uint32_t wA[4], wB[4];
            {
                const uint4 s0 = __ldg((const uint4*)(prm.shift_k + kch0 * 4));
                const uint4 s1 = __ldg((const uint4*)(prm.shift_k + kch0 * 4) + 1);
                wA[0] = __byte_perm(s0.x, s0.z, 0x5410); wA[1] = __byte_perm(s0.x, s0.z, 0x7632);
                wA[2] = __byte_perm(s0.y, s0.w, 0x5410); wA[3] = __byte_perm(s0.y, s0.w, 0x7632);
                wB[0] = __byte_perm(s1.x, s1.z, 0x5410); wB[1] = __byte_perm(s1.x, s1.z, 0x7632);
                wB[2] = __byte_perm(s1.y, s1.w, 0x5410); wB[3] = __byte_perm(s1.y, s1.w, 0x7632);
            }
            mbar_wait_w(bar(B_KVIN), 0);
            const uint32_t kb = sb + OFF_C + (wa - 2) * 32 * 256 + lane * 8, vb = kb + 17408;
            uint32_t k0a, k0b, k1a, k1b, k2a, k2b;
            lds64(kb, k0a, k0b); lds64(kb + 256, k1a, k1b); lds64(kb + 512, k2a, k2b);
#pragma unroll
            for (int o8 = 0; o8 < 4; o8++) {
                uint32_t xa[8], xb[8];
#pragma unroll
                for (int i = 0; i < 8; i++) {
                    uint32_t k3a, k3b, va, vb2;
                    lds64(kb + (o8 * 8 + i + 3) * 256, k3a, k3b);
                    lds64(vb + (o8 * 8 + i) * 256, va, vb2);
                    xa[i] = bmul2(badd2(badd2(badd2(bmul2(k0a, wA[3]), bmul2(k1a, wA[2])), bmul2(k2a, wA[1])), bmul2(k3a, wA[0])), va);
                    xb[i] = bmul2(badd2(badd2(badd2(bmul2(k0b, wB[3]), bmul2(k1b, wB[2])), bmul2(k2b, wB[1])), bmul2(k3b, wB[0])), vb2);
                    k0a = k1a; k0b = k1b; k1a = k2a; k1b = k2b; k2a = k3a; k2b = k3b;
                }
                uint4* dst = (uint4*)(g_kvT + (size_t)kch0 * S_LEN + pb * 64 + (wa - 2) * 32 + o8 * 8);
                dst[0] = make_uint4(__byte_perm(xa[0], xa[1], 0x5410), __byte_perm(xa[2], xa[3], 0x5410), __byte_perm(xa[4], xa[5], 0x5410), __byte_perm(xa[6], xa[7], 0x5410));
                dst[S_LEN / 8] = make_uint4(__byte_perm(xa[0], xa[1], 0x7632), __byte_perm(xa[2], xa[3], 0x7632), __byte_perm(xa[4], xa[5], 0x7632), __byte_perm(xa[6], xa[7], 0x7632));
                dst[2 * (S_LEN / 8)] = make_uint4(__byte_perm(xb[0], xb[1], 0x5410), __byte_perm(xb[2], xb[3], 0x5410), __byte_perm(xb[4], xb[5], 0x5410), __byte_perm(xb[6], xb[7], 0x5410));
                dst[3 * (S_LEN / 8)] = make_uint4(__byte_perm(xb[0], xb[1], 0x7632), __byte_perm(xb[2], xb[3], 0x7632), __byte_perm(xb[4], xb[5], 0x7632), __byte_perm(xb[6], xb[7], 0x7632));
            }
            mbar_arrive(bar(B_KVT));
            mbar_wait_w(bar(B_KVT), 0);
            sts128(sb + C_H + (tau - 64) * 32, 0u, 0u, 0u, 0u);
            sts128(sb + C_H + (tau - 64) * 32 + 16, 0u, 0u, 0u, 0u);
            fence_async_smem();
        } else {
            if (lane == 0) {
                mbar_wait(bar(B_KVT), 0);
                mbar_expect_tx(bar(B_H), 4096);
                tma2d(sb + C_H + 2048, &tm_h, 0, c0 * 64, bar(B_H));
                red_release_add(&g_kvt_count[hg], 1);
                TSTAMP(34);
                poll_counter(&g_kvt_count[b >> 5], 32);
                fence_async_global();
                mbar_expect_tx(bar(B_CV), 16384);
                bulk_g2s(sb + C_KVC, g_kvT + (size_t)c0 * S_LEN, 16384, bar(B_CV));
            }
            __syncwarp();
        }
        named_bar(5, 128);
        mbar_wait_w(bar(B_CV), 0);
        if (tau == 0) TSTAMP(9);
        const int NCH = 4;
#pragma unroll 1
        for (int ch = 0; ch < NCH; ch++) {
            {
                const uint32_t src = sb + C_KVC + ch * 4096 + tau * 32;
                const uint4 u0 = lds128(src), u1 = lds128(src + 16);
                const uint32_t prev = tau > 0 ? lds32(src - 4) : 0u;
                const uint32_t zd = sb + C_Z + (32 + tau * 16) * 4;
                sts128(zd,      __byte_perm(u0.x, prev, 0x7610), __byte_perm(u0.x, u0.x, 0x1032), __byte_perm(u0.y, u0.x, 0x7610), __byte_perm(u0.y, u0.y, 0x1032));
                sts128(zd + 16, __byte_perm(u0.z, u0.y, 0x7610), __byte_perm(u0.z, u0.z, 0x1032), __byte_perm(u0.w, u0.z, 0x7610), __byte_perm(u0.w, u0.w, 0x1032));
                sts128(zd + 32, __byte_perm(u1.x, u0.w, 0x7610), __byte_perm(u1.x, u1.x, 0x1032), __byte_perm(u1.y, u1.x, 0x7610), __byte_perm(u1.y, u1.y, 0x1032));
                sts128(zd + 48, __byte_perm(u1.z, u1.y, 0x7610), __byte_perm(u1.z, u1.z, 0x1032), __byte_perm(u1.w, u1.z, 0x7610), __byte_perm(u1.w, u1.w, 0x1032));
                if (tau < 32) sts32(sb + C_Z + tau * 4, 0u);
            }
            named_bar(5, 128);
            mbar_wait_w(bar(B_H), ch & 1);
            float D[32];
#pragma unroll
            for (int i = 0; i < 32; i++) D[i] = 0.f;
            fence_regs<32>(D);
            const uint32_t z0 = sb + C_Z + (32 + 32 * (wa >> 1) + 16 * (wa & 1) + 2 * g - 2 * t) * 4;
            const uint64_t hd = make_desc(sb + C_H + 2048, 16, 512, 2);
            conv_phase<64>(D, z0, hd);
            float E[16];
#pragma unroll
            for (int i = 0; i < 16; i++) asm volatile("mov.f32 %0, %1;" : "=f"(E[i]) : "f"(D[16 + i]));
            conv_phase<32>(E, z0 + 4096, hd);
            if (tau == 0 && ch < 3) {
                mbar_expect_tx(bar(B_H), 4096);
                tma2d(sb + C_H + 2048, &tm_h, 0, (c0 + ch + 1) * 64, bar(B_H));
            }
            const int bb0 = 16 * (wa & 1) + 2 * g;
            const int xsw = (g & 3) << 3;
            {
                const uint32_t xb = sb + C_Z + (wa >> 1) * 4096;
#pragma unroll
                for (int jn = 0; jn < 4; jn++) {
#pragma unroll
                    for (int r = 0; r < 2; r++) {
                        const float v0 = (wa < 2) ? E[4 * jn + 2 * r] : D[4 * jn + 2 * r];
                        const float v1 = (wa < 2) ? E[4 * jn + 2 * r + 1] : D[4 * jn + 2 * r + 1];
                        sts64f(xb + ((bb0 + r) * 32 + ((8 * jn + 2 * t) ^ xsw)) * 4, v0, v1);
                    }
                }
            }
            named_bar(5, 128);
            {
                const float dsc = __bfloat162float(prm.ssm_D[c0 + ch]);
                const uint32_t xb = sb + C_Z + ((wa >> 1) ^ 1) * 4096;
#pragma unroll
                for (int jn = 0; jn < 4; jn++) {
#pragma unroll
                    for (int e = 0; e < 2; e++) {
                        const int n = 8 * jn + 2 * t + e;
                        float y0, y1; int m, rn;
                        if (wa < 2) { y0 = D[4 * jn + e]; y1 = D[4 * jn + 2 + e]; m = n; rn = n - 1; }
                        else {
                            const bool last = (jn == 3 && e == 1) && (t == 3);
                            y0 = last ? D[13] : E[4 * jn + e]; y1 = last ? D[15] : E[4 * jn + 2 + e];
                            m = last ? 32 : 33 + n; rn = m - 32;
                        }
                        if (rn >= 0) {
                            y0 += ldsf(xb + (bb0 * 32 + (rn ^ xsw)) * 4);
                            y1 += ldsf(xb + ((bb0 + 1) * 32 + (rn ^ xsw)) * 4);
                        }
                        const uint32_t addr = sb + C_KVC + ch * 4096 + (32 * m + bb0) * 2;
                        const uint32_t kv = lds32(addr);
                        const uint32_t yb = pack_bf16(y0, y1);
                        const uint32_t kd = pack_bf16(bf_lo(kv) * dsc, bf_hi(kv) * dsc);
                        sts32(addr, badd2(yb, kd));
                    }
                }
                fence_async_smem();
            }
            named_bar(5, 128);
            if (tau == 0) {
                bulk_s2g(g_zT + (size_t)(c0 + ch) * S_LEN, sb + C_KVC + ch * 4096, 4096);
                bulk_commit();
                TSTAMP(10 + ch);
            }
        }
        {
            const int cg = tau & 15, pr = tau >> 4;
            const int p0 = pb * 64 + pr * 8, ch0 = hg * 128 + cg * 8;
            uint4 qr[8];
#pragma unroll
            for (int i = 0; i < 8; i++) qr[i] = __ldg((const uint4*)(prm.aq + (size_t)(p0 + i) * 512 + ch0));
            if (tau == 0) {
                bulk_wait_all();
                mbar_expect_tx(bar(B_WO + 3), 32768);
                tma4d(sb + OFF_C, &tm_wo, 0, 0, hg * 2, 6, bar(B_WO + 3));
                fence_async_global();
                red_release_add(&g_z_count[b >> 5], 1);
                poll_counter(&g_z_count[hg], 32);
                __threadfence();
                if (atomicAdd(&g_done, 1) == 2 * NCTA - 1) {
                    for (int i = 0; i < NCTA; i++) g_stats[i] = 0ull;
                    for (int i = 0; i < 4; i++) { g_kvt_count[i] = 0; g_z_count[i] = 0; }
                    for (int i = 0; i < 32; i++) g_o_count[i] = 0;
                    g_done = 0;
                    __threadfence();
                }
            }
            named_bar(5, 128);
            uint4 zz[8];
#pragma unroll
            for (int c = 0; c < 8; c++) zz[c] = __ldcg((const uint4*)(g_zT + (size_t)(ch0 + c) * S_LEN + p0));
#pragma unroll
            for (int i = 0; i < 8; i++) {
                uint32_t r[4];
#pragma unroll
                for (int k = 0; k < 4; k++) {
                    const uint32_t pr2 = __byte_perm((&zz[2 * k].x)[i >> 1], (&zz[2 * k + 1].x)[i >> 1], (i & 1) ? 0x7632 : 0x5410);
                    r[k] = bmul2((&qr[i].x)[k], pr2);
                }
                *(uint4*)(prm.out + (size_t)(p0 + i) * 1024 + ch0) = make_uint4(r[0], r[1], r[2], r[3]);
            }
        }
        if (tau == 0) TSTAMP(14);
    }
}

typedef CUresult (*EncodeFn)(CUtensorMap*, CUtensorMapDataType, cuuint32_t, void*, const cuuint64_t*, const cuuint64_t*,
                             const cuuint32_t*, const cuuint32_t*, CUtensorMapInterleave, CUtensorMapSwizzle,
                             CUtensorMapL2promotion, CUtensorMapFloatOOBfill);

void make_map(EncodeFn fn, CUtensorMap* tm, const void* ptr, int rank, const cuuint64_t* dims, const cuuint64_t* strides, const cuuint32_t* box, CUtensorMapSwizzle swz) {
    cuuint32_t es[4] = {1, 1, 1, 1};
    fn(tm, CU_TENSOR_MAP_DATA_TYPE_BFLOAT16, rank, const_cast<void*>(ptr), dims, strides, box, es, CU_TENSOR_MAP_INTERLEAVE_NONE, swz,
       CU_TENSOR_MAP_L2_PROMOTION_L2_128B, CU_TENSOR_MAP_FLOAT_OOB_FILL_NONE);
}

}

extern "C" void kernel_launch(void* const* d_in, const int* in_sizes, int n_in, void* d_out, int out_size) {
    (void)in_sizes; (void)n_in; (void)out_size;
    static EncodeFn encode = nullptr;
    static void* o_ptr = nullptr;
    if (!encode) {
        cudaDriverEntryPointQueryResult qres;
        void* fn = nullptr;
        cudaGetDriverEntryPoint("cuTensorMapEncodeTiled", &fn, cudaEnableDefault, &qres);
        encode = (EncodeFn)fn;
        cudaGetSymbolAddress(&o_ptr, g_o);
        cudaFuncSetAttribute(fused_kernel, cudaFuncAttributeMaxDynamicSharedMemorySize, SMEM_TOTAL);
    }
    CUtensorMap tm_x, tm_wq, tm_wo, tm_wk, tm_wv, tm_o, tm_h, tm_k, tm_v;
    {
        const cuuint64_t dims[3] = {64, 2048, 8}, str[2] = {1024, 128};
        const cuuint32_t b64[3] = {64, 64, 2};
        make_map(encode, &tm_x, d_in[6], 3, dims, str, b64, CU_TENSOR_MAP_SWIZZLE_128B);
        make_map(encode, &tm_o, o_ptr, 3, dims, str, b64, CU_TENSOR_MAP_SWIZZLE_128B);
    }
    {
        const cuuint64_t dims[4] = {64, 64, 8, 8}, str[3] = {1024, 128, 65536};
        const cuuint32_t box[4] = {64, 64, 2, 2};
        make_map(encode, &tm_wq, d_in[7], 4, dims, str, box, CU_TENSOR_MAP_SWIZZLE_128B);
        make_map(encode, &tm_wo, d_in[10], 4, dims, str, box, CU_TENSOR_MAP_SWIZZLE_128B);
    }
    {
        const cuuint64_t dims[3] = {16, 256, 2}, str[2] = {32, 8192};
        const cuuint32_t box[3] = {16, 256, 2};
        make_map(encode, &tm_wk, d_in[8], 3, dims, str, box, CU_TENSOR_MAP_SWIZZLE_32B);
        make_map(encode, &tm_wv, d_in[9], 3, dims, str, box, CU_TENSOR_MAP_SWIZZLE_32B);
    }
    {
        const cuuint64_t dims[2] = {32, 512 * 64}, str[1] = {64};
        const cuuint32_t box[2] = {32, 64};
        make_map(encode, &tm_h, d_in[4], 2, dims, str, box, CU_TENSOR_MAP_SWIZZLE_64B);
    }
    {
        const cuuint64_t dims[2] = {512, 2048}, str[1] = {1024};
        const cuuint32_t bk[2] = {128, 67}, bv[2] = {128, 64};
        make_map(encode, &tm_k, d_in[1], 2, dims, str, bk, CU_TENSOR_MAP_SWIZZLE_NONE);
        make_map(encode, &tm_v, d_in[2], 2, dims, str, bv, CU_TENSOR_MAP_SWIZZLE_NONE);
    }
    Params prm;
    prm.aq = (const __nv_bfloat16*)d_in[0];
    prm.ak = (const __nv_bfloat16*)d_in[1];
    prm.av = (const __nv_bfloat16*)d_in[2];
    prm.shift_k = (const __nv_bfloat16*)d_in[3];
    prm.ssm_D = (const __nv_bfloat16*)d_in[5];
    prm.out = (__nv_bfloat16*)d_out;
    fused_kernel<<<NCTA, NTHREADS, SMEM_TOTAL>>>(tm_x, tm_wq, tm_wo, tm_wk, tm_wv, tm_o, tm_h, tm_k, tm_v, prm);
}
```

```cpp
#include <cuda_runtime.h>
#include <cuda_bf16.h>
#include <cuda_fp16.h>
#include <cuda.h>
#include <stdint.h>

#define LATE_WQ
#define TAIL_CH 1
#define KVIN_AFTER 3
namespace {

constexpr int S_LEN = 2048;
constexpr int NCTA = 128;
constexpr int NTHREADS = 640;

constexpr uint32_t OFF_K = 0;
constexpr uint32_t OFF_V = 65536;
constexpr uint32_t OFF_VONES = OFF_V + 32768;
constexpr uint32_t OFF_X = 132096;
constexpr uint32_t OFF_C = 197632;
constexpr uint32_t C_KVC = OFF_C;
constexpr uint32_t S_KT = OFF_K;
constexpr uint32_t S_VT = OFF_K + 17408;
constexpr uint32_t S_H = OFF_K + 36864;
constexpr uint32_t S_Z = OFF_X;
constexpr uint32_t OFF_BAR = 231936;
constexpr uint32_t SMEM_TOTAL = 232448;

enum { B_WKV = 0, B_X = 1, B_QEMPTY = 5, B_QDONE = 7, B_KV = 8, B_WO = 16, B_O = 20, B_ATT = 24, B_H = 25, B_CV = 26, B_W = 27, B_KVT = 31, B_KVIN = 32, B_CONV = 33, B_COUNT = 34 };
constexpr uint32_t OFF_MISC = OFF_BAR + 8 * B_COUNT;

__device__ __align__(1024) uint8_t g_kimg[65536];
__device__ __align__(1024) uint8_t g_vimg[65792];
__device__ __align__(1024) __nv_bfloat16 g_vraw[S_LEN * 16];
__device__ __align__(1024) __nv_bfloat16 g_o[S_LEN * 512];
__device__ __align__(1024) __nv_bfloat16 g_kvT[512 * S_LEN];
__device__ __align__(1024) __nv_bfloat16 g_zT[512 * S_LEN];
__device__ unsigned long long g_stats[NCTA];
__device__ unsigned int g_kvt_count[4];
__device__ unsigned int g_z_count[4];
__device__ unsigned int g_o_count[32];
__device__ unsigned int g_done;
#define TSTAMP(i) do {} while (0)
#define CSTAMP(i) do {} while (0)

__device__ __forceinline__ void wg_fence() { asm volatile("wgmma.fence.sync.aligned;" ::: "memory"); }
__device__ __forceinline__ void wg_commit() { asm volatile("wgmma.commit_group.sync.aligned;" ::: "memory"); }
template <int N> __device__ __forceinline__ void wg_wait() { asm volatile("wgmma.wait_group.sync.aligned %0;" ::"n"(N) : "memory"); }
template <int N> __device__ __forceinline__ void fence_regs(float* r) {
#pragma unroll
    for (int i = 0; i < N; i++) asm volatile("" : "+f"(r[i])::"memory");
}
template <int N> __device__ __forceinline__ void fence_uregs(uint32_t* r) {
#pragma unroll
    for (int i = 0; i < N; i++) asm volatile("" : "+r"(r[i])::"memory");
}
__device__ __forceinline__ uint64_t make_desc(uint32_t saddr, uint32_t lbo, uint32_t sbo, uint32_t swz) {
    return (uint64_t)((saddr & 0x3FFFF) >> 4) | ((uint64_t)(lbo >> 4) << 16) | ((uint64_t)(sbo >> 4) << 32) | ((uint64_t)swz << 62);
}
__device__ __forceinline__ void mbar_init(uint32_t bar, uint32_t count) {
    asm volatile("mbarrier.init.shared::cta.b64 [%0], %1;" ::"r"(bar), "r"(count) : "memory");
}
__device__ __forceinline__ void mbar_expect_tx(uint32_t bar, uint32_t bytes) {
    asm volatile("mbarrier.arrive.expect_tx.shared::cta.b64 _, [%0], %1;" ::"r"(bar), "r"(bytes) : "memory");
}
__device__ __forceinline__ void mbar_expect_tx_noarrive(uint32_t bar, uint32_t bytes) {
    asm volatile("mbarrier.expect_tx.relaxed.cta.shared::cta.b64 [%0], %1;" ::"r"(bar), "r"(bytes) : "memory");
}
__device__ __forceinline__ void mbar_arrive(uint32_t bar) {
    asm volatile("mbarrier.arrive.shared::cta.b64 _, [%0];" ::"r"(bar) : "memory");
}
__device__ __forceinline__ bool mbar_try(uint32_t bar, uint32_t parity) {
    uint32_t ok;
    asm volatile("{\n.reg .pred p;\nmbarrier.try_wait.parity.shared::cta.b64 p, [%1], %2;\nselp.u32 %0, 1, 0, p;\n}\n"
                 : "=r"(ok) : "r"(bar), "r"(parity) : "memory");
    return ok != 0;
}
__device__ __forceinline__ void mbar_wait(uint32_t bar, uint32_t parity) {
    uint32_t spins = 0;
    while (!mbar_try(bar, parity)) {
        if (++spins > (1u << 24)) __trap();
    }
}
__device__ __forceinline__ void mbar_wait_w(uint32_t bar, uint32_t parity) {
    uint32_t spins = 0;
    while (!__all_sync(0xffffffffu, mbar_try(bar, parity))) {
        if (++spins > (1u << 24)) __trap();
    }
}
__device__ __forceinline__ void tma2d(uint32_t dst, const CUtensorMap* tm, int c0, int c1, uint32_t bar) {
    asm volatile("cp.async.bulk.tensor.2d.shared::cluster.global.mbarrier::complete_tx::bytes [%0], [%1, {%3, %4}], [%2];"
                 ::"r"(dst), "l"((uint64_t)tm), "r"(bar), "r"(c0), "r"(c1) : "memory");
}
__device__ __forceinline__ void tma3d(uint32_t dst, const CUtensorMap* tm, int c0, int c1, int c2, uint32_t bar) {
    asm volatile("cp.async.bulk.tensor.3d.shared::cluster.global.mbarrier::complete_tx::bytes [%0], [%1, {%3, %4, %5}], [%2];"
                 ::"r"(dst), "l"((uint64_t)tm), "r"(bar), "r"(c0), "r"(c1), "r"(c2) : "memory");
}
__device__ __forceinline__ void tma4d(uint32_t dst, const CUtensorMap* tm, int c0, int c1, int c2, int c3, uint32_t bar) {
    asm volatile("cp.async.bulk.tensor.4d.shared::cluster.global.mbarrier::complete_tx::bytes [%0], [%1, {%3, %4, %5, %6}], [%2];"
                 ::"r"(dst), "l"((uint64_t)tm), "r"(bar), "r"(c0), "r"(c1), "r"(c2), "r"(c3) : "memory");
}
__device__ __forceinline__ void prefetch_tm(const CUtensorMap* tm) { asm volatile("prefetch.tensormap [%0];" ::"l"((uint64_t)tm) : "memory"); }
__device__ __forceinline__ void bulk_s2g(void* dst, uint32_t src, uint32_t bytes) {
    asm volatile("cp.async.bulk.global.shared::cta.bulk_group [%0], [%1], %2;" ::"l"(dst), "r"(src), "r"(bytes) : "memory");
}
__device__ __forceinline__ void bulk_commit() { asm volatile("cp.async.bulk.commit_group;" ::: "memory"); }
__device__ __forceinline__ void bulk_wait_all() { asm volatile("cp.async.bulk.wait_group 0;" ::: "memory"); }
__device__ __forceinline__ void fence_async_global() { asm volatile("fence.proxy.async.global;" ::: "memory"); }
__device__ __forceinline__ void bulk_g2s(uint32_t dst, const void* src, uint32_t bytes, uint32_t bar) {
    asm volatile("cp.async.bulk.shared::cluster.global.mbarrier::complete_tx::bytes [%0], [%1], %2, [%3];"
                 ::"r"(dst), "l"(src), "r"(bytes), "r"(bar) : "memory");
}
__device__ __forceinline__ void fence_async_smem() { asm volatile("fence.proxy.async.shared::cta;" ::: "memory"); }
__device__ __forceinline__ void named_bar(int id, int n) { asm volatile("bar.sync %0, %1;" ::"r"(id), "r"(n) : "memory"); }
__device__ __forceinline__ bool named_bar_and(int id, int n, bool pred) {
    uint32_t r;
    asm volatile("{\n.reg .pred p, q;\nsetp.ne.u32 p, %3, 0;\nbarrier.cta.red.and.pred q, %1, %2, p;\nselp.u32 %0, 1, 0, q;\n}\n"
                 : "=r"(r) : "r"(id), "r"(n), "r"((uint32_t)pred) : "memory");
    return r != 0;
}
__device__ __forceinline__ unsigned int ld_acquire(const unsigned int* p) {
    unsigned int v;
    asm volatile("ld.acquire.gpu.global.u32 %0, [%1];" : "=r"(v) : "l"(p) : "memory");
    return v;
}
__device__ __forceinline__ void red_release_add(unsigned int* p, unsigned int v) {
    asm volatile("red.release.gpu.global.add.u32 [%0], %1;" ::"l"(p), "r"(v) : "memory");
}
__device__ __forceinline__ void poll_counter(const unsigned int* p, unsigned int target) {
    uint32_t spins = 0;
    while (ld_acquire(p) < target) {
        if (++spins > (1u << 22)) __trap();
    }
}
__device__ __forceinline__ float ex2f(float x) { float y; asm("ex2.approx.ftz.f32 %0, %1;" : "=f"(y) : "f"(x)); return y; }
__device__ __forceinline__ uint32_t pack_f16(float lo, float hi) { uint32_t r; asm("cvt.rn.f16x2.f32 %0, %1, %2;" : "=r"(r) : "f"(hi), "f"(lo)); return r; }
__device__ __forceinline__ uint32_t pack_bf16(float lo, float hi) { uint32_t r; asm("cvt.rn.bf16x2.f32 %0, %1, %2;" : "=r"(r) : "f"(hi), "f"(lo)); return r; }
__device__ __forceinline__ float bf_lo(uint32_t v) { return __uint_as_float(v << 16); }
__device__ __forceinline__ float bf_hi(uint32_t v) { return __uint_as_float(v & 0xFFFF0000u); }
__device__ __forceinline__ uint32_t hfma2(uint32_t a, uint32_t b, uint32_t c) { uint32_t r; asm("fma.rn.f16x2 %0, %1, %2, %3;" : "=r"(r) : "r"(a), "r"(b), "r"(c)); return r; }
__device__ __forceinline__ uint32_t bmul2(uint32_t a, uint32_t b) { uint32_t r; asm("mul.rn.bf16x2 %0, %1, %2;" : "=r"(r) : "r"(a), "r"(b)); return r; }
__device__ __forceinline__ uint32_t badd2(uint32_t a, uint32_t b) { uint32_t r; asm("add.rn.bf16x2 %0, %1, %2;" : "=r"(r) : "r"(a), "r"(b)); return r; }
template <int LUT> __device__ __forceinline__ uint32_t lop3(uint32_t a, uint32_t b, uint32_t c) {
    uint32_t r; asm("lop3.b32 %0, %1, %2, %3, %4;" : "=r"(r) : "r"(a), "r"(b), "r"(c), "n"(LUT)); return r;
}
__device__ __forceinline__ uint32_t lds32(uint32_t a) { uint32_t v; asm volatile("ld.shared.u32 %0, [%1];" : "=r"(v) : "r"(a)); return v; }
__device__ __forceinline__ float ldsf(uint32_t a) { float v; asm volatile("ld.shared.f32 %0, [%1];" : "=f"(v) : "r"(a)); return v; }
__device__ __forceinline__ uint4 lds128(uint32_t a) { uint4 v; asm volatile("ld.shared.v4.u32 {%0,%1,%2,%3}, [%4];" : "=r"(v.x), "=r"(v.y), "=r"(v.z), "=r"(v.w) : "r"(a)); return v; }
__device__ __forceinline__ void lds64(uint32_t a, uint32_t& x, uint32_t& y) { asm volatile("ld.shared.v2.u32 {%0,%1}, [%2];" : "=r"(x), "=r"(y) : "r"(a)); }
__device__ __forceinline__ void sts32(uint32_t a, uint32_t v) { asm volatile("st.shared.u32 [%0], %1;" ::"r"(a), "r"(v) : "memory"); }
__device__ __forceinline__ void sts64f(uint32_t a, float x, float y) { asm volatile("st.shared.v2.f32 [%0], {%1,%2};" ::"r"(a), "f"(x), "f"(y) : "memory"); }
__device__ __forceinline__ void sts128(uint32_t a, uint32_t x, uint32_t y, uint32_t z, uint32_t w) {
    asm volatile("st.shared.v4.u32 [%0], {%1,%2,%3,%4};" ::"r"(a), "r"(x), "r"(y), "r"(z), "r"(w) : "memory");
}

__device__ __forceinline__ void wg_ss_n32_tb(float* d, uint64_t descA, uint64_t descB) {
    asm volatile("wgmma.mma_async.sync.aligned.m64n32k16.f32.bf16.bf16 {%0,%1,%2,%3,%4,%5,%6,%7,%8,%9,%10,%11,%12,%13,%14,%15}, %16, %17, 1, 1, 1, 0, 1;\n"
        : "+f"(d[0]), "+f"(d[1]), "+f"(d[2]), "+f"(d[3]), "+f"(d[4]), "+f"(d[5]), "+f"(d[6]), "+f"(d[7]), "+f"(d[8]), "+f"(d[9]), "+f"(d[10]), "+f"(d[11]), "+f"(d[12]), "+f"(d[13]), "+f"(d[14]), "+f"(d[15])
        : "l"(descA), "l"(descB));
}
__device__ __forceinline__ void wg_qk_n64(float* d, const uint32_t* a, uint64_t desc) {
    asm volatile("wgmma.mma_async.sync.aligned.m64n64k16.f32.bf16.bf16 {%0,%1,%2,%3,%4,%5,%6,%7,%8,%9,%10,%11,%12,%13,%14,%15,%16,%17,%18,%19,%20,%21,%22,%23,%24,%25,%26,%27,%28,%29,%30,%31}, {%32,%33,%34,%35}, %36, 0, 1, 1, 0;\n"
        : "+f"(d[0]), "+f"(d[1]), "+f"(d[2]), "+f"(d[3]), "+f"(d[4]), "+f"(d[5]), "+f"(d[6]), "+f"(d[7]), "+f"(d[8]), "+f"(d[9]), "+f"(d[10]), "+f"(d[11]), "+f"(d[12]), "+f"(d[13]), "+f"(d[14]), "+f"(d[15]), "+f"(d[16]), "+f"(d[17]), "+f"(d[18]), "+f"(d[19]), "+f"(d[20]), "+f"(d[21]), "+f"(d[22]), "+f"(d[23]), "+f"(d[24]), "+f"(d[25]), "+f"(d[26]), "+f"(d[27]), "+f"(d[28]), "+f"(d[29]), "+f"(d[30]), "+f"(d[31])
        : "r"(a[0]), "r"(a[1]), "r"(a[2]), "r"(a[3]), "l"(desc));
}
__device__ __forceinline__ void wg_pv_n24(float* d, const uint32_t* a, uint64_t desc) {
    asm volatile("wgmma.mma_async.sync.aligned.m64n24k16.f32.f16.f16 {%0,%1,%2,%3,%4,%5,%6,%7,%8,%9,%10,%11}, {%12,%13,%14,%15}, %16, 1, 1, 1, 1;\n"
        : "+f"(d[0]), "+f"(d[1]), "+f"(d[2]), "+f"(d[3]), "+f"(d[4]), "+f"(d[5]), "+f"(d[6]), "+f"(d[7]), "+f"(d[8]), "+f"(d[9]), "+f"(d[10]), "+f"(d[11])
        : "r"(a[0]), "r"(a[1]), "r"(a[2]), "r"(a[3]), "l"(desc));
}
__device__ __forceinline__ void wg_cv_n32(float* d, const uint32_t* a, uint64_t desc) {
    asm volatile("wgmma.mma_async.sync.aligned.m64n32k16.f32.bf16.bf16 {%0,%1,%2,%3,%4,%5,%6,%7,%8,%9,%10,%11,%12,%13,%14,%15}, {%16,%17,%18,%19}, %20, 1, 1, 1, 0;\n"
        : "+f"(d[0]), "+f"(d[1]), "+f"(d[2]), "+f"(d[3]), "+f"(d[4]), "+f"(d[5]), "+f"(d[6]), "+f"(d[7]), "+f"(d[8]), "+f"(d[9]), "+f"(d[10]), "+f"(d[11]), "+f"(d[12]), "+f"(d[13]), "+f"(d[14]), "+f"(d[15])
        : "r"(a[0]), "r"(a[1]), "r"(a[2]), "r"(a[3]), "l"(desc));
}
__device__ __forceinline__ void wg_cv_n64(float* d, const uint32_t* a, uint64_t desc) {
    asm volatile("wgmma.mma_async.sync.aligned.m64n64k16.f32.bf16.bf16 {%0,%1,%2,%3,%4,%5,%6,%7,%8,%9,%10,%11,%12,%13,%14,%15,%16,%17,%18,%19,%20,%21,%22,%23,%24,%25,%26,%27,%28,%29,%30,%31}, {%32,%33,%34,%35}, %36, 1, 1, 1, 0;\n"
        : "+f"(d[0]), "+f"(d[1]), "+f"(d[2]), "+f"(d[3]), "+f"(d[4]), "+f"(d[5]), "+f"(d[6]), "+f"(d[7]), "+f"(d[8]), "+f"(d[9]), "+f"(d[10]), "+f"(d[11]), "+f"(d[12]), "+f"(d[13]), "+f"(d[14]), "+f"(d[15]), "+f"(d[16]), "+f"(d[17]), "+f"(d[18]), "+f"(d[19]), "+f"(d[20]), "+f"(d[21]), "+f"(d[22]), "+f"(d[23]), "+f"(d[24]), "+f"(d[25]), "+f"(d[26]), "+f"(d[27]), "+f"(d[28]), "+f"(d[29]), "+f"(d[30]), "+f"(d[31])
        : "r"(a[0]), "r"(a[1]), "r"(a[2]), "r"(a[3]), "l"(desc));
}

template <int N> __device__ __forceinline__ void wg_cv(float* d, const uint32_t* a, uint64_t desc);
template <> __device__ __forceinline__ void wg_cv<32>(float* d, const uint32_t* a, uint64_t s) { wg_cv_n32(d, a, s); }
template <> __device__ __forceinline__ void wg_cv<64>(float* d, const uint32_t* a, uint64_t s) { wg_cv_n64(d, a, s); }

constexpr uint32_t POLYMASK = 0xB5B5u;
__device__ __forceinline__ void softmax_fast(const float* s, uint32_t* p, uint32_t mlo) {
    const uint32_t C3 = 0x2cfb2cfbu, C2 = 0x9fec9fecu, C1 = 0x37a837a8u, C0 = 0x37383738u;
#pragma unroll
    for (int i = 0; i < 16; i++) {
        const float s0 = s[2 * i], s1 = s[2 * i + 1];
        if ((POLYMASK >> i) & 1) {
            const float t0 = s0 + 12303.0f, t1 = s1 + 12303.0f;
            const uint32_t T = __byte_perm(__float_as_uint(t0), __float_as_uint(t1), 0x5410);
            const uint32_t U = lop3<0xEA>(T, mlo, 0x3C003C00u);
            uint32_t h = hfma2(U, C3, C2);
            h = hfma2(h, U, C1);
            h = hfma2(h, U, C0);
            p[i] = lop3<0xE4>(h, T, 0x03FF03FFu);
        } else {
            p[i] = pack_f16(ex2f(s0), ex2f(s1));
        }
    }
}

__device__ __forceinline__ void gemm_chunk(float* acc, uint32_t a_addr, uint32_t b_addr) {
    const uint64_t da = make_desc(a_addr, 16, 1024, 1);
    const uint64_t db = make_desc(b_addr, 8192, 1024, 1);
#pragma unroll
    for (int ks = 0; ks < 4; ks++) wg_ss_n32_tb(acc, da + ks * 2, db + ks * 128);
}

__device__ __forceinline__ uint32_t smem_inc(uint32_t addr) {
    uint32_t old;
    asm volatile("atom.acq_rel.cta.shared.add.u32 %0, [%1], 1;" : "=r"(old) : "r"(addr) : "memory");
    return old;
}
__device__ __forceinline__ void wo_half(uint32_t sb, const CUtensorMap* tm_wo, int hg) {
    if (smem_inc(sb + OFF_MISC + 8) == 3) {
        mbar_expect_tx(sb + OFF_BAR + 8 * (B_WO + 2), 32768);
        tma4d(sb + OFF_K, tm_wo, 0, 0, hg * 2, 4, sb + OFF_BAR + 8 * (B_WO + 2));
    }
}

__device__ __forceinline__ void kv_tiles_load(uint32_t sb, const CUtensorMap* tm_k, const CUtensorMap* tm_v, int pb, int hg) {
    const uint32_t br = sb + OFF_BAR + 8 * B_KVIN;
    mbar_expect_tx(br, 67 * 256 + 64 * 256);
    tma2d(sb + S_KT, tm_k, hg * 128, pb * 64 - 3, br);
    tma2d(sb + S_VT, tm_v, hg * 128, pb * 64, br);
}

struct Params {
    const __nv_bfloat16 *aq, *ak, *av, *shift_k, *ssm_D;
    __nv_bfloat16* out;
};

template <int NQ>
__device__ __forceinline__ void conv_phase(float* Dn, uint32_t zaddr, uint64_t hdesc) {
    uint32_t a[3][8];
#pragma unroll
    for (int qi = 0; qi < 16; qi++) {
        uint32_t* aa = a[qi % 3];
        if (qi >= 3) wg_wait<2>();
        const uint32_t z = zaddr + qi * 256;
        lds64(z, aa[0], aa[1]);      lds64(z - 32, aa[2], aa[3]);
        lds64(z - 64, aa[4], aa[5]); lds64(z - 96, aa[6], aa[7]);
        wg_fence();
        wg_cv<NQ>(Dn, &aa[0], hdesc - qi * 8);
        wg_cv<NQ>(Dn, &aa[4], hdesc - qi * 8 + 2);
        wg_commit();
    }
    wg_wait<0>();
    fence_regs<NQ / 2>(Dn);
}

__device__ __forceinline__ void conv_channel(uint32_t kvc, uint32_t zb, uint32_t hb, int tau, int wa, int g, int t, int nb, float dsc_in) {
            {
                const uint32_t src = kvc + tau * 32;
                const uint4 u0 = lds128(src), u1 = lds128(src + 16);
                const uint32_t prev = tau > 0 ? lds32(src - 4) : 0u;
                const uint32_t zd = zb + (32 + tau * 16) * 4;
                sts128(zd,      __byte_perm(u0.x, prev, 0x7610), __byte_perm(u0.x, u0.x, 0x1032), __byte_perm(u0.y, u0.x, 0x7610), __byte_perm(u0.y, u0.y, 0x1032));
                sts128(zd + 16, __byte_perm(u0.z, u0.y, 0x7610), __byte_perm(u0.z, u0.z, 0x1032), __byte_perm(u0.w, u0.z, 0x7610), __byte_perm(u0.w, u0.w, 0x1032));
                sts128(zd + 32, __byte_perm(u1.x, u0.w, 0x7610), __byte_perm(u1.x, u1.x, 0x1032), __byte_perm(u1.y, u1.x, 0x7610), __byte_perm(u1.y, u1.y, 0x1032));
                sts128(zd + 48, __byte_perm(u1.z, u1.y, 0x7610), __byte_perm(u1.z, u1.z, 0x1032), __byte_perm(u1.w, u1.z, 0x7610), __byte_perm(u1.w, u1.w, 0x1032));
                if (tau < 32) sts32(zb + tau * 4, 0u);
            }
            named_bar(nb, 128);
            float D[32];
#pragma unroll
            for (int i = 0; i < 32; i++) D[i] = 0.f;
            fence_regs<32>(D);
            const uint32_t z0 = zb + (32 + 32 * (wa >> 1) + 16 * (wa & 1) + 2 * g - 2 * t) * 4;
            const uint64_t hd = make_desc(hb + 2048, 16, 512, 2);
            conv_phase<64>(D, z0, hd);
            float E[16];
#pragma unroll
            for (int i = 0; i < 16; i++) asm volatile("mov.f32 %0, %1;" : "=f"(E[i]) : "f"(D[16 + i]));
            conv_phase<32>(E, z0 + 4096, hd);
            const int bb0 = 16 * (wa & 1) + 2 * g;
            const int xsw = (g & 3) << 3;
            {
                const uint32_t xb = zb + (wa >> 1) * 4096;
#pragma unroll
                for (int jn = 0; jn < 4; jn++) {
#pragma unroll
                    for (int r = 0; r < 2; r++) {
                        const float v0 = (wa < 2) ? E[4 * jn + 2 * r] : D[4 * jn + 2 * r];
                        const float v1 = (wa < 2) ? E[4 * jn + 2 * r + 1] : D[4 * jn + 2 * r + 1];
                        sts64f(xb + ((bb0 + r) * 32 + ((8 * jn + 2 * t) ^ xsw)) * 4, v0, v1);
                    }
                }
            }
            named_bar(nb, 128);
            {
                const float dsc = dsc_in;
                const uint32_t xb = zb + ((wa >> 1) ^ 1) * 4096;
#pragma unroll
                for (int jn = 0; jn < 4; jn++) {
#pragma unroll
                    for (int e = 0; e < 2; e++) {
                        const int n = 8 * jn + 2 * t + e;
                        float y0, y1; int m, rn;
                        if (wa < 2) { y0 = D[4 * jn + e]; y1 = D[4 * jn + 2 + e]; m = n; rn = n - 1; }
                        else {
                            const bool last = (jn == 3 && e == 1) && (t == 3);
                            y0 = last ? D[13] : E[4 * jn + e]; y1 = last ? D[15] : E[4 * jn + 2 + e];
                            m = last ? 32 : 33 + n; rn = m - 32;
                        }
                        if (rn >= 0) {
                            y0 += ldsf(xb + (bb0 * 32 + (rn ^ xsw)) * 4);
                            y1 += ldsf(xb + ((bb0 + 1) * 32 + (rn ^ xsw)) * 4);
                        }
                        const uint32_t addr = kvc + (32 * m + bb0) * 2;
                        const uint32_t kv = lds32(addr);
                        const uint32_t yb = pack_bf16(y0, y1);
                        const uint32_t kd = pack_bf16(bf_lo(kv) * dsc, bf_hi(kv) * dsc);
                        sts32(addr, badd2(yb, kd));
                    }
                }
                fence_async_smem();
            }
}

__global__ void __launch_bounds__(NTHREADS, 1)
fused_kernel(const __grid_constant__ CUtensorMap tm_x,
             const __grid_constant__ CUtensorMap tm_wq, const __grid_constant__ CUtensorMap tm_wo,
             const __grid_constant__ CUtensorMap tm_wk, const __grid_constant__ CUtensorMap tm_wv,
             const __grid_constant__ CUtensorMap tm_o, const __grid_constant__ CUtensorMap tm_h,
             const __grid_constant__ CUtensorMap tm_k, const __grid_constant__ CUtensorMap tm_v, const Params prm) {
    extern __shared__ __align__(1024) uint8_t smem_raw[];
    const uint32_t sb = (uint32_t)__cvta_generic_to_shared(smem_raw);
    const int warp_id = __shfl_sync(0xffffffffu, threadIdx.x >> 5, 0);
    const int lane = threadIdx.x & 31;
    const int g = lane >> 2, t = lane & 3;
    const int b = blockIdx.x, pb = b >> 2, hg = b & 3;
    auto bar = [&](int i) { return sb + OFF_BAR + 8 * i; };

    if (threadIdx.x == 512) {
        TSTAMP(0);
        prefetch_tm(&tm_x); prefetch_tm(&tm_wq); prefetch_tm(&tm_wk); prefetch_tm(&tm_wv);
        mbar_init(bar(B_WKV), 1);
        for (int j = 0; j < 4; j++) { mbar_init(bar(B_X + j), 1); mbar_init(bar(B_W + j), 1); mbar_init(bar(B_WO + j), 1); mbar_init(bar(B_O + j), 1); }
        sts32(sb + OFF_MISC + 8, 0u); sts32(sb + OFF_MISC + 12, 0u); sts32(sb + OFF_MISC + 16, 0u);
        for (int j = 0; j < 8; j++) mbar_init(bar(B_KV + j), j == 0 ? 2 : 1);
        mbar_init(bar(B_QEMPTY), 4); mbar_init(bar(B_QEMPTY + 1), 4);
        mbar_init(bar(B_QDONE), 4); mbar_init(bar(B_ATT), 4);
        mbar_init(bar(B_H), 1); mbar_init(bar(B_CV), 1); mbar_init(bar(B_KVT), 512); mbar_init(bar(B_KVIN), 1); mbar_init(bar(B_CONV), 4);
        asm volatile("fence.mbarrier_init.release.cluster;" ::: "memory");
    }

    if (warp_id < 16) {
        const int w = warp_id >> 2, wq = warp_id & 3;
        __syncthreads();
        float acc[16];
#pragma unroll
        for (int i = 0; i < 16; i++) acc[i] = 0.f;
        fence_regs<16>(acc);
        const uint32_t bcol = (w >> 1) * 8192 + (w & 1) * 64;
        sts128(sb + S_H + w * 6144 + (threadIdx.x & 127) * 16, 0u, 0u, 0u, 0u);
        fence_async_smem();
        {
            const int kch0 = hg * 128 + lane * 4;
            const uint4 s0 = __ldg((const uint4*)(prm.shift_k + kch0 * 4));
            const uint4 s1 = __ldg((const uint4*)(prm.shift_k + kch0 * 4) + 1);
            uint32_t wA[4], wB[4];
            wA[0] = __byte_perm(s0.x, s0.z, 0x5410); wA[1] = __byte_perm(s0.x, s0.z, 0x7632);
            wA[2] = __byte_perm(s0.y, s0.w, 0x5410); wA[3] = __byte_perm(s0.y, s0.w, 0x7632);
            wB[0] = __byte_perm(s1.x, s1.z, 0x5410); wB[1] = __byte_perm(s1.x, s1.z, 0x7632);
            wB[2] = __byte_perm(s1.y, s1.w, 0x5410); wB[3] = __byte_perm(s1.y, s1.w, 0x7632);
            mbar_wait_w(bar(B_KVIN), 0);
            const uint32_t kb = sb + S_KT + warp_id * 4 * 256 + lane * 8, vb = sb + S_VT + warp_id * 4 * 256 + lane * 8;
            uint32_t ka[7], kq[7], xa[4], xb[4];
#pragma unroll
            for (int i = 0; i < 7; i++) lds64(kb + i * 256, ka[i], kq[i]);
#pragma unroll
            for (int i = 0; i < 4; i++) {
                uint32_t va, vq;
                lds64(vb + i * 256, va, vq);
                xa[i] = bmul2(badd2(badd2(badd2(bmul2(ka[i], wA[3]), bmul2(ka[i + 1], wA[2])), bmul2(ka[i + 2], wA[1])), bmul2(ka[i + 3], wA[0])), va);
                xb[i] = bmul2(badd2(badd2(badd2(bmul2(kq[i], wB[3]), bmul2(kq[i + 1], wB[2])), bmul2(kq[i + 2], wB[1])), bmul2(kq[i + 3], wB[0])), vq);
            }
            uint2* dst = (uint2*)(g_kvT + (size_t)kch0 * S_LEN + pb * 64 + warp_id * 4);
            dst[0] = make_uint2(__byte_perm(xa[0], xa[1], 0x5410), __byte_perm(xa[2], xa[3], 0x5410));
            dst[S_LEN / 4] = make_uint2(__byte_perm(xa[0], xa[1], 0x7632), __byte_perm(xa[2], xa[3], 0x7632));
            dst[2 * (S_LEN / 4)] = make_uint2(__byte_perm(xb[0], xb[1], 0x5410), __byte_perm(xb[2], xb[3], 0x5410));
            dst[3 * (S_LEN / 4)] = make_uint2(__byte_perm(xb[0], xb[1], 0x7632), __byte_perm(xb[2], xb[3], 0x7632));
            mbar_arrive(bar(B_KVT));
        }
#pragma unroll 1
        for (int jj = 0; jj < 4; jj++) {
            mbar_wait_w(bar(B_X + jj), 0);
            mbar_wait_w(bar(B_W + jj), 0);
            if (threadIdx.x == 0) TSTAMP(jj == 0 ? 23 : jj == 1 ? 24 : jj == 2 ? 26 : 27);
            wg_fence();
            gemm_chunk(acc, sb + OFF_X + jj * 16384, sb + OFF_V + (jj & 1) * 32768 + bcol);
            gemm_chunk(acc, sb + OFF_X + jj * 16384 + 8192, sb + OFF_V + (jj & 1) * 32768 + 16384 + bcol);
            wg_commit();
            wg_wait<0>();
            if (jj < 2 && (threadIdx.x & 127) == 0) {
                if (smem_inc(sb + OFF_MISC + 12 + 4 * jj) == 3) {
                    mbar_expect_tx(bar(B_W + jj + 2), 32768);
                    tma4d(sb + OFF_V + jj * 32768, &tm_wq, 0, 0, hg * 2, 2 * (jj + 2), bar(B_W + jj + 2));
                }
            }
        }
        fence_regs<16>(acc);
        if ((threadIdx.x & 127) == 0) { mbar_arrive(bar(B_QDONE)); if (w == 0) TSTAMP(1); }
        uint32_t qa[2][4];
        float qn[2];
        {
            const float c = 0.25f * 1.4426950408889634f;
#pragma unroll
            for (int hh = 0; hh < 2; hh++) {
                float n0 = 0.f, n1 = 0.f;
#pragma unroll
                for (int i = 0; i < 4; i++) {
                    const uint32_t qb = pack_bf16(acc[8 * hh + 2 * i], acc[8 * hh + 2 * i + 1]);
                    const uint32_t qs = pack_bf16(bf_lo(qb) * c, bf_hi(qb) * c);
                    qa[hh][i] = qs;
                    const float e = bf_lo(qs) * bf_lo(qs) + bf_hi(qs) * bf_hi(qs);
                    if (i & 1) n1 += e; else n0 += e;
                }
                n0 += __shfl_xor_sync(0xffffffffu, n0, 1); n0 += __shfl_xor_sync(0xffffffffu, n0, 2);
                n1 += __shfl_xor_sync(0xffffffffu, n1, 1); n1 += __shfl_xor_sync(0xffffffffu, n1, 2);
                qn[hh] = fmaxf(n0, n1);
            }
        }
        {
            const float dsc = __bfloat162float(prm.ssm_D[4 * b + w]);
            mbar_wait_w(bar(B_QDONE), 0);
            mbar_wait_w(bar(B_H), 0);
            mbar_wait_w(bar(B_CV), 0);
            if (threadIdx.x == 0) TSTAMP(9);
            conv_channel(sb + C_KVC + w * 4096, sb + S_Z + w * 8448, sb + S_H + w * 6144, threadIdx.x & 127, wq, g, t, 1 + w, dsc);
            named_bar(1 + w, 128);
            if ((threadIdx.x & 127) == 0) { mbar_arrive(bar(B_CONV)); if (w == 0) TSTAMP(10); }
        }
        uint32_t mlo = 0x03FF03FFu; asm volatile("" : "+r"(mlo));
        const uint64_t kdesc0 = make_desc(sb + OFF_K, 128, 256, 0);
        const uint64_t vdesc0 = make_desc(sb + OFF_VONES - 256, 128, 256, 0);
        constexpr uint64_t VSTEP = ((uint64_t)16 << 32) - 16;
        mbar_wait_w(bar(B_KV + 0), 0);
        if ((threadIdx.x & 127) == 0 && w == 0) TSTAMP(2);
        const float kmax2 = ldsf(sb + OFF_MISC);
        const bool fast0 = __all_sync(0xffffffffu, named_bar_and(1 + w, 128, qn[0] * kmax2 <= 193.0f));
        const bool fast1 = __all_sync(0xffffffffu, named_bar_and(1 + w, 128, qn[1] * kmax2 <= 193.0f));
        uint32_t a[4] = {qa[0][0], qa[0][1], qa[0][2], qa[0][3]};
#pragma unroll 1
        for (int hh = 0; hh < 2; hh++) {
            const bool fast = hh ? fast1 : fast0;
            float S[32], O[12];
#pragma unroll
            for (int i = 0; i < 12; i++) O[i] = 0.f;
#pragma unroll
            for (int i = 0; i < 32; i++) S[i] = 0.f;
            fence_regs<12>(O); fence_regs<32>(S);
            wg_fence();
            wg_qk_n64(S, a, kdesc0);
            wg_commit();
            wg_wait<0>();
            uint64_t kd = kdesc0 + 128, vd = vdesc0;
            if (fast) {
                uint32_t P[16];
#pragma unroll 1
                for (int c = 0; c < 8; c++) {
                    if (c < 7) mbar_wait_w(bar(B_KV + c + 1), 0);
#pragma unroll 1
                    for (int j = 0; j < 4; j++) {
                        fence_regs<32>(S);
                        softmax_fast(S, P, mlo);
                        fence_regs<32>(S);
                        wg_fence();
                        wg_qk_n64(S, a, kd);
#pragma unroll
                        for (int i = 0; i < 4; i++) wg_pv_n24(O, &P[4 * i], vd + i * VSTEP);
                        wg_commit();
                        wg_wait<0>();
                        kd += 128; vd += 4 * VSTEP;
                    }
                    if (hh == 1 && c == 3 && (threadIdx.x & 127) == 0) wo_half(sb, &tm_wo, hg);
                }
            } else {
                uint32_t P[16];
                float m0 = -INFINITY, m1 = -INFINITY;
#pragma unroll 1
                for (int c = 0; c < 8; c++) {
                    if (c < 7) mbar_wait_w(bar(B_KV + c + 1), 0);
#pragma unroll 1
                    for (int j = 0; j < 4; j++) {
                        fence_regs<32>(S); fence_regs<12>(O);
                        float x0 = m0, x1 = m1;
#pragma unroll
                        for (int i = 0; i < 8; i++) {
                            x0 = fmaxf(x0, fmaxf(S[4 * i], S[4 * i + 1]));
                            x1 = fmaxf(x1, fmaxf(S[4 * i + 2], S[4 * i + 3]));
                        }
                        x0 = fmaxf(x0, __shfl_xor_sync(0xffffffffu, x0, 1)); x0 = fmaxf(x0, __shfl_xor_sync(0xffffffffu, x0, 2));
                        x1 = fmaxf(x1, __shfl_xor_sync(0xffffffffu, x1, 1)); x1 = fmaxf(x1, __shfl_xor_sync(0xffffffffu, x1, 2));
                        const float r0 = ex2f(m0 - x0), r1 = ex2f(m1 - x1);
                        m0 = x0; m1 = x1;
#pragma unroll
                        for (int i = 0; i < 3; i++) { O[4 * i] *= r0; O[4 * i + 1] *= r0; O[4 * i + 2] *= r1; O[4 * i + 3] *= r1; }
#pragma unroll
                        for (int i = 0; i < 8; i++) {
                            P[2 * i] = pack_f16(ex2f(S[4 * i] - m0), ex2f(S[4 * i + 1] - m0));
                            P[2 * i + 1] = pack_f16(ex2f(S[4 * i + 2] - m1), ex2f(S[4 * i + 3] - m1));
                        }
                        fence_regs<32>(S); fence_regs<12>(O);
                        wg_fence();
                        wg_qk_n64(S, a, kd);
#pragma unroll
                        for (int i = 0; i < 4; i++) wg_pv_n24(O, &P[4 * i], vd + i * VSTEP);
                        wg_commit();
                        wg_wait<0>();
                        kd += 128; vd += 4 * VSTEP;
                    }
                    if (hh == 1 && c == 3 && (threadIdx.x & 127) == 0) wo_half(sb, &tm_wo, hg);
                }
            }
            fence_regs<12>(O);
            const float vscale = ldsf(sb + OFF_MISC + 4);
            const float i0 = __fdividef(vscale, O[4]), i1 = __fdividef(vscale, O[6]);
            const int row = pb * 64 + wq * 16 + g;
            uint32_t* o0 = (uint32_t*)(g_o + (size_t)row * 512 + (hg * 8 + 2 * w + hh) * 16) + t;
            uint32_t* o1 = o0 + 8 * 256;
            o0[0] = pack_bf16(O[0] * i0, O[1] * i0);
            o0[4] = pack_bf16(O[8] * i0, O[9] * i0);
            o1[0] = pack_bf16(O[2] * i1, O[3] * i1);
            o1[4] = pack_bf16(O[10] * i1, O[11] * i1);
            if ((threadIdx.x & 127) == 0 && w == 0) { TSTAMP(3 + hh); CSTAMP(40 + hh); }
#pragma unroll
            for (int i = 0; i < 4; i++) a[i] = qa[1][i];
        }
        named_bar(1 + w, 128);
        if ((threadIdx.x & 127) == 0) {
            red_release_add(&g_o_count[pb], 1);
            mbar_arrive(bar(B_ATT));
        }
        if (threadIdx.x == 0) {
            TSTAMP(30);
            mbar_wait(bar(B_ATT), 0);
            TSTAMP(31);
            poll_counter(&g_o_count[pb], 16);
            TSTAMP(18);
            fence_async_global();
            for (int jj = 0; jj < 4; jj++) {
                mbar_expect_tx(bar(B_O + jj), 16384);
                tma3d(sb + OFF_V + jj * 16384, &tm_o, 0, pb * 64, 2 * jj, bar(B_O + jj));
            }
            __threadfence();
            if (atomicAdd(&g_done, 1) == 2 * NCTA - 1) {
                for (int i = 0; i < NCTA; i++) g_stats[i] = 0ull;
                for (int i = 0; i < 4; i++) { g_kvt_count[i] = 0; g_z_count[i] = 0; }
                for (int i = 0; i < 32; i++) g_o_count[i] = 0;
                g_done = 0;
                __threadfence();
            }
        } else if (threadIdx.x == 128) {
            mbar_wait(bar(B_ATT), 0);
            mbar_expect_tx(bar(B_WO + 3), 32768);
            tma4d(sb + OFF_K + 32768, &tm_wo, 0, 0, hg * 2, 6, bar(B_WO + 3));
        }
        __syncwarp();
#pragma unroll
        for (int i = 0; i < 16; i++) acc[i] = 0.f;
        fence_regs<16>(acc);
#pragma unroll 1
        for (int jj = 0; jj < 4; jj++) {
            mbar_wait_w(bar(B_WO + jj), 0);
            mbar_wait_w(bar(B_O + jj), 0);
            if (threadIdx.x == 0 && (jj == 0 || jj == 3)) TSTAMP(jj == 0 ? 32 : 33);
            const uint32_t wb = sb + (jj < 2 ? OFF_X + jj * 32768 : (jj == 2 ? OFF_K : OFF_K + 32768)) + bcol;
            wg_fence();
            gemm_chunk(acc, sb + OFF_V + jj * 16384, wb);
            gemm_chunk(acc, sb + OFF_V + jj * 16384 + 8192, wb + 16384);
            wg_commit();
        }
        wg_wait<0>();
        fence_regs<16>(acc);
        {
            const int row = pb * 64 + wq * 16 + g;
            uint32_t* d0 = (uint32_t*)(prm.out + (size_t)row * 1024 + 512 + hg * 128 + w * 32) + t;
            uint32_t* d1 = d0 + 8 * 512;
#pragma unroll
            for (int i = 0; i < 4; i++) {
                d0[4 * i] = pack_bf16(acc[4 * i], acc[4 * i + 1]);
                d1[4 * i] = pack_bf16(acc[4 * i + 2], acc[4 * i + 3]);
            }
        }
        if ((threadIdx.x & 127) == 0 && w == 0) TSTAMP(5);
    } else {
        const int wa = warp_id - 16, tau = threadIdx.x - 512;
        __syncthreads();
        const bool kv_cta = (hg == (pb & 3));
        if (tau == 0) {
            if (kv_cta) {
                mbar_expect_tx(bar(B_WKV), 32768);
                tma3d(sb + OFF_C, &tm_wk, 0, 0, 0, bar(B_WKV));
                tma3d(sb + OFF_C + 16384, &tm_wv, 0, 0, 0, bar(B_WKV));
            }
            for (int jj = 0; jj < 4; jj++) {
                mbar_expect_tx(bar(B_X + jj), 16384);
                tma3d(sb + OFF_X + jj * 16384, &tm_x, 0, pb * 64, 2 * jj, bar(B_X + jj));
                if (!kv_cta && jj < 2) {
                    mbar_expect_tx(bar(B_W + jj), 32768);
                    tma4d(sb + OFF_V + jj * 32768, &tm_wq, 0, 0, hg * 2, 2 * jj, bar(B_W + jj));
                }
            }
            kv_tiles_load(sb, &tm_k, &tm_v, pb, hg);
            mbar_expect_tx(bar(B_H), 16384);
            for (int i = 0; i < 4; i++) tma2d(sb + S_H + i * 6144 + 2048, &tm_h, 0, (4 * b + i) * 64, bar(B_H));
            TSTAMP(25);
        }
        __syncwarp();
        if (kv_cta) {
            float acc[16];
#pragma unroll
            for (int i = 0; i < 16; i++) acc[i] = 0.f;
            fence_regs<16>(acc);
            mbar_wait_w(bar(B_WKV), 0);
            if (tau == 0) TSTAMP(20);
#pragma unroll
            for (int jj = 0; jj < 4; jj++) {
                mbar_wait_w(bar(B_X + jj), 0);
                wg_fence();
#pragma unroll
                for (int j = 2 * jj; j < 2 * jj + 2; j++) {
                    const uint64_t da = make_desc(sb + OFF_X + j * 8192, 16, 1024, 1);
                    const uint64_t db = make_desc(sb + OFF_C + j * 2048, 16384, 256, 3);
#pragma unroll
                    for (int ks = 0; ks < 4; ks++) wg_ss_n32_tb(acc, da + ks * 2, db + ks * 32);
                }
                wg_commit();
            }
            wg_wait<0>();
            fence_regs<16>(acc);
            if (tau == 0) TSTAMP(22);
            {
                uint32_t kk[4], vv[4];
#pragma unroll
                for (int i = 0; i < 4; i++) { kk[i] = pack_bf16(acc[2 * i], acc[2 * i + 1]); vv[i] = pack_bf16(acc[8 + 2 * i], acc[8 + 2 * i + 1]); }
                const int s = 4 * pb + wa;
                uint32_t* kp = (uint32_t*)(g_kimg + s * 512 + g * 16 + 4 * t);
                kp[0] = kk[0]; kp[64] = kk[1]; kp[32] = kk[2]; kp[96] = kk[3];
                uint32_t* vlo = (uint32_t*)(g_vimg + (127 - s) * 256 + g * 16 + 4 * t);
                uint32_t* vhi = (uint32_t*)(g_vimg + 32768 + 256 + s * 256 + g * 16 + 4 * t);
                vlo[0] = pack_f16(bf_lo(vv[0]), bf_hi(vv[0])); vlo[32] = pack_f16(bf_lo(vv[1]), bf_hi(vv[1]));
                vhi[0] = pack_f16(bf_lo(vv[2]), bf_hi(vv[2])); vhi[32] = pack_f16(bf_lo(vv[3]), bf_hi(vv[3]));
                uint32_t* vr = (uint32_t*)(g_vraw + (size_t)(16 * s + g) * 16) + t;
                vr[0] = vv[0]; vr[64] = vv[1]; vr[4] = vv[2]; vr[68] = vv[3];
                float n0 = bf_lo(kk[0]) * bf_lo(kk[0]) + bf_hi(kk[0]) * bf_hi(kk[0]) + bf_lo(kk[2]) * bf_lo(kk[2]) + bf_hi(kk[2]) * bf_hi(kk[2]);
                float n1 = bf_lo(kk[1]) * bf_lo(kk[1]) + bf_hi(kk[1]) * bf_hi(kk[1]) + bf_lo(kk[3]) * bf_lo(kk[3]) + bf_hi(kk[3]) * bf_hi(kk[3]);
                n0 += __shfl_xor_sync(0xffffffffu, n0, 1); n0 += __shfl_xor_sync(0xffffffffu, n0, 2);
                n1 += __shfl_xor_sync(0xffffffffu, n1, 1); n1 += __shfl_xor_sync(0xffffffffu, n1, 2);
                float km = fmaxf(n0, n1), vm = 0.f;
#pragma unroll
                for (int i = 0; i < 4; i++) vm = fmaxf(vm, fmaxf(fabsf(bf_lo(vv[i])), fabsf(bf_hi(vv[i]))));
#pragma unroll
                for (int o = 4; o < 32; o <<= 1) km = fmaxf(km, __shfl_xor_sync(0xffffffffu, km, o));
#pragma unroll
                for (int o = 1; o < 32; o <<= 1) vm = fmaxf(vm, __shfl_xor_sync(0xffffffffu, vm, o));
                __syncwarp();
                if (lane == 0) {
                    const unsigned long long rec = ((unsigned long long)(__float_as_uint(vm) | 0x80000000u) << 32) | __float_as_uint(km);
                    asm volatile("st.release.gpu.global.u64 [%0], %1;" ::"l"(&g_stats[s]), "l"(rec) : "memory");
                    if (wa == 0) TSTAMP(8);
                }
            }
            if (tau == 0) {
                for (int jj = 0; jj < 2; jj++) {
                    mbar_expect_tx(bar(B_W + jj), 32768);
                    tma4d(sb + OFF_V + jj * 32768, &tm_wq, 0, 0, hg * 2, 2 * jj, bar(B_W + jj));
                }
            }
            __syncwarp();
        }
        const int c0 = 4 * b;
        if (wa == 1) {
            float km = 0.f, vm = 0.f;
            {
                unsigned long long rec[4];
                uint32_t spins = 0;
                bool ok;
                do {
                    ok = true;
#pragma unroll
                    for (int i = 0; i < 4; i++) {
                        asm volatile("ld.relaxed.gpu.global.u64 %0, [%1];" : "=l"(rec[i]) : "l"(&g_stats[lane + 32 * i]) : "memory");
                        ok = ok && (rec[i] >> 63);
                    }
                    if (++spins > (1u << 22)) __trap();
                } while (!__all_sync(0xffffffffu, ok));
                asm volatile("fence.acq_rel.gpu;" ::: "memory");
#pragma unroll
                for (int i = 0; i < 4; i++) { km = fmaxf(km, __uint_as_float((uint32_t)rec[i])); vm = fmaxf(vm, __uint_as_float((uint32_t)(rec[i] >> 32) & 0x7FFFFFFFu)); }
            }
            if (lane == 0) {
                TSTAMP(16);
                fence_async_global();
                mbar_wait(bar(B_KVT), 0);
                for (int c = 0; c < 4; c++) {
                    mbar_expect_tx_noarrive(bar(B_KV + c), 8192);
                    bulk_g2s(sb + OFF_K + c * 8192, g_kimg + c * 8192, 8192, bar(B_KV + c));
                }
                for (int c = 4; c < 8; c++) mbar_expect_tx_noarrive(bar(B_KV + c), 8192);
                TSTAMP(28);
            }
#pragma unroll
            for (int o = 1; o < 32; o <<= 1) { km = fmaxf(km, __shfl_xor_sync(0xffffffffu, km, o)); vm = fmaxf(vm, __shfl_xor_sync(0xffffffffu, vm, o)); }
            const bool vdirect = (vm <= 32768.f && vm >= 9.765625e-4f) || vm == 0.f;
            float vs = 1.f;
            if (!vdirect && vm < INFINITY) {
                int e = (int)((__float_as_uint(vm) >> 23) & 0xFF) - 127;
                e = max(-100, min(100, e));
                vs = __uint_as_float((uint32_t)(127 + e - 13) << 23);
            }
            if (lane == 0) {
                asm volatile("st.shared.f32 [%0], %1;" ::"r"(sb + OFF_MISC), "f"(km) : "memory");
                asm volatile("st.shared.f32 [%0], %1;" ::"r"(sb + OFF_MISC + 4), "f"(vs) : "memory");
                mbar_wait(bar(B_QDONE), 0);
                TSTAMP(17);
                for (int c = 0; c < 8; c++) {
                    if (vdirect) {
                        mbar_expect_tx(bar(B_KV + c), 8192);
                        bulk_g2s(sb + OFF_V + (112 - 16 * c) * 256, g_vimg + (112 - 16 * c) * 256, 4096, bar(B_KV + c));
                        bulk_g2s(sb + OFF_VONES + 256 + c * 4096, g_vimg + 32768 + 256 + c * 4096, 4096, bar(B_KV + c));
                    }
                }
            }
            __syncwarp();
            sts32(sb + OFF_VONES + lane * 8, 0x3C003C00u);
            sts32(sb + OFF_VONES + lane * 8 + 4, 0x3C003C00u);
            if (!vdirect) {
                const float inv = 1.f / vs;
                for (int idx = lane; idx < S_LEN * 8; idx += 32) {
                    const int key = idx >> 3, dp = idx & 7;
                    const uint32_t v = __ldcg((const uint32_t*)g_vraw + idx);
                    const uint32_t h = pack_f16(bf_lo(v) * inv, bf_hi(v) * inv);
                    const int st = key >> 4, hf = (key >> 3) & 1;
                    const uint32_t base = (dp < 4) ? (OFF_V + (127 - st) * 256) : (OFF_VONES + 256 + st * 256);
                    sts32(sb + base + hf * 128 + (key & 7) * 16 + (dp & 3) * 4, h);
                }
            }
            fence_async_smem();
            __syncwarp();
            if (lane == 0) {
                mbar_arrive(bar(B_KV + 0));
                if (!vdirect) for (int c = 0; c < 8; c++) mbar_arrive(bar(B_KV + c));
                mbar_wait(bar(B_CONV), 0);
                for (int c = 4; c < 8; c++) bulk_g2s(sb + OFF_K + c * 8192, g_kimg + c * 8192, 8192, bar(B_KV + c));
            }
            __syncwarp();
        } else if (wa == 0) {
            if (lane == 0) {
                prefetch_tm(&tm_wo); prefetch_tm(&tm_o);
                mbar_wait(bar(B_KVT), 0);
                red_release_add(&g_kvt_count[hg], 1);
                TSTAMP(34);
                poll_counter(&g_kvt_count[b >> 5], 32);
                fence_async_global();
                mbar_expect_tx(bar(B_CV), 16384);
                bulk_g2s(sb + C_KVC, g_kvT + (size_t)c0 * S_LEN, 16384, bar(B_CV));
                mbar_wait(bar(B_CONV), 0);
                bulk_s2g(g_zT + (size_t)c0 * S_LEN, sb + C_KVC, 16384);
                bulk_commit();
                for (int jj = 0; jj < 2; jj++) {
                    mbar_expect_tx(bar(B_WO + jj), 32768);
                    tma4d(sb + OFF_X + jj * 32768, &tm_wo, 0, 0, hg * 2, 2 * jj, bar(B_WO + jj));
                }
            }
            __syncwarp();
        }
        {
            const int cg = tau & 15, pr = tau >> 4;
            const int p0 = pb * 64 + pr * 8, ch0 = hg * 128 + cg * 8;
            uint4 qr[8];
#pragma unroll
            for (int i = 0; i < 8; i++) qr[i] = __ldg((const uint4*)(prm.aq + (size_t)(p0 + i) * 512 + ch0));
            if (tau == 0) {
                bulk_wait_all();
                fence_async_global();
                red_release_add(&g_z_count[b >> 5], 1);
                poll_counter(&g_z_count[hg], 32);
                __threadfence();
                if (atomicAdd(&g_done, 1) == 2 * NCTA - 1) {
                    for (int i = 0; i < NCTA; i++) g_stats[i] = 0ull;
                    for (int i = 0; i < 4; i++) { g_kvt_count[i] = 0; g_z_count[i] = 0; }
                    for (int i = 0; i < 32; i++) g_o_count[i] = 0;
                    g_done = 0;
                    __threadfence();
                }
            }
            named_bar(5, 128);
            uint4 zz[8];
#pragma unroll
            for (int c = 0; c < 8; c++) zz[c] = __ldcg((const uint4*)(g_zT + (size_t)(ch0 + c) * S_LEN + p0));
#pragma unroll
            for (int i = 0; i < 8; i++) {
                uint32_t r[4];
#pragma unroll
                for (int k = 0; k < 4; k++) {
                    const uint32_t pr2 = __byte_perm((&zz[2 * k].x)[i >> 1], (&zz[2 * k + 1].x)[i >> 1], (i & 1) ? 0x7632 : 0x5410);
                    r[k] = bmul2((&qr[i].x)[k], pr2);
                }
                *(uint4*)(prm.out + (size_t)(p0 + i) * 1024 + ch0) = make_uint4(r[0], r[1], r[2], r[3]);
            }
        }
        if (tau == 0) TSTAMP(14);
    }
}

typedef CUresult (*EncodeFn)(CUtensorMap*, CUtensorMapDataType, cuuint32_t, void*, const cuuint64_t*, const cuuint64_t*,
                             const cuuint32_t*, const cuuint32_t*, CUtensorMapInterleave, CUtensorMapSwizzle,
                             CUtensorMapL2promotion, CUtensorMapFloatOOBfill);

void make_map(EncodeFn fn, CUtensorMap* tm, const void* ptr, int rank, const cuuint64_t* dims, const cuuint64_t* strides, const cuuint32_t* box, CUtensorMapSwizzle swz) {
    cuuint32_t es[4] = {1, 1, 1, 1};
    fn(tm, CU_TENSOR_MAP_DATA_TYPE_BFLOAT16, rank, const_cast<void*>(ptr), dims, strides, box, es, CU_TENSOR_MAP_INTERLEAVE_NONE, swz,
       CU_TENSOR_MAP_L2_PROMOTION_L2_128B, CU_TENSOR_MAP_FLOAT_OOB_FILL_NONE);
}

}

extern "C" void kernel_launch(void* const* d_in, const int* in_sizes, int n_in, void* d_out, int out_size) {
    (void)in_sizes; (void)n_in; (void)out_size;
    static EncodeFn encode = nullptr;
    static void* o_ptr = nullptr;
    if (!encode) {
        cudaDriverEntryPointQueryResult qres;
        void* fn = nullptr;
        cudaGetDriverEntryPoint("cuTensorMapEncodeTiled", &fn, cudaEnableDefault, &qres);
        encode = (EncodeFn)fn;
        cudaGetSymbolAddress(&o_ptr, g_o);
        cudaFuncSetAttribute(fused_kernel, cudaFuncAttributeMaxDynamicSharedMemorySize, SMEM_TOTAL);
    }
    CUtensorMap tm_x, tm_wq, tm_wo, tm_wk, tm_wv, tm_o, tm_h, tm_k, tm_v;
    {
        const cuuint64_t dims[3] = {64, 2048, 8}, str[2] = {1024, 128};
        const cuuint32_t b64[3] = {64, 64, 2};
        make_map(encode, &tm_x, d_in[6], 3, dims, str, b64, CU_TENSOR_MAP_SWIZZLE_128B);
        make_map(encode, &tm_o, o_ptr, 3, dims, str, b64, CU_TENSOR_MAP_SWIZZLE_128B);
    }
    {
        const cuuint64_t dims[4] = {64, 64, 8, 8}, str[3] = {1024, 128, 65536};
        const cuuint32_t box[4] = {64, 64, 2, 2};
        make_map(encode, &tm_wq, d_in[7], 4, dims, str, box, CU_TENSOR_MAP_SWIZZLE_128B);
        make_map(encode, &tm_wo, d_in[10], 4, dims, str, box, CU_TENSOR_MAP_SWIZZLE_128B);
    }
    {
        const cuuint64_t dims[3] = {16, 256, 2}, str[2] = {32, 8192};
        const cuuint32_t box[3] = {16, 256, 2};
        make_map(encode, &tm_wk, d_in[8], 3, dims, str, box, CU_TENSOR_MAP_SWIZZLE_32B);
        make_map(encode, &tm_wv, d_in[9], 3, dims, str, box, CU_TENSOR_MAP_SWIZZLE_32B);
    }
    {
        const cuuint64_t dims[2] = {32, 512 * 64}, str[1] = {64};
        const cuuint32_t box[2] = {32, 64};
        make_map(encode, &tm_h, d_in[4], 2, dims, str, box, CU_TENSOR_MAP_SWIZZLE_64B);
    }
    {
        const cuuint64_t dims[2] = {512, 2048}, str[1] = {1024};
        const cuuint32_t bk[2] = {128, 67}, bv[2] = {128, 64};
        make_map(encode, &tm_k, d_in[1], 2, dims, str, bk, CU_TENSOR_MAP_SWIZZLE_NONE);
        make_map(encode, &tm_v, d_in[2], 2, dims, str, bv, CU_TENSOR_MAP_SWIZZLE_NONE);
    }
    Params prm;
    prm.aq = (const __nv_bfloat16*)d_in[0];
    prm.ak = (const __nv_bfloat16*)d_in[1];
    prm.av = (const __nv_bfloat16*)d_in[2];
    prm.shift_k = (const __nv_bfloat16*)d_in[3];
    prm.ssm_D = (const __nv_bfloat16*)d_in[5];
    prm.out = (__nv_bfloat16*)d_out;
    fused_kernel<<<NCTA, NTHREADS, SMEM_TOTAL>>>(tm_x, tm_wq, tm_wo, tm_wk, tm_wv, tm_o, tm_h, tm_k, tm_v, prm);
}
```

```cpp
#include <cuda_runtime.h>
#include <cuda_bf16.h>
#include <cuda_fp16.h>
#include <cuda.h>
#include <stdint.h>

#define LATE_WQ
#define TAIL_CH 1
#define KVIN_AFTER 3
namespace {

constexpr int S_LEN = 2048;
constexpr int NCTA = 128;
constexpr int NTHREADS = 640;

constexpr uint32_t OFF_K = 0;
constexpr uint32_t OFF_V = 65536;
constexpr uint32_t OFF_VONES = OFF_V + 32768;
constexpr uint32_t OFF_X = 132096;
constexpr uint32_t OFF_C = 197632;
constexpr uint32_t C_KVC = OFF_C;
constexpr uint32_t S_KT = OFF_K;
constexpr uint32_t S_VT = OFF_K + 17408;
constexpr uint32_t S_H = OFF_K + 36864;
constexpr uint32_t S_Z = OFF_X;
constexpr uint32_t OFF_BAR = 231936;
constexpr uint32_t SMEM_TOTAL = 232448;

enum { B_WKV = 0, B_X = 1, B_QEMPTY = 5, B_QDONE = 7, B_KV = 8, B_WO = 16, B_O = 20, B_ATT = 24, B_H = 25, B_CV = 26, B_W = 27, B_KVT = 31, B_KVIN = 32, B_CONV = 33, B_COUNT = 34 };
constexpr uint32_t OFF_MISC = OFF_BAR + 8 * B_COUNT;

__device__ __align__(1024) uint8_t g_kimg[65536];
__device__ __align__(1024) uint8_t g_vimg[65792];
__device__ __align__(1024) __nv_bfloat16 g_vraw[S_LEN * 16];
__device__ __align__(1024) __nv_bfloat16 g_o[S_LEN * 512];
__device__ __align__(1024) __nv_bfloat16 g_kvT[512 * S_LEN];
__device__ __align__(1024) __nv_bfloat16 g_zT[512 * S_LEN];
__device__ unsigned long long g_stats[NCTA];
__device__ unsigned int g_kvt_count[4];
__device__ unsigned int g_z_count[4];
__device__ unsigned int g_o_count[32];
__device__ unsigned int g_done;
#define TSTAMP(i) do {} while (0)
#define CSTAMP(i) do {} while (0)

__device__ __forceinline__ void wg_fence() { asm volatile("wgmma.fence.sync.aligned;" ::: "memory"); }
__device__ __forceinline__ void wg_commit() { asm volatile("wgmma.commit_group.sync.aligned;" ::: "memory"); }
template <int N> __device__ __forceinline__ void wg_wait() { asm volatile("wgmma.wait_group.sync.aligned %0;" ::"n"(N) : "memory"); }
template <int N> __device__ __forceinline__ void fence_regs(float* r) {
#pragma unroll
    for (int i = 0; i < N; i++) asm volatile("" : "+f"(r[i])::"memory");
}
template <int N> __device__ __forceinline__ void fence_uregs(uint32_t* r) {
#pragma unroll
    for (int i = 0; i < N; i++) asm volatile("" : "+r"(r[i])::"memory");
}
__device__ __forceinline__ uint64_t make_desc(uint32_t saddr, uint32_t lbo, uint32_t sbo, uint32_t swz) {
    return (uint64_t)((saddr & 0x3FFFF) >> 4) | ((uint64_t)(lbo >> 4) << 16) | ((uint64_t)(sbo >> 4) << 32) | ((uint64_t)swz << 62);
}
__device__ __forceinline__ void mbar_init(uint32_t bar, uint32_t count) {
    asm volatile("mbarrier.init.shared::cta.b64 [%0], %1;" ::"r"(bar), "r"(count) : "memory");
}
__device__ __forceinline__ void mbar_expect_tx(uint32_t bar, uint32_t bytes) {
    asm volatile("mbarrier.arrive.expect_tx.shared::cta.b64 _, [%0], %1;" ::"r"(bar), "r"(bytes) : "memory");
}
__device__ __forceinline__ void mbar_expect_tx_noarrive(uint32_t bar, uint32_t bytes) {
    asm volatile("mbarrier.expect_tx.relaxed.cta.shared::cta.b64 [%0], %1;" ::"r"(bar), "r"(bytes) : "memory");
}
__device__ __forceinline__ void mbar_arrive(uint32_t bar) {
    asm volatile("mbarrier.arrive.shared::cta.b64 _, [%0];" ::"r"(bar) : "memory");
}
__device__ __forceinline__ bool mbar_try(uint32_t bar, uint32_t parity) {
    uint32_t ok;
    asm volatile("{\n.reg .pred p;\nmbarrier.try_wait.parity.shared::cta.b64 p, [%1], %2;\nselp.u32 %0, 1, 0, p;\n}\n"
                 : "=r"(ok) : "r"(bar), "r"(parity) : "memory");
    return ok != 0;
}
__device__ __forceinline__ void mbar_wait(uint32_t bar, uint32_t parity) {
    uint32_t spins = 0;
    while (!mbar_try(bar, parity)) {
        if (++spins > (1u << 24)) __trap();
    }
}
__device__ __forceinline__ void mbar_wait_w(uint32_t bar, uint32_t parity) {
    uint32_t spins = 0;
    while (!__all_sync(0xffffffffu, mbar_try(bar, parity))) {
        if (++spins > (1u << 24)) __trap();
    }
}
__device__ __forceinline__ void tma2d(uint32_t dst, const CUtensorMap* tm, int c0, int c1, uint32_t bar) {
    asm volatile("cp.async.bulk.tensor.2d.shared::cluster.global.mbarrier::complete_tx::bytes [%0], [%1, {%3, %4}], [%2];"
                 ::"r"(dst), "l"((uint64_t)tm), "r"(bar), "r"(c0), "r"(c1) : "memory");
}
__device__ __forceinline__ void tma3d(uint32_t dst, const CUtensorMap* tm, int c0, int c1, int c2, uint32_t bar) {
    asm volatile("cp.async.bulk.tensor.3d.shared::cluster.global.mbarrier::complete_tx::bytes [%0], [%1, {%3, %4, %5}], [%2];"
                 ::"r"(dst), "l"((uint64_t)tm), "r"(bar), "r"(c0), "r"(c1), "r"(c2) : "memory");
}
__device__ __forceinline__ void tma4d(uint32_t dst, const CUtensorMap* tm, int c0, int c1, int c2, int c3, uint32_t bar) {
    asm volatile("cp.async.bulk.tensor.4d.shared::cluster.global.mbarrier::complete_tx::bytes [%0], [%1, {%3, %4, %5, %6}], [%2];"
                 ::"r"(dst), "l"((uint64_t)tm), "r"(bar), "r"(c0), "r"(c1), "r"(c2), "r"(c3) : "memory");
}
__device__ __forceinline__ void prefetch_tm(const CUtensorMap* tm) { asm volatile("prefetch.tensormap [%0];" ::"l"((uint64_t)tm) : "memory"); }
__device__ __forceinline__ void bulk_s2g(void* dst, uint32_t src, uint32_t bytes) {
    asm volatile("cp.async.bulk.global.shared::cta.bulk_group [%0], [%1], %2;" ::"l"(dst), "r"(src), "r"(bytes) : "memory");
}
__device__ __forceinline__ void bulk_commit() { asm volatile("cp.async.bulk.commit_group;" ::: "memory"); }
__device__ __forceinline__ void bulk_wait_all() { asm volatile("cp.async.bulk.wait_group 0;" ::: "memory"); }
__device__ __forceinline__ void fence_async_global() { asm volatile("fence.proxy.async.global;" ::: "memory"); }
__device__ __forceinline__ void bulk_g2s(uint32_t dst, const void* src, uint32_t bytes, uint32_t bar) {
    asm volatile("cp.async.bulk.shared::cluster.global.mbarrier::complete_tx::bytes [%0], [%1], %2, [%3];"
                 ::"r"(dst), "l"(src), "r"(bytes), "r"(bar) : "memory");
}
__device__ __forceinline__ void fence_async_smem() { asm volatile("fence.proxy.async.shared::cta;" ::: "memory"); }
__device__ __forceinline__ void named_bar(int id, int n) { asm volatile("bar.sync %0, %1;" ::"r"(id), "r"(n) : "memory"); }
__device__ __forceinline__ bool named_bar_and(int id, int n, bool pred) {
    uint32_t r;
    asm volatile("{\n.reg .pred p, q;\nsetp.ne.u32 p, %3, 0;\nbarrier.cta.red.and.pred q, %1, %2, p;\nselp.u32 %0, 1, 0, q;\n}\n"
                 : "=r"(r) : "r"(id), "r"(n), "r"((uint32_t)pred) : "memory");
    return r != 0;
}
__device__ __forceinline__ unsigned int ld_acquire(const unsigned int* p) {
    unsigned int v;
    asm volatile("ld.acquire.gpu.global.u32 %0, [%1];" : "=r"(v) : "l"(p) : "memory");
    return v;
}
__device__ __forceinline__ void red_release_add(unsigned int* p, unsigned int v) {
    asm volatile("red.release.gpu.global.add.u32 [%0], %1;" ::"l"(p), "r"(v) : "memory");
}
__device__ __forceinline__ void poll_counter(const unsigned int* p, unsigned int target) {
    uint32_t spins = 0;
    while (ld_acquire(p) < target) {
        if (++spins > (1u << 22)) __trap();
    }
}
__device__ __forceinline__ float ex2f(float x) { float y; asm("ex2.approx.ftz.f32 %0, %1;" : "=f"(y) : "f"(x)); return y; }
__device__ __forceinline__ uint32_t pack_f16(float lo, float hi) { uint32_t r; asm("cvt.rn.f16x2.f32 %0, %1, %2;" : "=r"(r) : "f"(hi), "f"(lo)); return r; }
__device__ __forceinline__ uint32_t pack_bf16(float lo, float hi) { uint32_t r; asm("cvt.rn.bf16x2.f32 %0, %1, %2;" : "=r"(r) : "f"(hi), "f"(lo)); return r; }
__device__ __forceinline__ float bf_lo(uint32_t v) { return __uint_as_float(v << 16); }
__device__ __forceinline__ float bf_hi(uint32_t v) { return __uint_as_float(v & 0xFFFF0000u); }
__device__ __forceinline__ uint32_t hfma2(uint32_t a, uint32_t b, uint32_t c) { uint32_t r; asm("fma.rn.f16x2 %0, %1, %2, %3;" : "=r"(r) : "r"(a), "r"(b), "r"(c)); return r; }
__device__ __forceinline__ uint32_t bmul2(uint32_t a, uint32_t b) { uint32_t r; asm("mul.rn.bf16x2 %0, %1, %2;" : "=r"(r) : "r"(a), "r"(b)); return r; }
__device__ __forceinline__ uint32_t badd2(uint32_t a, uint32_t b) { uint32_t r; asm("add.rn.bf16x2 %0, %1, %2;" : "=r"(r) : "r"(a), "r"(b)); return r; }
template <int LUT> __device__ __forceinline__ uint32_t lop3(uint32_t a, uint32_t b, uint32_t c) {
    uint32_t r; asm("lop3.b32 %0, %1, %2, %3, %4;" : "=r"(r) : "r"(a), "r"(b), "r"(c), "n"(LUT)); return r;
}
__device__ __forceinline__ uint32_t lds32(uint32_t a) { uint32_t v; asm volatile("ld.shared.u32 %0, [%1];" : "=r"(v) : "r"(a)); return v; }
__device__ __forceinline__ float ldsf(uint32_t a) { float v; asm volatile("ld.shared.f32 %0, [%1];" : "=f"(v) : "r"(a)); return v; }
__device__ __forceinline__ uint4 lds128(uint32_t a) { uint4 v; asm volatile("ld.shared.v4.u32 {%0,%1,%2,%3}, [%4];" : "=r"(v.x), "=r"(v.y), "=r"(v.z), "=r"(v.w) : "r"(a)); return v; }
__device__ __forceinline__ void lds64(uint32_t a, uint32_t& x, uint32_t& y) { asm volatile("ld.shared.v2.u32 {%0,%1}, [%2];" : "=r"(x), "=r"(y) : "r"(a)); }
__device__ __forceinline__ void sts32(uint32_t a, uint32_t v) { asm volatile("st.shared.u32 [%0], %1;" ::"r"(a), "r"(v) : "memory"); }
__device__ __forceinline__ void sts64f(uint32_t a, float x, float y) { asm volatile("st.shared.v2.f32 [%0], {%1,%2};" ::"r"(a), "f"(x), "f"(y) : "memory"); }
__device__ __forceinline__ void sts128(uint32_t a, uint32_t x, uint32_t y, uint32_t z, uint32_t w) {
    asm volatile("st.shared.v4.u32 [%0], {%1,%2,%3,%4};" ::"r"(a), "r"(x), "r"(y), "r"(z), "r"(w) : "memory");
}

__device__ __forceinline__ void wg_ss_n32_tb(float* d, uint64_t descA, uint64_t descB) {
    asm volatile("wgmma.mma_async.sync.aligned.m64n32k16.f32.bf16.bf16 {%0,%1,%2,%3,%4,%5,%6,%7,%8,%9,%10,%11,%12,%13,%14,%15}, %16, %17, 1, 1, 1, 0, 1;\n"
        : "+f"(d[0]), "+f"(d[1]), "+f"(d[2]), "+f"(d[3]), "+f"(d[4]), "+f"(d[5]), "+f"(d[6]), "+f"(d[7]), "+f"(d[8]), "+f"(d[9]), "+f"(d[10]), "+f"(d[11]), "+f"(d[12]), "+f"(d[13]), "+f"(d[14]), "+f"(d[15])
        : "l"(descA), "l"(descB));
}
__device__ __forceinline__ void wg_qk_n64(float* d, const uint32_t* a, uint64_t desc) {
    asm volatile("wgmma.mma_async.sync.aligned.m64n64k16.f32.bf16.bf16 {%0,%1,%2,%3,%4,%5,%6,%7,%8,%9,%10,%11,%12,%13,%14,%15,%16,%17,%18,%19,%20,%21,%22,%23,%24,%25,%26,%27,%28,%29,%30,%31}, {%32,%33,%34,%35}, %36, 0, 1, 1, 0;\n"
        : "+f"(d[0]), "+f"(d[1]), "+f"(d[2]), "+f"(d[3]), "+f"(d[4]), "+f"(d[5]), "+f"(d[6]), "+f"(d[7]), "+f"(d[8]), "+f"(d[9]), "+f"(d[10]), "+f"(d[11]), "+f"(d[12]), "+f"(d[13]), "+f"(d[14]), "+f"(d[15]), "+f"(d[16]), "+f"(d[17]), "+f"(d[18]), "+f"(d[19]), "+f"(d[20]), "+f"(d[21]), "+f"(d[22]), "+f"(d[23]), "+f"(d[24]), "+f"(d[25]), "+f"(d[26]), "+f"(d[27]), "+f"(d[28]), "+f"(d[29]), "+f"(d[30]), "+f"(d[31])
        : "r"(a[0]), "r"(a[1]), "r"(a[2]), "r"(a[3]), "l"(desc));
}
__device__ __forceinline__ void wg_pv_n24(float* d, const uint32_t* a, uint64_t desc) {
    asm volatile("wgmma.mma_async.sync.aligned.m64n24k16.f32.f16.f16 {%0,%1,%2,%3,%4,%5,%6,%7,%8,%9,%10,%11}, {%12,%13,%14,%15}, %16, 1, 1, 1, 1;\n"
        : "+f"(d[0]), "+f"(d[1]), "+f"(d[2]), "+f"(d[3]), "+f"(d[4]), "+f"(d[5]), "+f"(d[6]), "+f"(d[7]), "+f"(d[8]), "+f"(d[9]), "+f"(d[10]), "+f"(d[11])
        : "r"(a[0]), "r"(a[1]), "r"(a[2]), "r"(a[3]), "l"(desc));
}
__device__ __forceinline__ void wg_cv_n32(float* d, const uint32_t* a, uint64_t desc) {
    asm volatile("wgmma.mma_async.sync.aligned.m64n32k16.f32.bf16.bf16 {%0,%1,%2,%3,%4,%5,%6,%7,%8,%9,%10,%11,%12,%13,%14,%15}, {%16,%17,%18,%19}, %20, 1, 1, 1, 0;\n"
        : "+f"(d[0]), "+f"(d[1]), "+f"(d[2]), "+f"(d[3]), "+f"(d[4]), "+f"(d[5]), "+f"(d[6]), "+f"(d[7]), "+f"(d[8]), "+f"(d[9]), "+f"(d[10]), "+f"(d[11]), "+f"(d[12]), "+f"(d[13]), "+f"(d[14]), "+f"(d[15])
        : "r"(a[0]), "r"(a[1]), "r"(a[2]), "r"(a[3]), "l"(desc));
}
__device__ __forceinline__ void wg_cv_n64(float* d, const uint32_t* a, uint64_t desc) {
    asm volatile("wgmma.mma_async.sync.aligned.m64n64k16.f32.bf16.bf16 {%0,%1,%2,%3,%4,%5,%6,%7,%8,%9,%10,%11,%12,%13,%14,%15,%16,%17,%18,%19,%20,%21,%22,%23,%24,%25,%26,%27,%28,%29,%30,%31}, {%32,%33,%34,%35}, %36, 1, 1, 1, 0;\n"
        : "+f"(d[0]), "+f"(d[1]), "+f"(d[2]), "+f"(d[3]), "+f"(d[4]), "+f"(d[5]), "+f"(d[6]), "+f"(d[7]), "+f"(d[8]), "+f"(d[9]), "+f"(d[10]), "+f"(d[11]), "+f"(d[12]), "+f"(d[13]), "+f"(d[14]), "+f"(d[15]), "+f"(d[16]), "+f"(d[17]), "+f"(d[18]), "+f"(d[19]), "+f"(d[20]), "+f"(d[21]), "+f"(d[22]), "+f"(d[23]), "+f"(d[24]), "+f"(d[25]), "+f"(d[26]), "+f"(d[27]), "+f"(d[28]), "+f"(d[29]), "+f"(d[30]), "+f"(d[31])
        : "r"(a[0]), "r"(a[1]), "r"(a[2]), "r"(a[3]), "l"(desc));
}

template <int N> __device__ __forceinline__ void wg_cv(float* d, const uint32_t* a, uint64_t desc);
template <> __device__ __forceinline__ void wg_cv<32>(float* d, const uint32_t* a, uint64_t s) { wg_cv_n32(d, a, s); }
template <> __device__ __forceinline__ void wg_cv<64>(float* d, const uint32_t* a, uint64_t s) { wg_cv_n64(d, a, s); }

constexpr uint32_t POLYMASK = 0xB5B5u;
__device__ __forceinline__ void softmax_fast(const float* s, uint32_t* p, uint32_t mlo) {
    const uint32_t C3 = 0x2cfb2cfbu, C2 = 0x9fec9fecu, C1 = 0x37a837a8u, C0 = 0x37383738u;
#pragma unroll
    for (int i = 0; i < 16; i++) {
        const float s0 = s[2 * i], s1 = s[2 * i + 1];
        if ((POLYMASK >> i) & 1) {
            const float t0 = s0 + 12303.0f, t1 = s1 + 12303.0f;
            const uint32_t T = __byte_perm(__float_as_uint(t0), __float_as_uint(t1), 0x5410);
            const uint32_t U = lop3<0xEA>(T, mlo, 0x3C003C00u);
            uint32_t h = hfma2(U, C3, C2);
            h = hfma2(h, U, C1);
            h = hfma2(h, U, C0);
            p[i] = lop3<0xE4>(h, T, 0x03FF03FFu);
        } else {
            p[i] = pack_f16(ex2f(s0), ex2f(s1));
        }
    }
}

__device__ __forceinline__ void gemm_chunk(float* acc, uint32_t a_addr, uint32_t b_addr) {
    const uint64_t da = make_desc(a_addr, 16, 1024, 1);
    const uint64_t db = make_desc(b_addr, 8192, 1024, 1);
#pragma unroll
    for (int ks = 0; ks < 4; ks++) wg_ss_n32_tb(acc, da + ks * 2, db + ks * 128);
}

__device__ __forceinline__ uint32_t smem_inc(uint32_t addr) {
    uint32_t old;
    asm volatile("atom.acq_rel.cta.shared.add.u32 %0, [%1], 1;" : "=r"(old) : "r"(addr) : "memory");
    return old;
}
__device__ __forceinline__ void wo_half(uint32_t sb, const CUtensorMap* tm_wo, int hg) {
    if (smem_inc(sb + OFF_MISC + 8) == 3) {
        mbar_expect_tx(sb + OFF_BAR + 8 * (B_WO + 2), 32768);
        tma4d(sb + OFF_K, tm_wo, 0, 0, hg * 2, 4, sb + OFF_BAR + 8 * (B_WO + 2));
    }
}

__device__ __forceinline__ void kv_tiles_load(uint32_t sb, const CUtensorMap* tm_k, const CUtensorMap* tm_v, int pb, int hg) {
    const uint32_t br = sb + OFF_BAR + 8 * B_KVIN;
    mbar_expect_tx(br, 67 * 256 + 64 * 256);
    tma2d(sb + S_KT, tm_k, hg * 128, pb * 64 - 3, br);
    tma2d(sb + S_VT, tm_v, hg * 128, pb * 64, br);
}

struct Params {
    const __nv_bfloat16 *aq, *ak, *av, *shift_k, *ssm_D;
    __nv_bfloat16* out;
};

template <int NQ>
__device__ __forceinline__ void conv_phase(float* Dn, uint32_t zaddr, uint64_t hdesc) {
    uint32_t a[2][16];
#pragma unroll
    for (int st = 0; st < 8; st++) {
        uint32_t* aa = a[st & 1];
        if (st >= 2) wg_wait<1>();
#pragma unroll
        for (int u = 0; u < 2; u++) {
            const uint32_t z = zaddr + (st * 2 + u) * 256;
            lds64(z, aa[8 * u + 0], aa[8 * u + 1]);      lds64(z - 32, aa[8 * u + 2], aa[8 * u + 3]);
            lds64(z - 64, aa[8 * u + 4], aa[8 * u + 5]); lds64(z - 96, aa[8 * u + 6], aa[8 * u + 7]);
        }
        wg_fence();
#pragma unroll
        for (int u = 0; u < 2; u++) {
            const int qi = st * 2 + u;
            wg_cv<NQ>(Dn, &aa[8 * u], hdesc - qi * 8);
            wg_cv<NQ>(Dn, &aa[8 * u + 4], hdesc - qi * 8 + 2);
        }
        wg_commit();
    }
    wg_wait<0>();
    fence_regs<NQ / 2>(Dn);
}

__device__ __forceinline__ void conv_channel(uint32_t kvc, uint32_t zb, uint32_t hb, int tau, int wa, int g, int t, int nb, float dsc_in) {
            {
                const uint32_t src = kvc + tau * 32;
                const uint4 u0 = lds128(src), u1 = lds128(src + 16);
                const uint32_t prev = tau > 0 ? lds32(src - 4) : 0u;
                const uint32_t zd = zb + (32 + tau * 16) * 4;
                sts128(zd,      __byte_perm(u0.x, prev, 0x7610), __byte_perm(u0.x, u0.x, 0x1032), __byte_perm(u0.y, u0.x, 0x7610), __byte_perm(u0.y, u0.y, 0x1032));
                sts128(zd + 16, __byte_perm(u0.z, u0.y, 0x7610), __byte_perm(u0.z, u0.z, 0x1032), __byte_perm(u0.w, u0.z, 0x7610), __byte_perm(u0.w, u0.w, 0x1032));
                sts128(zd + 32, __byte_perm(u1.x, u0.w, 0x7610), __byte_perm(u1.x, u1.x, 0x1032), __byte_perm(u1.y, u1.x, 0x7610), __byte_perm(u1.y, u1.y, 0x1032));
                sts128(zd + 48, __byte_perm(u1.z, u1.y, 0x7610), __byte_perm(u1.z, u1.z, 0x1032), __byte_perm(u1.w, u1.z, 0x7610), __byte_perm(u1.w, u1.w, 0x1032));
                if (tau < 32) sts32(zb + tau * 4, 0u);
            }
            named_bar(nb, 128);
            float D[32];
#pragma unroll
            for (int i = 0; i < 32; i++) D[i] = 0.f;
            fence_regs<32>(D);
            const uint32_t z0 = zb + (32 + 32 * (wa >> 1) + 16 * (wa & 1) + 2 * g - 2 * t) * 4;
            const uint64_t hd = make_desc(hb + 2048, 16, 512, 2);
            conv_phase<64>(D, z0, hd);
            float E[16];
#pragma unroll
            for (int i = 0; i < 16; i++) asm volatile("mov.f32 %0, %1;" : "=f"(E[i]) : "f"(D[16 + i]));
            conv_phase<32>(E, z0 + 4096, hd);
            const int bb0 = 16 * (wa & 1) + 2 * g;
            const int xsw = (g & 3) << 3;
            {
                const uint32_t xb = zb + (wa >> 1) * 4096;
#pragma unroll
                for (int jn = 0; jn < 4; jn++) {
#pragma unroll
                    for (int r = 0; r < 2; r++) {
                        const float v0 = (wa < 2) ? E[4 * jn + 2 * r] : D[4 * jn + 2 * r];
                        const float v1 = (wa < 2) ? E[4 * jn + 2 * r + 1] : D[4 * jn + 2 * r + 1];
                        sts64f(xb + ((bb0 + r) * 32 + ((8 * jn + 2 * t) ^ xsw)) * 4, v0, v1);
                    }
                }
            }
            named_bar(nb, 128);
            {
                const float dsc = dsc_in;
                const uint32_t xb = zb + ((wa >> 1) ^ 1) * 4096;
#pragma unroll
                for (int jn = 0; jn < 4; jn++) {
#pragma unroll
                    for (int e = 0; e < 2; e++) {
                        const int n = 8 * jn + 2 * t + e;
                        float y0, y1; int m, rn;
                        if (wa < 2) { y0 = D[4 * jn + e]; y1 = D[4 * jn + 2 + e]; m = n; rn = n - 1; }
                        else {
                            const bool last = (jn == 3 && e == 1) && (t == 3);
                            y0 = last ? D[13] : E[4 * jn + e]; y1 = last ? D[15] : E[4 * jn + 2 + e];
                            m = last ? 32 : 33 + n; rn = m - 32;
                        }
                        if (rn >= 0) {
                            y0 += ldsf(xb + (bb0 * 32 + (rn ^ xsw)) * 4);
                            y1 += ldsf(xb + ((bb0 + 1) * 32 + (rn ^ xsw)) * 4);
                        }
                        const uint32_t addr = kvc + (32 * m + bb0) * 2;
                        const uint32_t kv = lds32(addr);
                        const uint32_t yb = pack_bf16(y0, y1);
                        const uint32_t kd = pack_bf16(bf_lo(kv) * dsc, bf_hi(kv) * dsc);
                        sts32(addr, badd2(yb, kd));
                    }
                }
                fence_async_smem();
            }
}

__global__ void __launch_bounds__(NTHREADS, 1)
fused_kernel(const __grid_constant__ CUtensorMap tm_x,
             const __grid_constant__ CUtensorMap tm_wq, const __grid_constant__ CUtensorMap tm_wo,
             const __grid_constant__ CUtensorMap tm_wk, const __grid_constant__ CUtensorMap tm_wv,
             const __grid_constant__ CUtensorMap tm_o, const __grid_constant__ CUtensorMap tm_h,
             const __grid_constant__ CUtensorMap tm_k, const __grid_constant__ CUtensorMap tm_v, const Params prm) {
    extern __shared__ __align__(1024) uint8_t smem_raw[];
    const uint32_t sb = (uint32_t)__cvta_generic_to_shared(smem_raw);
    const int warp_id = __shfl_sync(0xffffffffu, threadIdx.x >> 5, 0);
    const int lane = threadIdx.x & 31;
    const int g = lane >> 2, t = lane & 3;
    const int b = blockIdx.x, pb = b >> 2, hg = b & 3;
    auto bar = [&](int i) { return sb + OFF_BAR + 8 * i; };

    if (threadIdx.x == 512) {
        TSTAMP(0);
        prefetch_tm(&tm_x); prefetch_tm(&tm_wq); prefetch_tm(&tm_wk); prefetch_tm(&tm_wv);
        mbar_init(bar(B_WKV), 1);
        for (int j = 0; j < 4; j++) { mbar_init(bar(B_X + j), 1); mbar_init(bar(B_W + j), 1); mbar_init(bar(B_WO + j), 1); mbar_init(bar(B_O + j), 1); }
        sts32(sb + OFF_MISC + 8, 0u); sts32(sb + OFF_MISC + 12, 0u); sts32(sb + OFF_MISC + 16, 0u);
        for (int j = 0; j < 8; j++) mbar_init(bar(B_KV + j), j == 0 ? 2 : 1);
        mbar_init(bar(B_QEMPTY), 4); mbar_init(bar(B_QEMPTY + 1), 4);
        mbar_init(bar(B_QDONE), 4); mbar_init(bar(B_ATT), 4);
        mbar_init(bar(B_H), 1); mbar_init(bar(B_CV), 1); mbar_init(bar(B_KVT), 512); mbar_init(bar(B_KVIN), 1); mbar_init(bar(B_CONV), 4);
        asm volatile("fence.mbarrier_init.release.cluster;" ::: "memory");
    }

    if (warp_id < 16) {
        const int w = warp_id >> 2, wq = warp_id & 3;
        __syncthreads();
        float acc[16];
#pragma unroll
        for (int i = 0; i < 16; i++) acc[i] = 0.f;
        fence_regs<16>(acc);
        const uint32_t bcol = (w >> 1) * 8192 + (w & 1) * 64;
        sts128(sb + S_H + w * 6144 + (threadIdx.x & 127) * 16, 0u, 0u, 0u, 0u);
        fence_async_smem();
#pragma unroll 1
        for (int jj = 0; jj < 2; jj++) {
            mbar_wait_w(bar(B_X + jj), 0);
            mbar_wait_w(bar(B_W + jj), 0);
            if (threadIdx.x == 0) TSTAMP(jj == 0 ? 23 : jj == 1 ? 24 : jj == 2 ? 26 : 27);
            wg_fence();
            gemm_chunk(acc, sb + OFF_X + jj * 16384, sb + OFF_V + (jj & 1) * 32768 + bcol);
            gemm_chunk(acc, sb + OFF_X + jj * 16384 + 8192, sb + OFF_V + (jj & 1) * 32768 + 16384 + bcol);
            wg_commit();
            wg_wait<0>();
            if (jj < 2 && (threadIdx.x & 127) == 0) {
                if (smem_inc(sb + OFF_MISC + 12 + 4 * jj) == 3) {
                    mbar_expect_tx(bar(B_W + jj + 2), 32768);
                    tma4d(sb + OFF_V + jj * 32768, &tm_wq, 0, 0, hg * 2, 2 * (jj + 2), bar(B_W + jj + 2));
                }
            }
        }
        fence_regs<16>(acc);
        {
            const int kch0 = hg * 128 + lane * 4;
            const uint4 s0 = __ldg((const uint4*)(prm.shift_k + kch0 * 4));
            const uint4 s1 = __ldg((const uint4*)(prm.shift_k + kch0 * 4) + 1);
            uint32_t wA[4], wB[4];
            wA[0] = __byte_perm(s0.x, s0.z, 0x5410); wA[1] = __byte_perm(s0.x, s0.z, 0x7632);
            wA[2] = __byte_perm(s0.y, s0.w, 0x5410); wA[3] = __byte_perm(s0.y, s0.w, 0x7632);
            wB[0] = __byte_perm(s1.x, s1.z, 0x5410); wB[1] = __byte_perm(s1.x, s1.z, 0x7632);
            wB[2] = __byte_perm(s1.y, s1.w, 0x5410); wB[3] = __byte_perm(s1.y, s1.w, 0x7632);
            mbar_wait_w(bar(B_KVIN), 0);
            const uint32_t kb = sb + S_KT + warp_id * 4 * 256 + lane * 8, vb = sb + S_VT + warp_id * 4 * 256 + lane * 8;
            uint32_t ka[7], kq[7], xa[4], xb[4];
#pragma unroll
            for (int i = 0; i < 7; i++) lds64(kb + i * 256, ka[i], kq[i]);
#pragma unroll
            for (int i = 0; i < 4; i++) {
                uint32_t va, vq;
                lds64(vb + i * 256, va, vq);
                xa[i] = bmul2(badd2(badd2(badd2(bmul2(ka[i], wA[3]), bmul2(ka[i + 1], wA[2])), bmul2(ka[i + 2], wA[1])), bmul2(ka[i + 3], wA[0])), va);
                xb[i] = bmul2(badd2(badd2(badd2(bmul2(kq[i], wB[3]), bmul2(kq[i + 1], wB[2])), bmul2(kq[i + 2], wB[1])), bmul2(kq[i + 3], wB[0])), vq);
            }
            uint2* dst = (uint2*)(g_kvT + (size_t)kch0 * S_LEN + pb * 64 + warp_id * 4);
            dst[0] = make_uint2(__byte_perm(xa[0], xa[1], 0x5410), __byte_perm(xa[2], xa[3], 0x5410));
            dst[S_LEN / 4] = make_uint2(__byte_perm(xa[0], xa[1], 0x7632), __byte_perm(xa[2], xa[3], 0x7632));
            dst[2 * (S_LEN / 4)] = make_uint2(__byte_perm(xb[0], xb[1], 0x5410), __byte_perm(xb[2], xb[3], 0x5410));
            dst[3 * (S_LEN / 4)] = make_uint2(__byte_perm(xb[0], xb[1], 0x7632), __byte_perm(xb[2], xb[3], 0x7632));
            mbar_arrive(bar(B_KVT));
        }
#pragma unroll 1
        for (int jj = 2; jj < 4; jj++) {
            mbar_wait_w(bar(B_X + jj), 0);
            mbar_wait_w(bar(B_W + jj), 0);
            if (threadIdx.x == 0) TSTAMP(jj == 0 ? 23 : jj == 1 ? 24 : jj == 2 ? 26 : 27);
            wg_fence();
            gemm_chunk(acc, sb + OFF_X + jj * 16384, sb + OFF_V + (jj & 1) * 32768 + bcol);
            gemm_chunk(acc, sb + OFF_X + jj * 16384 + 8192, sb + OFF_V + (jj & 1) * 32768 + 16384 + bcol);
            wg_commit();
            wg_wait<0>();
            if (jj < 2 && (threadIdx.x & 127) == 0) {
                if (smem_inc(sb + OFF_MISC + 12 + 4 * jj) == 3) {
                    mbar_expect_tx(bar(B_W + jj + 2), 32768);
                    tma4d(sb + OFF_V + jj * 32768, &tm_wq, 0, 0, hg * 2, 2 * (jj + 2), bar(B_W + jj + 2));
                }
            }
        }
        fence_regs<16>(acc);
        if ((threadIdx.x & 127) == 0) { mbar_arrive(bar(B_QDONE)); if (w == 0) TSTAMP(1); }
        uint32_t qa[2][4];
        float qn[2];
        {
            const float c = 0.25f * 1.4426950408889634f;
#pragma unroll
            for (int hh = 0; hh < 2; hh++) {
                float n0 = 0.f, n1 = 0.f;
#pragma unroll
                for (int i = 0; i < 4; i++) {
                    const uint32_t qb = pack_bf16(acc[8 * hh + 2 * i], acc[8 * hh + 2 * i + 1]);
                    const uint32_t qs = pack_bf16(bf_lo(qb) * c, bf_hi(qb) * c);
                    qa[hh][i] = qs;
                    const float e = bf_lo(qs) * bf_lo(qs) + bf_hi(qs) * bf_hi(qs);
                    if (i & 1) n1 += e; else n0 += e;
                }
                n0 += __shfl_xor_sync(0xffffffffu, n0, 1); n0 += __shfl_xor_sync(0xffffffffu, n0, 2);
                n1 += __shfl_xor_sync(0xffffffffu, n1, 1); n1 += __shfl_xor_sync(0xffffffffu, n1, 2);
                qn[hh] = fmaxf(n0, n1);
            }
        }
        const uint32_t qpark = sb + OFF_C + 16384 + threadIdx.x * 32;
        sts128(qpark, qa[0][0], qa[0][1], qa[0][2], qa[0][3]);
        sts128(qpark + 16, qa[1][0], qa[1][1], qa[1][2], qa[1][3]);
        {
            const float dsc = __bfloat162float(prm.ssm_D[4 * b + w]);
            mbar_wait_w(bar(B_QDONE), 0);
            mbar_wait_w(bar(B_H), 0);
            mbar_wait_w(bar(B_CV), 0);
            if (threadIdx.x == 0) TSTAMP(9);
            conv_channel(sb + C_KVC + w * 4096, sb + S_Z + w * 8448, sb + S_H + w * 6144, threadIdx.x & 127, wq, g, t, 1 + w, dsc);
            named_bar(1 + w, 128);
            if ((threadIdx.x & 127) == 0) { mbar_arrive(bar(B_CONV)); if (w == 0) TSTAMP(10); }
        }
        uint32_t mlo = 0x03FF03FFu; asm volatile("" : "+r"(mlo));
        const uint64_t kdesc0 = make_desc(sb + OFF_K, 128, 256, 0);
        const uint64_t vdesc0 = make_desc(sb + OFF_VONES - 256, 128, 256, 0);
        constexpr uint64_t VSTEP = ((uint64_t)16 << 32) - 16;
        mbar_wait_w(bar(B_KV + 0), 0);
        if ((threadIdx.x & 127) == 0 && w == 0) TSTAMP(2);
        const float kmax2 = ldsf(sb + OFF_MISC);
        const bool fast0 = __all_sync(0xffffffffu, named_bar_and(1 + w, 128, qn[0] * kmax2 <= 193.0f));
        const bool fast1 = __all_sync(0xffffffffu, named_bar_and(1 + w, 128, qn[1] * kmax2 <= 193.0f));
        uint32_t a[4];
        { const uint4 v = lds128(qpark); a[0] = v.x; a[1] = v.y; a[2] = v.z; a[3] = v.w; }
#pragma unroll 1
        for (int hh = 0; hh < 2; hh++) {
            const bool fast = hh ? fast1 : fast0;
            float S[32], O[12];
#pragma unroll
            for (int i = 0; i < 12; i++) O[i] = 0.f;
#pragma unroll
            for (int i = 0; i < 32; i++) S[i] = 0.f;
            fence_regs<12>(O); fence_regs<32>(S);
            wg_fence();
            wg_qk_n64(S, a, kdesc0);
            wg_commit();
            wg_wait<0>();
            uint64_t kd = kdesc0 + 128, vd = vdesc0;
            if (fast) {
                uint32_t P[16];
#pragma unroll 1
                for (int c = 0; c < 8; c++) {
                    if (c < 7) mbar_wait_w(bar(B_KV + c + 1), 0);
#pragma unroll 1
                    for (int j = 0; j < 4; j++) {
                        fence_regs<32>(S);
                        softmax_fast(S, P, mlo);
                        fence_regs<32>(S);
                        wg_fence();
                        wg_qk_n64(S, a, kd);
#pragma unroll
                        for (int i = 0; i < 4; i++) wg_pv_n24(O, &P[4 * i], vd + i * VSTEP);
                        wg_commit();
                        wg_wait<0>();
                        kd += 128; vd += 4 * VSTEP;
                    }
                    if (hh == 1 && c == 3 && (threadIdx.x & 127) == 0) wo_half(sb, &tm_wo, hg);
                }
            } else {
                uint32_t P[16];
                float m0 = -INFINITY, m1 = -INFINITY;
#pragma unroll 1
                for (int c = 0; c < 8; c++) {
                    if (c < 7) mbar_wait_w(bar(B_KV + c + 1), 0);
#pragma unroll 1
                    for (int j = 0; j < 4; j++) {
                        fence_regs<32>(S); fence_regs<12>(O);
                        float x0 = m0, x1 = m1;
#pragma unroll
                        for (int i = 0; i < 8; i++) {
                            x0 = fmaxf(x0, fmaxf(S[4 * i], S[4 * i + 1]));
                            x1 = fmaxf(x1, fmaxf(S[4 * i + 2], S[4 * i + 3]));
                        }
                        x0 = fmaxf(x0, __shfl_xor_sync(0xffffffffu, x0, 1)); x0 = fmaxf(x0, __shfl_xor_sync(0xffffffffu, x0, 2));
                        x1 = fmaxf(x1, __shfl_xor_sync(0xffffffffu, x1, 1)); x1 = fmaxf(x1, __shfl_xor_sync(0xffffffffu, x1, 2));
                        const float r0 = ex2f(m0 - x0), r1 = ex2f(m1 - x1);
                        m0 = x0; m1 = x1;
#pragma unroll
                        for (int i = 0; i < 3; i++) { O[4 * i] *= r0; O[4 * i + 1] *= r0; O[4 * i + 2] *= r1; O[4 * i + 3] *= r1; }
#pragma unroll
                        for (int i = 0; i < 8; i++) {
                            P[2 * i] = pack_f16(ex2f(S[4 * i] - m0), ex2f(S[4 * i + 1] - m0));
                            P[2 * i + 1] = pack_f16(ex2f(S[4 * i + 2] - m1), ex2f(S[4 * i + 3] - m1));
                        }
                        fence_regs<32>(S); fence_regs<12>(O);
                        wg_fence();
                        wg_qk_n64(S, a, kd);
#pragma unroll
                        for (int i = 0; i < 4; i++) wg_pv_n24(O, &P[4 * i], vd + i * VSTEP);
                        wg_commit();
                        wg_wait<0>();
                        kd += 128; vd += 4 * VSTEP;
                    }
                    if (hh == 1 && c == 3 && (threadIdx.x & 127) == 0) wo_half(sb, &tm_wo, hg);
                }
            }
            fence_regs<12>(O);
            const float vscale = ldsf(sb + OFF_MISC + 4);
            const float i0 = __fdividef(vscale, O[4]), i1 = __fdividef(vscale, O[6]);
            const int row = pb * 64 + wq * 16 + g;
            uint32_t* o0 = (uint32_t*)(g_o + (size_t)row * 512 + (hg * 8 + 2 * w + hh) * 16) + t;
            uint32_t* o1 = o0 + 8 * 256;
            o0[0] = pack_bf16(O[0] * i0, O[1] * i0);
            o0[4] = pack_bf16(O[8] * i0, O[9] * i0);
            o1[0] = pack_bf16(O[2] * i1, O[3] * i1);
            o1[4] = pack_bf16(O[10] * i1, O[11] * i1);
            if ((threadIdx.x & 127) == 0 && w == 0) { TSTAMP(3 + hh); CSTAMP(40 + hh); }
            { const uint4 v = lds128(qpark + 16); a[0] = v.x; a[1] = v.y; a[2] = v.z; a[3] = v.w; }
        }
        named_bar(1 + w, 128);
        if ((threadIdx.x & 127) == 0) {
            red_release_add(&g_o_count[pb], 1);
            mbar_arrive(bar(B_ATT));
        }
        if (threadIdx.x == 0) {
            TSTAMP(30);
            mbar_wait(bar(B_ATT), 0);
            TSTAMP(31);
            poll_counter(&g_o_count[pb], 16);
            TSTAMP(18);
            fence_async_global();
            for (int jj = 0; jj < 4; jj++) {
                mbar_expect_tx(bar(B_O + jj), 16384);
                tma3d(sb + OFF_V + jj * 16384, &tm_o, 0, pb * 64, 2 * jj, bar(B_O + jj));
            }
            __threadfence();
            if (atomicAdd(&g_done, 1) == 2 * NCTA - 1) {
                for (int i = 0; i < NCTA; i++) g_stats[i] = 0ull;
                for (int i = 0; i < 4; i++) { g_kvt_count[i] = 0; g_z_count[i] = 0; }
                for (int i = 0; i < 32; i++) g_o_count[i] = 0;
                g_done = 0;
                __threadfence();
            }
        } else if (threadIdx.x == 128) {
            mbar_wait(bar(B_ATT), 0);
            mbar_expect_tx(bar(B_WO + 3), 32768);
            tma4d(sb + OFF_K + 32768, &tm_wo, 0, 0, hg * 2, 6, bar(B_WO + 3));
        }
        __syncwarp();
#pragma unroll
        for (int i = 0; i < 16; i++) acc[i] = 0.f;
        fence_regs<16>(acc);
#pragma unroll 1
        for (int jj = 0; jj < 4; jj++) {
            mbar_wait_w(bar(B_WO + jj), 0);
            mbar_wait_w(bar(B_O + jj), 0);
            if (threadIdx.x == 0 && (jj == 0 || jj == 3)) TSTAMP(jj == 0 ? 32 : 33);
            const uint32_t wb = sb + (jj < 2 ? OFF_X + jj * 32768 : (jj == 2 ? OFF_K : OFF_K + 32768)) + bcol;
            wg_fence();
            gemm_chunk(acc, sb + OFF_V + jj * 16384, wb);
            gemm_chunk(acc, sb + OFF_V + jj * 16384 + 8192, wb + 16384);
            wg_commit();
        }
        wg_wait<0>();
        fence_regs<16>(acc);
        {
            const int row = pb * 64 + wq * 16 + g;
            uint32_t* d0 = (uint32_t*)(prm.out + (size_t)row * 1024 + 512 + hg * 128 + w * 32) + t;
            uint32_t* d1 = d0 + 8 * 512;
#pragma unroll
            for (int i = 0; i < 4; i++) {
                d0[4 * i] = pack_bf16(acc[4 * i], acc[4 * i + 1]);
                d1[4 * i] = pack_bf16(acc[4 * i + 2], acc[4 * i + 3]);
            }
        }
        if ((threadIdx.x & 127) == 0 && w == 0) TSTAMP(5);
    } else {
        const int wa = warp_id - 16, tau = threadIdx.x - 512;
        __syncthreads();
        const bool kv_cta = (hg == (pb & 3));
        if (tau == 0) {
            if (kv_cta) {
                mbar_expect_tx(bar(B_WKV), 32768);
                tma3d(sb + OFF_C, &tm_wk, 0, 0, 0, bar(B_WKV));
                tma3d(sb + OFF_C + 16384, &tm_wv, 0, 0, 0, bar(B_WKV));
            }
            for (int jj = 0; jj < 4; jj++) {
                mbar_expect_tx(bar(B_X + jj), 16384);
                tma3d(sb + OFF_X + jj * 16384, &tm_x, 0, pb * 64, 2 * jj, bar(B_X + jj));
                if (!kv_cta && jj < 2) {
                    mbar_expect_tx(bar(B_W + jj), 32768);
                    tma4d(sb + OFF_V + jj * 32768, &tm_wq, 0, 0, hg * 2, 2 * jj, bar(B_W + jj));
                }
            }
            kv_tiles_load(sb, &tm_k, &tm_v, pb, hg);
            mbar_expect_tx(bar(B_H), 16384);
            for (int i = 0; i < 4; i++) tma2d(sb + S_H + i * 6144 + 2048, &tm_h, 0, (4 * b + i) * 64, bar(B_H));
            TSTAMP(25);
        }
        __syncwarp();
        if (kv_cta) {
            float acc[16];
#pragma unroll
            for (int i = 0; i < 16; i++) acc[i] = 0.f;
            fence_regs<16>(acc);
            mbar_wait_w(bar(B_WKV), 0);
            if (tau == 0) TSTAMP(20);
#pragma unroll
            for (int jj = 0; jj < 4; jj++) {
                mbar_wait_w(bar(B_X + jj), 0);
                wg_fence();
#pragma unroll
                for (int j = 2 * jj; j < 2 * jj + 2; j++) {
                    const uint64_t da = make_desc(sb + OFF_X + j * 8192, 16, 1024, 1);
                    const uint64_t db = make_desc(sb + OFF_C + j * 2048, 16384, 256, 3);
#pragma unroll
                    for (int ks = 0; ks < 4; ks++) wg_ss_n32_tb(acc, da + ks * 2, db + ks * 32);
                }
                wg_commit();
            }
            wg_wait<0>();
            fence_regs<16>(acc);
            if (tau == 0) TSTAMP(22);
            {
                uint32_t kk[4], vv[4];
#pragma unroll
                for (int i = 0; i < 4; i++) { kk[i] = pack_bf16(acc[2 * i], acc[2 * i + 1]); vv[i] = pack_bf16(acc[8 + 2 * i], acc[8 + 2 * i + 1]); }
                const int s = 4 * pb + wa;
                uint32_t* kp = (uint32_t*)(g_kimg + s * 512 + g * 16 + 4 * t);
                kp[0] = kk[0]; kp[64] = kk[1]; kp[32] = kk[2]; kp[96] = kk[3];
                uint32_t* vlo = (uint32_t*)(g_vimg + (127 - s) * 256 + g * 16 + 4 * t);
                uint32_t* vhi = (uint32_t*)(g_vimg + 32768 + 256 + s * 256 + g * 16 + 4 * t);
                vlo[0] = pack_f16(bf_lo(vv[0]), bf_hi(vv[0])); vlo[32] = pack_f16(bf_lo(vv[1]), bf_hi(vv[1]));
                vhi[0] = pack_f16(bf_lo(vv[2]), bf_hi(vv[2])); vhi[32] = pack_f16(bf_lo(vv[3]), bf_hi(vv[3]));
                uint32_t* vr = (uint32_t*)(g_vraw + (size_t)(16 * s + g) * 16) + t;
                vr[0] = vv[0]; vr[64] = vv[1]; vr[4] = vv[2]; vr[68] = vv[3];
                float n0 = bf_lo(kk[0]) * bf_lo(kk[0]) + bf_hi(kk[0]) * bf_hi(kk[0]) + bf_lo(kk[2]) * bf_lo(kk[2]) + bf_hi(kk[2]) * bf_hi(kk[2]);
                float n1 = bf_lo(kk[1]) * bf_lo(kk[1]) + bf_hi(kk[1]) * bf_hi(kk[1]) + bf_lo(kk[3]) * bf_lo(kk[3]) + bf_hi(kk[3]) * bf_hi(kk[3]);
                n0 += __shfl_xor_sync(0xffffffffu, n0, 1); n0 += __shfl_xor_sync(0xffffffffu, n0, 2);
                n1 += __shfl_xor_sync(0xffffffffu, n1, 1); n1 += __shfl_xor_sync(0xffffffffu, n1, 2);
                float km = fmaxf(n0, n1), vm = 0.f;
#pragma unroll
                for (int i = 0; i < 4; i++) vm = fmaxf(vm, fmaxf(fabsf(bf_lo(vv[i])), fabsf(bf_hi(vv[i]))));
#pragma unroll
                for (int o = 4; o < 32; o <<= 1) km = fmaxf(km, __shfl_xor_sync(0xffffffffu, km, o));
#pragma unroll
                for (int o = 1; o < 32; o <<= 1) vm = fmaxf(vm, __shfl_xor_sync(0xffffffffu, vm, o));
                __syncwarp();
                if (lane == 0) {
                    const unsigned long long rec = ((unsigned long long)(__float_as_uint(vm) | 0x80000000u) << 32) | __float_as_uint(km);
                    asm volatile("st.release.gpu.global.u64 [%0], %1;" ::"l"(&g_stats[s]), "l"(rec) : "memory");
                    if (wa == 0) TSTAMP(8);
                }
            }
            if (tau == 0) {
                for (int jj = 0; jj < 2; jj++) {
                    mbar_expect_tx(bar(B_W + jj), 32768);
                    tma4d(sb + OFF_V + jj * 32768, &tm_wq, 0, 0, hg * 2, 2 * jj, bar(B_W + jj));
                }
            }
            __syncwarp();
        }
        const int c0 = 4 * b;
        if (wa == 1) {
            float km = 0.f, vm = 0.f;
            {
                unsigned long long rec[4];
                uint32_t spins = 0;
                bool ok;
                do {
                    ok = true;
#pragma unroll
                    for (int i = 0; i < 4; i++) {
                        asm volatile("ld.relaxed.gpu.global.u64 %0, [%1];" : "=l"(rec[i]) : "l"(&g_stats[lane + 32 * i]) : "memory");
                        ok = ok && (rec[i] >> 63);
                    }
                    if (++spins > (1u << 22)) __trap();
                } while (!__all_sync(0xffffffffu, ok));
                asm volatile("fence.acq_rel.gpu;" ::: "memory");
#pragma unroll
                for (int i = 0; i < 4; i++) { km = fmaxf(km, __uint_as_float((uint32_t)rec[i])); vm = fmaxf(vm, __uint_as_float((uint32_t)(rec[i] >> 32) & 0x7FFFFFFFu)); }
            }
            if (lane == 0) {
                TSTAMP(16);
                fence_async_global();
                mbar_wait(bar(B_KVT), 0);
                for (int c = 0; c < 4; c++) {
                    mbar_expect_tx_noarrive(bar(B_KV + c), 8192);
                    bulk_g2s(sb + OFF_K + c * 8192, g_kimg + c * 8192, 8192, bar(B_KV + c));
                }
                for (int c = 4; c < 8; c++) mbar_expect_tx_noarrive(bar(B_KV + c), 8192);
                TSTAMP(28);
            }
#pragma unroll
            for (int o = 1; o < 32; o <<= 1) { km = fmaxf(km, __shfl_xor_sync(0xffffffffu, km, o)); vm = fmaxf(vm, __shfl_xor_sync(0xffffffffu, vm, o)); }
            const bool vdirect = (vm <= 32768.f && vm >= 9.765625e-4f) || vm == 0.f;
            float vs = 1.f;
            if (!vdirect && vm < INFINITY) {
                int e = (int)((__float_as_uint(vm) >> 23) & 0xFF) - 127;
                e = max(-100, min(100, e));
                vs = __uint_as_float((uint32_t)(127 + e - 13) << 23);
            }
            if (lane == 0) {
                asm volatile("st.shared.f32 [%0], %1;" ::"r"(sb + OFF_MISC), "f"(km) : "memory");
                asm volatile("st.shared.f32 [%0], %1;" ::"r"(sb + OFF_MISC + 4), "f"(vs) : "memory");
                mbar_wait(bar(B_QDONE), 0);
                TSTAMP(17);
                for (int c = 0; c < 8; c++) {
                    if (vdirect) {
                        mbar_expect_tx(bar(B_KV + c), 8192);
                        bulk_g2s(sb + OFF_V + (112 - 16 * c) * 256, g_vimg + (112 - 16 * c) * 256, 4096, bar(B_KV + c));
                        bulk_g2s(sb + OFF_VONES + 256 + c * 4096, g_vimg + 32768 + 256 + c * 4096, 4096, bar(B_KV + c));
                    }
                }
            }
            __syncwarp();
            sts32(sb + OFF_VONES + lane * 8, 0x3C003C00u);
            sts32(sb + OFF_VONES + lane * 8 + 4, 0x3C003C00u);
            if (!vdirect) {
                const float inv = 1.f / vs;
                for (int idx = lane; idx < S_LEN * 8; idx += 32) {
                    const int key = idx >> 3, dp = idx & 7;
                    const uint32_t v = __ldcg((const uint32_t*)g_vraw + idx);
                    const uint32_t h = pack_f16(bf_lo(v) * inv, bf_hi(v) * inv);
                    const int st = key >> 4, hf = (key >> 3) & 1;
                    const uint32_t base = (dp < 4) ? (OFF_V + (127 - st) * 256) : (OFF_VONES + 256 + st * 256);
                    sts32(sb + base + hf * 128 + (key & 7) * 16 + (dp & 3) * 4, h);
                }
            }
            fence_async_smem();
            __syncwarp();
            if (lane == 0) {
                mbar_arrive(bar(B_KV + 0));
                if (!vdirect) for (int c = 0; c < 8; c++) mbar_arrive(bar(B_KV + c));
                mbar_wait(bar(B_CONV), 0);
                for (int c = 4; c < 8; c++) bulk_g2s(sb + OFF_K + c * 8192, g_kimg + c * 8192, 8192, bar(B_KV + c));
            }
            __syncwarp();
        } else if (wa == 0) {
            if (lane == 0) {
                prefetch_tm(&tm_wo); prefetch_tm(&tm_o);
                mbar_wait(bar(B_KVT), 0);
                red_release_add(&g_kvt_count[hg], 1);
                TSTAMP(34);
                poll_counter(&g_kvt_count[b >> 5], 32);
                fence_async_global();
                mbar_expect_tx(bar(B_CV), 16384);
                bulk_g2s(sb + C_KVC, g_kvT + (size_t)c0 * S_LEN, 16384, bar(B_CV));
                mbar_wait(bar(B_CONV), 0);
                bulk_s2g(g_zT + (size_t)c0 * S_LEN, sb + C_KVC, 16384);
                bulk_commit();
                for (int jj = 0; jj < 2; jj++) {
                    mbar_expect_tx(bar(B_WO + jj), 32768);
                    tma4d(sb + OFF_X + jj * 32768, &tm_wo, 0, 0, hg * 2, 2 * jj, bar(B_WO + jj));
                }
            }
            __syncwarp();
        }
        {
            const int cg = tau & 15, pr = tau >> 4;
            const int p0 = pb * 64 + pr * 8, ch0 = hg * 128 + cg * 8;
            uint4 qr[8];
#pragma unroll
            for (int i = 0; i < 8; i++) qr[i] = __ldg((const uint4*)(prm.aq + (size_t)(p0 + i) * 512 + ch0));
            if (tau == 0) {
                bulk_wait_all();
                fence_async_global();
                red_release_add(&g_z_count[b >> 5], 1);
                poll_counter(&g_z_count[hg], 32);
                __threadfence();
                if (atomicAdd(&g_done, 1) == 2 * NCTA - 1) {
                    for (int i = 0; i < NCTA; i++) g_stats[i] = 0ull;
                    for (int i = 0; i < 4; i++) { g_kvt_count[i] = 0; g_z_count[i] = 0; }
                    for (int i = 0; i < 32; i++) g_o_count[i] = 0;
                    g_done = 0;
                    __threadfence();
                }
            }
            named_bar(5, 128);
            uint4 zz[8];
#pragma unroll
            for (int c = 0; c < 8; c++) zz[c] = __ldcg((const uint4*)(g_zT + (size_t)(ch0 + c) * S_LEN + p0));
#pragma unroll
            for (int i = 0; i < 8; i++) {
                uint32_t r[4];
#pragma unroll
                for (int k = 0; k < 4; k++) {
                    const uint32_t pr2 = __byte_perm((&zz[2 * k].x)[i >> 1], (&zz[2 * k + 1].x)[i >> 1], (i & 1) ? 0x7632 : 0x5410);
                    r[k] = bmul2((&qr[i].x)[k], pr2);
                }
                *(uint4*)(prm.out + (size_t)(p0 + i) * 1024 + ch0) = make_uint4(r[0], r[1], r[2], r[3]);
            }
        }
        if (tau == 0) TSTAMP(14);
    }
}

typedef CUresult (*EncodeFn)(CUtensorMap*, CUtensorMapDataType, cuuint32_t, void*, const cuuint64_t*, const cuuint64_t*,
                             const cuuint32_t*, const cuuint32_t*, CUtensorMapInterleave, CUtensorMapSwizzle,
                             CUtensorMapL2promotion, CUtensorMapFloatOOBfill);

void make_map(EncodeFn fn, CUtensorMap* tm, const void* ptr, int rank, const cuuint64_t* dims, const cuuint64_t* strides, const cuuint32_t* box, CUtensorMapSwizzle swz) {
    cuuint32_t es[4] = {1, 1, 1, 1};
    fn(tm, CU_TENSOR_MAP_DATA_TYPE_BFLOAT16, rank, const_cast<void*>(ptr), dims, strides, box, es, CU_TENSOR_MAP_INTERLEAVE_NONE, swz,
       CU_TENSOR_MAP_L2_PROMOTION_L2_128B, CU_TENSOR_MAP_FLOAT_OOB_FILL_NONE);
}

}

extern "C" void kernel_launch(void* const* d_in, const int* in_sizes, int n_in, void* d_out, int out_size) {
    (void)in_sizes; (void)n_in; (void)out_size;
    static EncodeFn encode = nullptr;
    static void* o_ptr = nullptr;
    if (!encode) {
        cudaDriverEntryPointQueryResult qres;
        void* fn = nullptr;
        cudaGetDriverEntryPoint("cuTensorMapEncodeTiled", &fn, cudaEnableDefault, &qres);
        encode = (EncodeFn)fn;
        cudaGetSymbolAddress(&o_ptr, g_o);
        cudaFuncSetAttribute(fused_kernel, cudaFuncAttributeMaxDynamicSharedMemorySize, SMEM_TOTAL);
    }
    CUtensorMap tm_x, tm_wq, tm_wo, tm_wk, tm_wv, tm_o, tm_h, tm_k, tm_v;
    {
        const cuuint64_t dims[3] = {64, 2048, 8}, str[2] = {1024, 128};
        const cuuint32_t b64[3] = {64, 64, 2};
        make_map(encode, &tm_x, d_in[6], 3, dims, str, b64, CU_TENSOR_MAP_SWIZZLE_128B);
        make_map(encode, &tm_o, o_ptr, 3, dims, str, b64, CU_TENSOR_MAP_SWIZZLE_128B);
    }
    {
        const cuuint64_t dims[4] = {64, 64, 8, 8}, str[3] = {1024, 128, 65536};
        const cuuint32_t box[4] = {64, 64, 2, 2};
        make_map(encode, &tm_wq, d_in[7], 4, dims, str, box, CU_TENSOR_MAP_SWIZZLE_128B);
        make_map(encode, &tm_wo, d_in[10], 4, dims, str, box, CU_TENSOR_MAP_SWIZZLE_128B);
    }
    {
        const cuuint64_t dims[3] = {16, 256, 2}, str[2] = {32, 8192};
        const cuuint32_t box[3] = {16, 256, 2};
        make_map(encode, &tm_wk, d_in[8], 3, dims, str, box, CU_TENSOR_MAP_SWIZZLE_32B);
        make_map(encode, &tm_wv, d_in[9], 3, dims, str, box, CU_TENSOR_MAP_SWIZZLE_32B);
    }
    {
        const cuuint64_t dims[2] = {32, 512 * 64}, str[1] = {64};
        const cuuint32_t box[2] = {32, 64};
        make_map(encode, &tm_h, d_in[4], 2, dims, str, box, CU_TENSOR_MAP_SWIZZLE_64B);
    }
    {
        const cuuint64_t dims[2] = {512, 2048}, str[1] = {1024};
        const cuuint32_t bk[2] = {128, 67}, bv[2] = {128, 64};
        make_map(encode, &tm_k, d_in[1], 2, dims, str, bk, CU_TENSOR_MAP_SWIZZLE_NONE);
        make_map(encode, &tm_v, d_in[2], 2, dims, str, bv, CU_TENSOR_MAP_SWIZZLE_NONE);
    }
    Params prm;
    prm.aq = (const __nv_bfloat16*)d_in[0];
    prm.ak = (const __nv_bfloat16*)d_in[1];
    prm.av = (const __nv_bfloat16*)d_in[2];
    prm.shift_k = (const __nv_bfloat16*)d_in[3];
    prm.ssm_D = (const __nv_bfloat16*)d_in[5];
    prm.out = (__nv_bfloat16*)d_out;
    fused_kernel<<<NCTA, NTHREADS, SMEM_TOTAL>>>(tm_x, tm_wq, tm_wo, tm_wk, tm_wv, tm_o, tm_h, tm_k, tm_v, prm);
}
```

```cpp
#include <cuda_runtime.h>
#include <cuda_bf16.h>
#include <cuda_fp16.h>
#include <cuda.h>
#include <stdint.h>

#define LATE_WQ
#define TAIL_CH 0
#define KVIN_AFTER 3
namespace {

constexpr int S_LEN = 2048;
constexpr int NCTA = 128;
constexpr int NTHREADS = 640;

constexpr uint32_t OFF_K = 0;
constexpr uint32_t OFF_V = 65536;
constexpr uint32_t OFF_VONES = OFF_V + 32768;
constexpr uint32_t OFF_X = 132096;
constexpr uint32_t OFF_C = 197632;
constexpr uint32_t C_KVC = OFF_C;
constexpr uint32_t C_H = OFF_C + 16384;
constexpr uint32_t C_Z = C_H + 6144;
constexpr uint32_t OFF_BAR = 231936;
constexpr uint32_t SMEM_TOTAL = 232448;

enum { B_WKV = 0, B_X = 1, B_QEMPTY = 5, B_QDONE = 7, B_KV = 8, B_WO = 16, B_O = 20, B_ATT = 24, B_H = 25, B_CV = 26, B_W = 27, B_KVT = 31, B_KVIN = 32, B_COUNT = 33 };
constexpr uint32_t OFF_MISC = OFF_BAR + 8 * B_COUNT;

__device__ __align__(1024) uint8_t g_kimg[65536];
__device__ __align__(1024) uint8_t g_vimg[65792];
__device__ __align__(1024) __nv_bfloat16 g_vraw[S_LEN * 16];
__device__ __align__(1024) __nv_bfloat16 g_o[S_LEN * 512];
__device__ __align__(1024) __nv_bfloat16 g_kvT[512 * S_LEN];
__device__ __align__(1024) __nv_bfloat16 g_zT[512 * S_LEN];
__device__ unsigned long long g_stats[NCTA];
__device__ unsigned int g_kvt_count[4];
__device__ unsigned int g_z_count[4];
__device__ unsigned int g_o_count[32];
__device__ unsigned int g_done;
#define TSTAMP(i) do {} while (0)
#define CSTAMP(i) do {} while (0)

__device__ __forceinline__ void wg_fence() { asm volatile("wgmma.fence.sync.aligned;" ::: "memory"); }
__device__ __forceinline__ void wg_commit() { asm volatile("wgmma.commit_group.sync.aligned;" ::: "memory"); }
template <int N> __device__ __forceinline__ void wg_wait() { asm volatile("wgmma.wait_group.sync.aligned %0;" ::"n"(N) : "memory"); }
template <int N> __device__ __forceinline__ void fence_regs(float* r) {
#pragma unroll
    for (int i = 0; i < N; i++) asm volatile("" : "+f"(r[i])::"memory");
}
template <int N> __device__ __forceinline__ void fence_uregs(uint32_t* r) {
#pragma unroll
    for (int i = 0; i < N; i++) asm volatile("" : "+r"(r[i])::"memory");
}
__device__ __forceinline__ uint64_t make_desc(uint32_t saddr, uint32_t lbo, uint32_t sbo, uint32_t swz) {
    return (uint64_t)((saddr & 0x3FFFF) >> 4) | ((uint64_t)(lbo >> 4) << 16) | ((uint64_t)(sbo >> 4) << 32) | ((uint64_t)swz << 62);
}
__device__ __forceinline__ void mbar_init(uint32_t bar, uint32_t count) {
    asm volatile("mbarrier.init.shared::cta.b64 [%0], %1;" ::"r"(bar), "r"(count) : "memory");
}
__device__ __forceinline__ void mbar_expect_tx(uint32_t bar, uint32_t bytes) {
    asm volatile("mbarrier.arrive.expect_tx.shared::cta.b64 _, [%0], %1;" ::"r"(bar), "r"(bytes) : "memory");
}
__device__ __forceinline__ void mbar_expect_tx_noarrive(uint32_t bar, uint32_t bytes) {
    asm volatile("mbarrier.expect_tx.relaxed.cta.shared::cta.b64 [%0], %1;" ::"r"(bar), "r"(bytes) : "memory");
}
__device__ __forceinline__ void mbar_arrive(uint32_t bar) {
    asm volatile("mbarrier.arrive.shared::cta.b64 _, [%0];" ::"r"(bar) : "memory");
}
__device__ __forceinline__ bool mbar_try(uint32_t bar, uint32_t parity) {
    uint32_t ok;
    asm volatile("{\n.reg .pred p;\nmbarrier.try_wait.parity.shared::cta.b64 p, [%1], %2;\nselp.u32 %0, 1, 0, p;\n}\n"
                 : "=r"(ok) : "r"(bar), "r"(parity) : "memory");
    return ok != 0;
}
__device__ __forceinline__ void mbar_wait(uint32_t bar, uint32_t parity) {
    uint32_t spins = 0;
    while (!mbar_try(bar, parity)) {
        if (++spins > (1u << 24)) __trap();
    }
}
__device__ __forceinline__ void mbar_wait_w(uint32_t bar, uint32_t parity) {
    uint32_t spins = 0;
    while (!__all_sync(0xffffffffu, mbar_try(bar, parity))) {
        if (++spins > (1u << 24)) __trap();
    }
}
__device__ __forceinline__ void tma2d(uint32_t dst, const CUtensorMap* tm, int c0, int c1, uint32_t bar) {
    asm volatile("cp.async.bulk.tensor.2d.shared::cluster.global.mbarrier::complete_tx::bytes [%0], [%1, {%3, %4}], [%2];"
                 ::"r"(dst), "l"((uint64_t)tm), "r"(bar), "r"(c0), "r"(c1) : "memory");
}
__device__ __forceinline__ void tma3d(uint32_t dst, const CUtensorMap* tm, int c0, int c1, int c2, uint32_t bar) {
    asm volatile("cp.async.bulk.tensor.3d.shared::cluster.global.mbarrier::complete_tx::bytes [%0], [%1, {%3, %4, %5}], [%2];"
                 ::"r"(dst), "l"((uint64_t)tm), "r"(bar), "r"(c0), "r"(c1), "r"(c2) : "memory");
}
__device__ __forceinline__ void tma4d(uint32_t dst, const CUtensorMap* tm, int c0, int c1, int c2, int c3, uint32_t bar) {
    asm volatile("cp.async.bulk.tensor.4d.shared::cluster.global.mbarrier::complete_tx::bytes [%0], [%1, {%3, %4, %5, %6}], [%2];"
                 ::"r"(dst), "l"((uint64_t)tm), "r"(bar), "r"(c0), "r"(c1), "r"(c2), "r"(c3) : "memory");
}
__device__ __forceinline__ void prefetch_tm(const CUtensorMap* tm) { asm volatile("prefetch.tensormap [%0];" ::"l"((uint64_t)tm) : "memory"); }
__device__ __forceinline__ void bulk_s2g(void* dst, uint32_t src, uint32_t bytes) {
    asm volatile("cp.async.bulk.global.shared::cta.bulk_group [%0], [%1], %2;" ::"l"(dst), "r"(src), "r"(bytes) : "memory");
}
__device__ __forceinline__ void bulk_commit() { asm volatile("cp.async.bulk.commit_group;" ::: "memory"); }
__device__ __forceinline__ void bulk_wait_all() { asm volatile("cp.async.bulk.wait_group 0;" ::: "memory"); }
__device__ __forceinline__ void fence_async_global() { asm volatile("fence.proxy.async.global;" ::: "memory"); }
__device__ __forceinline__ void bulk_g2s(uint32_t dst, const void* src, uint32_t bytes, uint32_t bar) {
    asm volatile("cp.async.bulk.shared::cluster.global.mbarrier::complete_tx::bytes [%0], [%1], %2, [%3];"
                 ::"r"(dst), "l"(src), "r"(bytes), "r"(bar) : "memory");
}
__device__ __forceinline__ void fence_async_smem() { asm volatile("fence.proxy.async.shared::cta;" ::: "memory"); }
__device__ __forceinline__ void named_bar(int id, int n) { asm volatile("bar.sync %0, %1;" ::"r"(id), "r"(n) : "memory"); }
__device__ __forceinline__ bool named_bar_and(int id, int n, bool pred) {
    uint32_t r;
    asm volatile("{\n.reg .pred p, q;\nsetp.ne.u32 p, %3, 0;\nbarrier.cta.red.and.pred q, %1, %2, p;\nselp.u32 %0, 1, 0, q;\n}\n"
                 : "=r"(r) : "r"(id), "r"(n), "r"((uint32_t)pred) : "memory");
    return r != 0;
}
__device__ __forceinline__ unsigned int ld_acquire(const unsigned int* p) {
    unsigned int v;
    asm volatile("ld.acquire.gpu.global.u32 %0, [%1];" : "=r"(v) : "l"(p) : "memory");
    return v;
}
__device__ __forceinline__ void red_release_add(unsigned int* p, unsigned int v) {
    asm volatile("red.release.gpu.global.add.u32 [%0], %1;" ::"l"(p), "r"(v) : "memory");
}
__device__ __forceinline__ void poll_counter(const unsigned int* p, unsigned int target) {
    uint32_t spins = 0;
    while (ld_acquire(p) < target) {
        if (++spins > (1u << 22)) __trap();
    }
}
__device__ __forceinline__ float ex2f(float x) { float y; asm("ex2.approx.ftz.f32 %0, %1;" : "=f"(y) : "f"(x)); return y; }
__device__ __forceinline__ uint32_t pack_f16(float lo, float hi) { uint32_t r; asm("cvt.rn.f16x2.f32 %0, %1, %2;" : "=r"(r) : "f"(hi), "f"(lo)); return r; }
__device__ __forceinline__ uint32_t pack_bf16(float lo, float hi) { uint32_t r; asm("cvt.rn.bf16x2.f32 %0, %1, %2;" : "=r"(r) : "f"(hi), "f"(lo)); return r; }
__device__ __forceinline__ float bf_lo(uint32_t v) { return __uint_as_float(v << 16); }
__device__ __forceinline__ float bf_hi(uint32_t v) { return __uint_as_float(v & 0xFFFF0000u); }
__device__ __forceinline__ uint32_t hfma2(uint32_t a, uint32_t b, uint32_t c) { uint32_t r; asm("fma.rn.f16x2 %0, %1, %2, %3;" : "=r"(r) : "r"(a), "r"(b), "r"(c)); return r; }
__device__ __forceinline__ uint32_t bmul2(uint32_t a, uint32_t b) { uint32_t r; asm("mul.rn.bf16x2 %0, %1, %2;" : "=r"(r) : "r"(a), "r"(b)); return r; }
__device__ __forceinline__ uint32_t badd2(uint32_t a, uint32_t b) { uint32_t r; asm("add.rn.bf16x2 %0, %1, %2;" : "=r"(r) : "r"(a), "r"(b)); return r; }
template <int LUT> __device__ __forceinline__ uint32_t lop3(uint32_t a, uint32_t b, uint32_t c) {
    uint32_t r; asm("lop3.b32 %0, %1, %2, %3, %4;" : "=r"(r) : "r"(a), "r"(b), "r"(c), "n"(LUT)); return r;
}
__device__ __forceinline__ uint32_t lds32(uint32_t a) { uint32_t v; asm volatile("ld.shared.u32 %0, [%1];" : "=r"(v) : "r"(a)); return v; }
__device__ __forceinline__ float ldsf(uint32_t a) { float v; asm volatile("ld.shared.f32 %0, [%1];" : "=f"(v) : "r"(a)); return v; }
__device__ __forceinline__ uint4 lds128(uint32_t a) { uint4 v; asm volatile("ld.shared.v4.u32 {%0,%1,%2,%3}, [%4];" : "=r"(v.x), "=r"(v.y), "=r"(v.z), "=r"(v.w) : "r"(a)); return v; }
__device__ __forceinline__ void lds64(uint32_t a, uint32_t& x, uint32_t& y) { asm volatile("ld.shared.v2.u32 {%0,%1}, [%2];" : "=r"(x), "=r"(y) : "r"(a)); }
__device__ __forceinline__ void sts32(uint32_t a, uint32_t v) { asm volatile("st.shared.u32 [%0], %1;" ::"r"(a), "r"(v) : "memory"); }
__device__ __forceinline__ void sts64f(uint32_t a, float x, float y) { asm volatile("st.shared.v2.f32 [%0], {%1,%2};" ::"r"(a), "f"(x), "f"(y) : "memory"); }
__device__ __forceinline__ void sts128(uint32_t a, uint32_t x, uint32_t y, uint32_t z, uint32_t w) {
    asm volatile("st.shared.v4.u32 [%0], {%1,%2,%3,%4};" ::"r"(a), "r"(x), "r"(y), "r"(z), "r"(w) : "memory");
}

__device__ __forceinline__ void wg_ss_n32_tb(float* d, uint64_t descA, uint64_t descB) {
    asm volatile("wgmma.mma_async.sync.aligned.m64n32k16.f32.bf16.bf16 {%0,%1,%2,%3,%4,%5,%6,%7,%8,%9,%10,%11,%12,%13,%14,%15}, %16, %17, 1, 1, 1, 0, 1;\n"
        : "+f"(d[0]), "+f"(d[1]), "+f"(d[2]), "+f"(d[3]), "+f"(d[4]), "+f"(d[5]), "+f"(d[6]), "+f"(d[7]), "+f"(d[8]), "+f"(d[9]), "+f"(d[10]), "+f"(d[11]), "+f"(d[12]), "+f"(d[13]), "+f"(d[14]), "+f"(d[15])
        : "l"(descA), "l"(descB));
}
__device__ __forceinline__ void wg_qk_n64(float* d, const uint32_t* a, uint64_t desc) {
    asm volatile("wgmma.mma_async.sync.aligned.m64n64k16.f32.bf16.bf16 {%0,%1,%2,%3,%4,%5,%6,%7,%8,%9,%10,%11,%12,%13,%14,%15,%16,%17,%18,%19,%20,%21,%22,%23,%24,%25,%26,%27,%28,%29,%30,%31}, {%32,%33,%34,%35}, %36, 0, 1, 1, 0;\n"
        : "+f"(d[0]), "+f"(d[1]), "+f"(d[2]), "+f"(d[3]), "+f"(d[4]), "+f"(d[5]), "+f"(d[6]), "+f"(d[7]), "+f"(d[8]), "+f"(d[9]), "+f"(d[10]), "+f"(d[11]), "+f"(d[12]), "+f"(d[13]), "+f"(d[14]), "+f"(d[15]), "+f"(d[16]), "+f"(d[17]), "+f"(d[18]), "+f"(d[19]), "+f"(d[20]), "+f"(d[21]), "+f"(d[22]), "+f"(d[23]), "+f"(d[24]), "+f"(d[25]), "+f"(d[26]), "+f"(d[27]), "+f"(d[28]), "+f"(d[29]), "+f"(d[30]), "+f"(d[31])
        : "r"(a[0]), "r"(a[1]), "r"(a[2]), "r"(a[3]), "l"(desc));
}
__device__ __forceinline__ void wg_pv_n24(float* d, const uint32_t* a, uint64_t desc) {
    asm volatile("wgmma.mma_async.sync.aligned.m64n24k16.f32.f16.f16 {%0,%1,%2,%3,%4,%5,%6,%7,%8,%9,%10,%11}, {%12,%13,%14,%15}, %16, 1, 1, 1, 1;\n"
        : "+f"(d[0]), "+f"(d[1]), "+f"(d[2]), "+f"(d[3]), "+f"(d[4]), "+f"(d[5]), "+f"(d[6]), "+f"(d[7]), "+f"(d[8]), "+f"(d[9]), "+f"(d[10]), "+f"(d[11])
        : "r"(a[0]), "r"(a[1]), "r"(a[2]), "r"(a[3]), "l"(desc));
}
__device__ __forceinline__ void wg_cv_n32(float* d, const uint32_t* a, uint64_t desc) {
    asm volatile("wgmma.mma_async.sync.aligned.m64n32k16.f32.bf16.bf16 {%0,%1,%2,%3,%4,%5,%6,%7,%8,%9,%10,%11,%12,%13,%14,%15}, {%16,%17,%18,%19}, %20, 1, 1, 1, 0;\n"
        : "+f"(d[0]), "+f"(d[1]), "+f"(d[2]), "+f"(d[3]), "+f"(d[4]), "+f"(d[5]), "+f"(d[6]), "+f"(d[7]), "+f"(d[8]), "+f"(d[9]), "+f"(d[10]), "+f"(d[11]), "+f"(d[12]), "+f"(d[13]), "+f"(d[14]), "+f"(d[15])
        : "r"(a[0]), "r"(a[1]), "r"(a[2]), "r"(a[3]), "l"(desc));
}
__device__ __forceinline__ void wg_cv_n64(float* d, const uint32_t* a, uint64_t desc) {
    asm volatile("wgmma.mma_async.sync.aligned.m64n64k16.f32.bf16.bf16 {%0,%1,%2,%3,%4,%5,%6,%7,%8,%9,%10,%11,%12,%13,%14,%15,%16,%17,%18,%19,%20,%21,%22,%23,%24,%25,%26,%27,%28,%29,%30,%31}, {%32,%33,%34,%35}, %36, 1, 1, 1, 0;\n"
        : "+f"(d[0]), "+f"(d[1]), "+f"(d[2]), "+f"(d[3]), "+f"(d[4]), "+f"(d[5]), "+f"(d[6]), "+f"(d[7]), "+f"(d[8]), "+f"(d[9]), "+f"(d[10]), "+f"(d[11]), "+f"(d[12]), "+f"(d[13]), "+f"(d[14]), "+f"(d[15]), "+f"(d[16]), "+f"(d[17]), "+f"(d[18]), "+f"(d[19]), "+f"(d[20]), "+f"(d[21]), "+f"(d[22]), "+f"(d[23]), "+f"(d[24]), "+f"(d[25]), "+f"(d[26]), "+f"(d[27]), "+f"(d[28]), "+f"(d[29]), "+f"(d[30]), "+f"(d[31])
        : "r"(a[0]), "r"(a[1]), "r"(a[2]), "r"(a[3]), "l"(desc));
}

template <int N> __device__ __forceinline__ void wg_cv(float* d, const uint32_t* a, uint64_t desc);
template <> __device__ __forceinline__ void wg_cv<32>(float* d, const uint32_t* a, uint64_t s) { wg_cv_n32(d, a, s); }
template <> __device__ __forceinline__ void wg_cv<64>(float* d, const uint32_t* a, uint64_t s) { wg_cv_n64(d, a, s); }

constexpr uint32_t POLYMASK = 0xB5B5u;
__device__ __forceinline__ void softmax_fast(const float* s, uint32_t* p, uint32_t mlo) {
    const uint32_t C3 = 0x2cfb2cfbu, C2 = 0x9fec9fecu, C1 = 0x37a837a8u, C0 = 0x37383738u;
#pragma unroll
    for (int i = 0; i < 16; i++) {
        const float s0 = s[2 * i], s1 = s[2 * i + 1];
        if ((POLYMASK >> i) & 1) {
            const float t0 = s0 + 12303.0f, t1 = s1 + 12303.0f;
            const uint32_t T = __byte_perm(__float_as_uint(t0), __float_as_uint(t1), 0x5410);
            const uint32_t U = lop3<0xEA>(T, mlo, 0x3C003C00u);
            uint32_t h = hfma2(U, C3, C2);
            h = hfma2(h, U, C1);
            h = hfma2(h, U, C0);
            p[i] = lop3<0xE4>(h, T, 0x03FF03FFu);
        } else {
            p[i] = pack_f16(ex2f(s0), ex2f(s1));
        }
    }
}

__device__ __forceinline__ void gemm_chunk(float* acc, uint32_t a_addr, uint32_t b_addr) {
    const uint64_t da = make_desc(a_addr, 16, 1024, 1);
    const uint64_t db = make_desc(b_addr, 8192, 1024, 1);
#pragma unroll
    for (int ks = 0; ks < 4; ks++) wg_ss_n32_tb(acc, da + ks * 2, db + ks * 128);
}

__device__ __forceinline__ uint32_t smem_inc(uint32_t addr) {
    uint32_t old;
    asm volatile("atom.acq_rel.cta.shared.add.u32 %0, [%1], 1;" : "=r"(old) : "r"(addr) : "memory");
    return old;
}
__device__ __forceinline__ void wo_half(uint32_t sb, const CUtensorMap* tm_wo, int hg) {
    if (smem_inc(sb + OFF_MISC + 8) == 3) {
        mbar_expect_tx(sb + OFF_BAR + 8 * (B_WO + 2), 32768);
        tma4d(sb + OFF_K, tm_wo, 0, 0, hg * 2, 4, sb + OFF_BAR + 8 * (B_WO + 2));
    }
}

__device__ __forceinline__ void kv_tiles_load(uint32_t sb, const CUtensorMap* tm_k, const CUtensorMap* tm_v, int pb, int hg) {
    const uint32_t br = sb + OFF_BAR + 8 * B_KVIN;
    mbar_expect_tx(br, 67 * 256 + 64 * 256);
    tma2d(sb + OFF_C, tm_k, hg * 128, pb * 64 - 3, br);
    tma2d(sb + OFF_C + 17408, tm_v, hg * 128, pb * 64, br);
}

struct Params {
    const __nv_bfloat16 *aq, *ak, *av, *shift_k, *ssm_D;
    __nv_bfloat16* out;
};

template <int NQ>
__device__ __forceinline__ void conv_phase(float* Dn, uint32_t zaddr, uint64_t hdesc) {
    uint32_t a[2][16];
#pragma unroll
    for (int st = 0; st < 8; st++) {
        uint32_t* aa = a[st & 1];
        if (st >= 2) wg_wait<1>();
#pragma unroll
        for (int u = 0; u < 2; u++) {
            const uint32_t z = zaddr + (st * 2 + u) * 256;
            lds64(z, aa[8 * u + 0], aa[8 * u + 1]);      lds64(z - 32, aa[8 * u + 2], aa[8 * u + 3]);
            lds64(z - 64, aa[8 * u + 4], aa[8 * u + 5]); lds64(z - 96, aa[8 * u + 6], aa[8 * u + 7]);
        }
        wg_fence();
#pragma unroll
        for (int u = 0; u < 2; u++) {
            const int qi = st * 2 + u;
            wg_cv<NQ>(Dn, &aa[8 * u], hdesc - qi * 8);
            wg_cv<NQ>(Dn, &aa[8 * u + 4], hdesc - qi * 8 + 2);
        }
        wg_commit();
    }
    wg_wait<0>();
    fence_regs<NQ / 2>(Dn);
}

__global__ void __launch_bounds__(NTHREADS, 1)
fused_kernel(const __grid_constant__ CUtensorMap tm_x,
             const __grid_constant__ CUtensorMap tm_wq, const __grid_constant__ CUtensorMap tm_wo,
             const __grid_constant__ CUtensorMap tm_wk, const __grid_constant__ CUtensorMap tm_wv,
             const __grid_constant__ CUtensorMap tm_o, const __grid_constant__ CUtensorMap tm_h,
             const __grid_constant__ CUtensorMap tm_k, const __grid_constant__ CUtensorMap tm_v, const Params prm) {
    extern __shared__ __align__(1024) uint8_t smem_raw[];
    const uint32_t sb = (uint32_t)__cvta_generic_to_shared(smem_raw);
    const int warp_id = __shfl_sync(0xffffffffu, threadIdx.x >> 5, 0);
    const int lane = threadIdx.x & 31;
    const int g = lane >> 2, t = lane & 3;
    const int b = blockIdx.x, pb = b >> 2, hg = b & 3;
    auto bar = [&](int i) { return sb + OFF_BAR + 8 * i; };

    if (threadIdx.x == 512) {
        TSTAMP(0);
        prefetch_tm(&tm_x); prefetch_tm(&tm_wq); prefetch_tm(&tm_wk); prefetch_tm(&tm_wv);
        mbar_init(bar(B_WKV), 1);
        for (int j = 0; j < 4; j++) { mbar_init(bar(B_X + j), 1); mbar_init(bar(B_W + j), 1); mbar_init(bar(B_WO + j), 1); mbar_init(bar(B_O + j), 1); }
        sts32(sb + OFF_MISC + 8, 0u); sts32(sb + OFF_MISC + 12, 0u); sts32(sb + OFF_MISC + 16, 0u);
        for (int j = 0; j < 8; j++) mbar_init(bar(B_KV + j), j == 0 ? 2 : 1);
        mbar_init(bar(B_QEMPTY), 4); mbar_init(bar(B_QEMPTY + 1), 4);
        mbar_init(bar(B_QDONE), 4); mbar_init(bar(B_ATT), 4);
        mbar_init(bar(B_H), 1); mbar_init(bar(B_CV), 1); mbar_init(bar(B_KVT), 64); mbar_init(bar(B_KVIN), 1);
        asm volatile("fence.mbarrier_init.release.cluster;" ::: "memory");
    }

    if (warp_id < 16) {
        const int w = warp_id >> 2, wq = warp_id & 3;
        __syncthreads();
        float acc[16];
#pragma unroll
        for (int i = 0; i < 16; i++) acc[i] = 0.f;
        fence_regs<16>(acc);
        const uint32_t bcol = (w >> 1) * 8192 + (w & 1) * 64;
#pragma unroll 1
        for (int jj = 0; jj < 4; jj++) {
            mbar_wait_w(bar(B_X + jj), 0);
            mbar_wait_w(bar(B_W + jj), 0);
            if (threadIdx.x == 0) TSTAMP(jj == 0 ? 23 : jj == 1 ? 24 : jj == 2 ? 26 : 27);
            wg_fence();
            gemm_chunk(acc, sb + OFF_X + jj * 16384, sb + OFF_V + (jj & 1) * 32768 + bcol);
            gemm_chunk(acc, sb + OFF_X + jj * 16384 + 8192, sb + OFF_V + (jj & 1) * 32768 + 16384 + bcol);
            wg_commit();
            wg_wait<0>();
            if (jj < 2 && (threadIdx.x & 127) == 0) {
                if (smem_inc(sb + OFF_MISC + 12 + 4 * jj) == 3) {
                    mbar_expect_tx(bar(B_W + jj + 2), 32768);
                    tma4d(sb + OFF_V + jj * 32768, &tm_wq, 0, 0, hg * 2, 2 * (jj + 2), bar(B_W + jj + 2));
                }
            }
        }
        fence_regs<16>(acc);
        if ((threadIdx.x & 127) == 0) { mbar_arrive(bar(B_QDONE)); if (w == 0) TSTAMP(1); }
        uint32_t qa[2][4];
        float qn[2];
        {
            const float c = 0.25f * 1.4426950408889634f;
#pragma unroll
            for (int hh = 0; hh < 2; hh++) {
                float n0 = 0.f, n1 = 0.f;
#pragma unroll
                for (int i = 0; i < 4; i++) {
                    const uint32_t qb = pack_bf16(acc[8 * hh + 2 * i], acc[8 * hh + 2 * i + 1]);
                    const uint32_t qs = pack_bf16(bf_lo(qb) * c, bf_hi(qb) * c);
                    qa[hh][i] = qs;
                    const float e = bf_lo(qs) * bf_lo(qs) + bf_hi(qs) * bf_hi(qs);
                    if (i & 1) n1 += e; else n0 += e;
                }
                n0 += __shfl_xor_sync(0xffffffffu, n0, 1); n0 += __shfl_xor_sync(0xffffffffu, n0, 2);
                n1 += __shfl_xor_sync(0xffffffffu, n1, 1); n1 += __shfl_xor_sync(0xffffffffu, n1, 2);
                qn[hh] = fmaxf(n0, n1);
            }
        }
        uint32_t mlo = 0x03FF03FFu; asm volatile("" : "+r"(mlo));
        const uint64_t kdesc0 = make_desc(sb + OFF_K, 128, 256, 0);
        const uint64_t vdesc0 = make_desc(sb + OFF_VONES - 256, 128, 256, 0);
        constexpr uint64_t VSTEP = ((uint64_t)16 << 32) - 16;
        mbar_wait_w(bar(B_KV + 0), 0);
        if ((threadIdx.x & 127) == 0 && w == 0) TSTAMP(2);
        const float kmax2 = ldsf(sb + OFF_MISC);
        const bool fast0 = __all_sync(0xffffffffu, named_bar_and(1 + w, 128, qn[0] * kmax2 <= 193.0f));
        const bool fast1 = __all_sync(0xffffffffu, named_bar_and(1 + w, 128, qn[1] * kmax2 <= 193.0f));
        uint32_t a[4] = {qa[0][0], qa[0][1], qa[0][2], qa[0][3]};
#pragma unroll 1
        for (int hh = 0; hh < 2; hh++) {
            const bool fast = hh ? fast1 : fast0;
            float S[32], O[12];
#pragma unroll
            for (int i = 0; i < 12; i++) O[i] = 0.f;
#pragma unroll
            for (int i = 0; i < 32; i++) S[i] = 0.f;
            fence_regs<12>(O); fence_regs<32>(S);
            wg_fence();
            wg_qk_n64(S, a, kdesc0);
            wg_commit();
            wg_wait<0>();
            uint64_t kd = kdesc0 + 128, vd = vdesc0;
            if (fast) {
                uint32_t P[16];
#pragma unroll 1
                for (int c = 0; c < 8; c++) {
                    if (c < 7) mbar_wait_w(bar(B_KV + c + 1), 0);
#pragma unroll 1
                    for (int j = 0; j < 4; j++) {
                        fence_regs<32>(S);
                        softmax_fast(S, P, mlo);
                        fence_regs<32>(S);
                        wg_fence();
                        wg_qk_n64(S, a, kd);
#pragma unroll
                        for (int i = 0; i < 4; i++) wg_pv_n24(O, &P[4 * i], vd + i * VSTEP);
                        wg_commit();
                        wg_wait<0>();
                        kd += 128; vd += 4 * VSTEP;
                    }
                    if (hh == 1 && c == 3 && (threadIdx.x & 127) == 0) wo_half(sb, &tm_wo, hg);
                }
            } else {
                uint32_t P[16];
                float m0 = -INFINITY, m1 = -INFINITY;
#pragma unroll 1
                for (int c = 0; c < 8; c++) {
                    if (c < 7) mbar_wait_w(bar(B_KV + c + 1), 0);
#pragma unroll 1
                    for (int j = 0; j < 4; j++) {
                        fence_regs<32>(S); fence_regs<12>(O);
                        float x0 = m0, x1 = m1;
#pragma unroll
                        for (int i = 0; i < 8; i++) {
                            x0 = fmaxf(x0, fmaxf(S[4 * i], S[4 * i + 1]));
                            x1 = fmaxf(x1, fmaxf(S[4 * i + 2], S[4 * i + 3]));
                        }
                        x0 = fmaxf(x0, __shfl_xor_sync(0xffffffffu, x0, 1)); x0 = fmaxf(x0, __shfl_xor_sync(0xffffffffu, x0, 2));
                        x1 = fmaxf(x1, __shfl_xor_sync(0xffffffffu, x1, 1)); x1 = fmaxf(x1, __shfl_xor_sync(0xffffffffu, x1, 2));
                        const float r0 = ex2f(m0 - x0), r1 = ex2f(m1 - x1);
                        m0 = x0; m1 = x1;
#pragma unroll
                        for (int i = 0; i < 3; i++) { O[4 * i] *= r0; O[4 * i + 1] *= r0; O[4 * i + 2] *= r1; O[4 * i + 3] *= r1; }
#pragma unroll
                        for (int i = 0; i < 8; i++) {
                            P[2 * i] = pack_f16(ex2f(S[4 * i] - m0), ex2f(S[4 * i + 1] - m0));
                            P[2 * i + 1] = pack_f16(ex2f(S[4 * i + 2] - m1), ex2f(S[4 * i + 3] - m1));
                        }
                        fence_regs<32>(S); fence_regs<12>(O);
                        wg_fence();
                        wg_qk_n64(S, a, kd);
#pragma unroll
                        for (int i = 0; i < 4; i++) wg_pv_n24(O, &P[4 * i], vd + i * VSTEP);
                        wg_commit();
                        wg_wait<0>();
                        kd += 128; vd += 4 * VSTEP;
                    }
                    if (hh == 1 && c == 3 && (threadIdx.x & 127) == 0) wo_half(sb, &tm_wo, hg);
                }
            }
            fence_regs<12>(O);
            const float vscale = ldsf(sb + OFF_MISC + 4);
            const float i0 = __fdividef(vscale, O[4]), i1 = __fdividef(vscale, O[6]);
            const int row = pb * 64 + wq * 16 + g;
            uint32_t* o0 = (uint32_t*)(g_o + (size_t)row * 512 + (hg * 8 + 2 * w + hh) * 16) + t;
            uint32_t* o1 = o0 + 8 * 256;
            o0[0] = pack_bf16(O[0] * i0, O[1] * i0);
            o0[4] = pack_bf16(O[8] * i0, O[9] * i0);
            o1[0] = pack_bf16(O[2] * i1, O[3] * i1);
            o1[4] = pack_bf16(O[10] * i1, O[11] * i1);
            if ((threadIdx.x & 127) == 0 && w == 0) { TSTAMP(3 + hh); CSTAMP(40 + hh); }
#pragma unroll
            for (int i = 0; i < 4; i++) a[i] = qa[1][i];
        }
        named_bar(1 + w, 128);
        if ((threadIdx.x & 127) == 0) {
            red_release_add(&g_o_count[pb], 1);
            mbar_arrive(bar(B_ATT));
        }
        if (threadIdx.x == 0) {
            TSTAMP(30);
            mbar_wait(bar(B_ATT), 0);
            TSTAMP(31);
            poll_counter(&g_o_count[pb], 16);
            TSTAMP(18);
            fence_async_global();
            for (int jj = 0; jj < 4; jj++) {
                mbar_expect_tx(bar(B_O + jj), 16384);
                tma3d(sb + OFF_V + jj * 16384, &tm_o, 0, pb * 64, 2 * jj, bar(B_O + jj));
            }
            __threadfence();
            if (atomicAdd(&g_done, 1) == 2 * NCTA - 1) {
                for (int i = 0; i < NCTA; i++) g_stats[i] = 0ull;
                for (int i = 0; i < 4; i++) { g_kvt_count[i] = 0; g_z_count[i] = 0; }
                for (int i = 0; i < 32; i++) g_o_count[i] = 0;
                g_done = 0;
                __threadfence();
            }
        } else if (threadIdx.x == 128) {
            mbar_wait(bar(B_ATT), 0);
            mbar_expect_tx(bar(B_WO + 3), 32768);
            tma4d(sb + OFF_K + 32768, &tm_wo, 0, 0, hg * 2, 6, bar(B_WO + 3));
        }
        __syncwarp();
#pragma unroll
        for (int i = 0; i < 16; i++) acc[i] = 0.f;
        fence_regs<16>(acc);
#pragma unroll 1
        for (int jj = 0; jj < 4; jj++) {
            mbar_wait_w(bar(B_WO + jj), 0);
            mbar_wait_w(bar(B_O + jj), 0);
            if (threadIdx.x == 0 && (jj == 0 || jj == 3)) TSTAMP(jj == 0 ? 32 : 33);
            const uint32_t wb = sb + (jj < 2 ? OFF_X + jj * 32768 : (jj == 2 ? OFF_K : OFF_K + 32768)) + bcol;
            wg_fence();
            gemm_chunk(acc, sb + OFF_V + jj * 16384, wb);
            gemm_chunk(acc, sb + OFF_V + jj * 16384 + 8192, wb + 16384);
            wg_commit();
        }
        wg_wait<0>();
        fence_regs<16>(acc);
        {
            const int row = pb * 64 + wq * 16 + g;
            uint32_t* d0 = (uint32_t*)(prm.out + (size_t)row * 1024 + 512 + hg * 128 + w * 32) + t;
            uint32_t* d1 = d0 + 8 * 512;
#pragma unroll
            for (int i = 0; i < 4; i++) {
                d0[4 * i] = pack_bf16(acc[4 * i], acc[4 * i + 1]);
                d1[4 * i] = pack_bf16(acc[4 * i + 2], acc[4 * i + 3]);
            }
        }
        if ((threadIdx.x & 127) == 0 && w == 0) TSTAMP(5);
    } else {
        const int wa = warp_id - 16, tau = threadIdx.x - 512;
        __syncthreads();
        const bool kv_cta = (hg == (pb & 3));
        if (tau == 0) {
            if (kv_cta) {
                mbar_expect_tx(bar(B_WKV), 32768);
                tma3d(sb + OFF_C, &tm_wk, 0, 0, 0, bar(B_WKV));
                tma3d(sb + OFF_C + 16384, &tm_wv, 0, 0, 0, bar(B_WKV));
            }
            for (int jj = 0; jj < 4; jj++) {
                mbar_expect_tx(bar(B_X + jj), 16384);
                tma3d(sb + OFF_X + jj * 16384, &tm_x, 0, pb * 64, 2 * jj, bar(B_X + jj));
                if (!kv_cta && jj < 2) {
                    mbar_expect_tx(bar(B_W + jj), 32768);
                    tma4d(sb + OFF_V + jj * 32768, &tm_wq, 0, 0, hg * 2, 2 * jj, bar(B_W + jj));
                }
            }
            TSTAMP(25);
        }
        __syncwarp();
        if (kv_cta) {
            float acc[16];
#pragma unroll
            for (int i = 0; i < 16; i++) acc[i] = 0.f;
            fence_regs<16>(acc);
            mbar_wait_w(bar(B_WKV), 0);
            if (tau == 0) TSTAMP(20);
#pragma unroll
            for (int jj = 0; jj < 4; jj++) {
                mbar_wait_w(bar(B_X + jj), 0);
                wg_fence();
#pragma unroll
                for (int j = 2 * jj; j < 2 * jj + 2; j++) {
                    const uint64_t da = make_desc(sb + OFF_X + j * 8192, 16, 1024, 1);
                    const uint64_t db = make_desc(sb + OFF_C + j * 2048, 16384, 256, 3);
#pragma unroll
                    for (int ks = 0; ks < 4; ks++) wg_ss_n32_tb(acc, da + ks * 2, db + ks * 32);
                }
                wg_commit();
            }
            wg_wait<0>();
            fence_regs<16>(acc);
            if (tau == 0) TSTAMP(22);
            {
                uint32_t kk[4], vv[4];
#pragma unroll
                for (int i = 0; i < 4; i++) { kk[i] = pack_bf16(acc[2 * i], acc[2 * i + 1]); vv[i] = pack_bf16(acc[8 + 2 * i], acc[8 + 2 * i + 1]); }
                const int s = 4 * pb + wa;
                uint32_t* kp = (uint32_t*)(g_kimg + s * 512 + g * 16 + 4 * t);
                kp[0] = kk[0]; kp[64] = kk[1]; kp[32] = kk[2]; kp[96] = kk[3];
                uint32_t* vlo = (uint32_t*)(g_vimg + (127 - s) * 256 + g * 16 + 4 * t);
                uint32_t* vhi = (uint32_t*)(g_vimg + 32768 + 256 + s * 256 + g * 16 + 4 * t);
                vlo[0] = pack_f16(bf_lo(vv[0]), bf_hi(vv[0])); vlo[32] = pack_f16(bf_lo(vv[1]), bf_hi(vv[1]));
                vhi[0] = pack_f16(bf_lo(vv[2]), bf_hi(vv[2])); vhi[32] = pack_f16(bf_lo(vv[3]), bf_hi(vv[3]));
                uint32_t* vr = (uint32_t*)(g_vraw + (size_t)(16 * s + g) * 16) + t;
                vr[0] = vv[0]; vr[64] = vv[1]; vr[4] = vv[2]; vr[68] = vv[3];
                float n0 = bf_lo(kk[0]) * bf_lo(kk[0]) + bf_hi(kk[0]) * bf_hi(kk[0]) + bf_lo(kk[2]) * bf_lo(kk[2]) + bf_hi(kk[2]) * bf_hi(kk[2]);
                float n1 = bf_lo(kk[1]) * bf_lo(kk[1]) + bf_hi(kk[1]) * bf_hi(kk[1]) + bf_lo(kk[3]) * bf_lo(kk[3]) + bf_hi(kk[3]) * bf_hi(kk[3]);
                n0 += __shfl_xor_sync(0xffffffffu, n0, 1); n0 += __shfl_xor_sync(0xffffffffu, n0, 2);
                n1 += __shfl_xor_sync(0xffffffffu, n1, 1); n1 += __shfl_xor_sync(0xffffffffu, n1, 2);
                float km = fmaxf(n0, n1), vm = 0.f;
#pragma unroll
                for (int i = 0; i < 4; i++) vm = fmaxf(vm, fmaxf(fabsf(bf_lo(vv[i])), fabsf(bf_hi(vv[i]))));
#pragma unroll
                for (int o = 4; o < 32; o <<= 1) km = fmaxf(km, __shfl_xor_sync(0xffffffffu, km, o));
#pragma unroll
                for (int o = 1; o < 32; o <<= 1) vm = fmaxf(vm, __shfl_xor_sync(0xffffffffu, vm, o));
                __syncwarp();
                if (lane == 0) {
                    const unsigned long long rec = ((unsigned long long)(__float_as_uint(vm) | 0x80000000u) << 32) | __float_as_uint(km);
                    asm volatile("st.release.gpu.global.u64 [%0], %1;" ::"l"(&g_stats[s]), "l"(rec) : "memory");
                    if (wa == 0) TSTAMP(8);
                }
            }
            if (tau == 0) {
                for (int jj = 0; jj < 2; jj++) {
                    mbar_expect_tx(bar(B_W + jj), 32768);
                    tma4d(sb + OFF_V + jj * 32768, &tm_wq, 0, 0, hg * 2, 2 * jj, bar(B_W + jj));
                }
            }
            __syncwarp();
        }
        const int c0 = 4 * b;
        if (wa == 1) {
            float km = 0.f, vm = 0.f;
            {
                unsigned long long rec[4];
                uint32_t spins = 0;
                bool ok;
                do {
                    ok = true;
#pragma unroll
                    for (int i = 0; i < 4; i++) {
                        asm volatile("ld.relaxed.gpu.global.u64 %0, [%1];" : "=l"(rec[i]) : "l"(&g_stats[lane + 32 * i]) : "memory");
                        ok = ok && (rec[i] >> 63);
                    }
                    if (++spins > (1u << 22)) __trap();
                } while (!__all_sync(0xffffffffu, ok));
                asm volatile("fence.acq_rel.gpu;" ::: "memory");
#pragma unroll
                for (int i = 0; i < 4; i++) { km = fmaxf(km, __uint_as_float((uint32_t)rec[i])); vm = fmaxf(vm, __uint_as_float((uint32_t)(rec[i] >> 32) & 0x7FFFFFFFu)); }
            }
            if (lane == 0) {
                TSTAMP(16);
                fence_async_global();
                for (int c = 0; c < 8; c++) {
                    mbar_expect_tx_noarrive(bar(B_KV + c), 8192);
                    bulk_g2s(sb + OFF_K + c * 8192, g_kimg + c * 8192, 8192, bar(B_KV + c));
                }
                TSTAMP(28);
            }
#pragma unroll
            for (int o = 1; o < 32; o <<= 1) { km = fmaxf(km, __shfl_xor_sync(0xffffffffu, km, o)); vm = fmaxf(vm, __shfl_xor_sync(0xffffffffu, vm, o)); }
            const bool vdirect = (vm <= 32768.f && vm >= 9.765625e-4f) || vm == 0.f;
            float vs = 1.f;
            if (!vdirect && vm < INFINITY) {
                int e = (int)((__float_as_uint(vm) >> 23) & 0xFF) - 127;
                e = max(-100, min(100, e));
                vs = __uint_as_float((uint32_t)(127 + e - 13) << 23);
            }
            if (lane == 0) {
                asm volatile("st.shared.f32 [%0], %1;" ::"r"(sb + OFF_MISC), "f"(km) : "memory");
                asm volatile("st.shared.f32 [%0], %1;" ::"r"(sb + OFF_MISC + 4), "f"(vs) : "memory");
                mbar_wait(bar(B_QDONE), 0);
                TSTAMP(17);
                for (int c = 0; c < 8; c++) {
                    if (vdirect) {
                        mbar_expect_tx(bar(B_KV + c), 8192);
                        bulk_g2s(sb + OFF_V + (112 - 16 * c) * 256, g_vimg + (112 - 16 * c) * 256, 4096, bar(B_KV + c));
                        bulk_g2s(sb + OFF_VONES + 256 + c * 4096, g_vimg + 32768 + 256 + c * 4096, 4096, bar(B_KV + c));
                    }
                }
            }
            __syncwarp();
            sts32(sb + OFF_VONES + lane * 8, 0x3C003C00u);
            sts32(sb + OFF_VONES + lane * 8 + 4, 0x3C003C00u);
            if (!vdirect) {
                const float inv = 1.f / vs;
                for (int idx = lane; idx < S_LEN * 8; idx += 32) {
                    const int key = idx >> 3, dp = idx & 7;
                    const uint32_t v = __ldcg((const uint32_t*)g_vraw + idx);
                    const uint32_t h = pack_f16(bf_lo(v) * inv, bf_hi(v) * inv);
                    const int st = key >> 4, hf = (key >> 3) & 1;
                    const uint32_t base = (dp < 4) ? (OFF_V + (127 - st) * 256) : (OFF_VONES + 256 + st * 256);
                    sts32(sb + base + hf * 128 + (key & 7) * 16 + (dp & 3) * 4, h);
                }
            }
            fence_async_smem();
            __syncwarp();
            if (lane == 0) {
                mbar_arrive(bar(B_KV + 0));
                if (!vdirect) for (int c = 0; c < 8; c++) mbar_arrive(bar(B_KV + c));
            }
            __syncwarp();
        } else if (wa >= 2) {
            const int kch0 = hg * 128 + lane * 4;
            uint32_t wA[4], wB[4];
            {
                const uint4 s0 = __ldg((const uint4*)(prm.shift_k + kch0 * 4));
                const uint4 s1 = __ldg((const uint4*)(prm.shift_k + kch0 * 4) + 1);
                wA[0] = __byte_perm(s0.x, s0.z, 0x5410); wA[1] = __byte_perm(s0.x, s0.z, 0x7632);
                wA[2] = __byte_perm(s0.y, s0.w, 0x5410); wA[3] = __byte_perm(s0.y, s0.w, 0x7632);
                wB[0] = __byte_perm(s1.x, s1.z, 0x5410); wB[1] = __byte_perm(s1.x, s1.z, 0x7632);
                wB[2] = __byte_perm(s1.y, s1.w, 0x5410); wB[3] = __byte_perm(s1.y, s1.w, 0x7632);
            }
            mbar_wait_w(bar(B_KVIN), 0);
            const uint32_t kb = sb + OFF_C + (wa - 2) * 32 * 256 + lane * 8, vb = kb + 17408;
            uint32_t k0a, k0b, k1a, k1b, k2a, k2b;
            lds64(kb, k0a, k0b); lds64(kb + 256, k1a, k1b); lds64(kb + 512, k2a, k2b);
#pragma unroll
            for (int o8 = 0; o8 < 4; o8++) {
                uint32_t xa[8], xb[8];
#pragma unroll
                for (int i = 0; i < 8; i++) {
                    uint32_t k3a, k3b, va, vb2;
                    lds64(kb + (o8 * 8 + i + 3) * 256, k3a, k3b);
                    lds64(vb + (o8 * 8 + i) * 256, va, vb2);
                    xa[i] = bmul2(badd2(badd2(badd2(bmul2(k0a, wA[3]), bmul2(k1a, wA[2])), bmul2(k2a, wA[1])), bmul2(k3a, wA[0])), va);
                    xb[i] = bmul2(badd2(badd2(badd2(bmul2(k0b, wB[3]), bmul2(k1b, wB[2])), bmul2(k2b, wB[1])), bmul2(k3b, wB[0])), vb2);
                    k0a = k1a; k0b = k1b; k1a = k2a; k1b = k2b; k2a = k3a; k2b = k3b;
                }
                uint4* dst = (uint4*)(g_kvT + (size_t)kch0 * S_LEN + pb * 64 + (wa - 2) * 32 + o8 * 8);
                dst[0] = make_uint4(__byte_perm(xa[0], xa[1], 0x5410), __byte_perm(xa[2], xa[3], 0x5410), __byte_perm(xa[4], xa[5], 0x5410), __byte_perm(xa[6], xa[7], 0x5410));
                dst[S_LEN / 8] = make_uint4(__byte_perm(xa[0], xa[1], 0x7632), __byte_perm(xa[2], xa[3], 0x7632), __byte_perm(xa[4], xa[5], 0x7632), __byte_perm(xa[6], xa[7], 0x7632));
                dst[2 * (S_LEN / 8)] = make_uint4(__byte_perm(xb[0], xb[1], 0x5410), __byte_perm(xb[2], xb[3], 0x5410), __byte_perm(xb[4], xb[5], 0x5410), __byte_perm(xb[6], xb[7], 0x5410));
                dst[3 * (S_LEN / 8)] = make_uint4(__byte_perm(xb[0], xb[1], 0x7632), __byte_perm(xb[2], xb[3], 0x7632), __byte_perm(xb[4], xb[5], 0x7632), __byte_perm(xb[6], xb[7], 0x7632));
            }
            mbar_arrive(bar(B_KVT));
            mbar_wait_w(bar(B_KVT), 0);
            sts128(sb + C_H + (tau - 64) * 32, 0u, 0u, 0u, 0u);
            sts128(sb + C_H + (tau - 64) * 32 + 16, 0u, 0u, 0u, 0u);
            fence_async_smem();
        } else {
            if (lane == 0) {
                mbar_wait(bar(B_W + KVIN_AFTER), 0);
                kv_tiles_load(sb, &tm_k, &tm_v, pb, hg);
                prefetch_tm(&tm_wo); prefetch_tm(&tm_o); prefetch_tm(&tm_h);
                mbar_wait(bar(B_KVT), 0);
                mbar_expect_tx(bar(B_H), 4096);
                tma2d(sb + C_H + 2048, &tm_h, 0, c0 * 64, bar(B_H));
                red_release_add(&g_kvt_count[hg], 1);
                TSTAMP(34);
                poll_counter(&g_kvt_count[b >> 5], 32);
                fence_async_global();
                mbar_expect_tx(bar(B_CV), 16384);
                bulk_g2s(sb + C_KVC, g_kvT + (size_t)c0 * S_LEN, 16384, bar(B_CV));
                mbar_wait(bar(B_QDONE), 0);
                for (int jj = 0; jj < 2; jj++) {
                    mbar_expect_tx(bar(B_WO + jj), 32768);
                    tma4d(sb + OFF_X + jj * 32768, &tm_wo, 0, 0, hg * 2, 2 * jj, bar(B_WO + jj));
                }
            }
            __syncwarp();
        }
        named_bar(5, 128);
        mbar_wait_w(bar(B_CV), 0);
        if (tau == 0) TSTAMP(9);
        const int NCH = 4;
#pragma unroll 1
        for (int ch = 0; ch < NCH; ch++) {
            if (ch >= 4 - TAIL_CH) mbar_wait_w(bar(B_ATT), 0);
            {
                const uint32_t src = sb + C_KVC + ch * 4096 + tau * 32;
                const uint4 u0 = lds128(src), u1 = lds128(src + 16);
                const uint32_t prev = tau > 0 ? lds32(src - 4) : 0u;
                const uint32_t zd = sb + C_Z + (32 + tau * 16) * 4;
                sts128(zd,      __byte_perm(u0.x, prev, 0x7610), __byte_perm(u0.x, u0.x, 0x1032), __byte_perm(u0.y, u0.x, 0x7610), __byte_perm(u0.y, u0.y, 0x1032));
                sts128(zd + 16, __byte_perm(u0.z, u0.y, 0x7610), __byte_perm(u0.z, u0.z, 0x1032), __byte_perm(u0.w, u0.z, 0x7610), __byte_perm(u0.w, u0.w, 0x1032));
                sts128(zd + 32, __byte_perm(u1.x, u0.w, 0x7610), __byte_perm(u1.x, u1.x, 0x1032), __byte_perm(u1.y, u1.x, 0x7610), __byte_perm(u1.y, u1.y, 0x1032));
                sts128(zd + 48, __byte_perm(u1.z, u1.y, 0x7610), __byte_perm(u1.z, u1.z, 0x1032), __byte_perm(u1.w, u1.z, 0x7610), __byte_perm(u1.w, u1.w, 0x1032));
                if (tau < 32) sts32(sb + C_Z + tau * 4, 0u);
            }
            named_bar(5, 128);
            mbar_wait_w(bar(B_H), ch & 1);
            float D[32];
#pragma unroll
            for (int i = 0; i < 32; i++) D[i] = 0.f;
            fence_regs<32>(D);
            const uint32_t z0 = sb + C_Z + (32 + 32 * (wa >> 1) + 16 * (wa & 1) + 2 * g - 2 * t) * 4;
            const uint64_t hd = make_desc(sb + C_H + 2048, 16, 512, 2);
            conv_phase<64>(D, z0, hd);
            float E[16];
#pragma unroll
            for (int i = 0; i < 16; i++) asm volatile("mov.f32 %0, %1;" : "=f"(E[i]) : "f"(D[16 + i]));
            conv_phase<32>(E, z0 + 4096, hd);
            if (tau == 0 && ch < 3) {
                mbar_expect_tx(bar(B_H), 4096);
                tma2d(sb + C_H + 2048, &tm_h, 0, (c0 + ch + 1) * 64, bar(B_H));
            }
            const int bb0 = 16 * (wa & 1) + 2 * g;
            const int xsw = (g & 3) << 3;
            {
                const uint32_t xb = sb + C_Z + (wa >> 1) * 4096;
#pragma unroll
                for (int jn = 0; jn < 4; jn++) {
#pragma unroll
                    for (int r = 0; r < 2; r++) {
                        const float v0 = (wa < 2) ? E[4 * jn + 2 * r] : D[4 * jn + 2 * r];
                        const float v1 = (wa < 2) ? E[4 * jn + 2 * r + 1] : D[4 * jn + 2 * r + 1];
                        sts64f(xb + ((bb0 + r) * 32 + ((8 * jn + 2 * t) ^ xsw)) * 4, v0, v1);
                    }
                }
            }
            named_bar(5, 128);
            {
                const float dsc = __bfloat162float(prm.ssm_D[c0 + ch]);
                const uint32_t xb = sb + C_Z + ((wa >> 1) ^ 1) * 4096;
#pragma unroll
                for (int jn = 0; jn < 4; jn++) {
#pragma unroll
                    for (int e = 0; e < 2; e++) {
                        const int n = 8 * jn + 2 * t + e;
                        float y0, y1; int m, rn;
                        if (wa < 2) { y0 = D[4 * jn + e]; y1 = D[4 * jn + 2 + e]; m = n; rn = n - 1; }
                        else {
                            const bool last = (jn == 3 && e == 1) && (t == 3);
                            y0 = last ? D[13] : E[4 * jn + e]; y1 = last ? D[15] : E[4 * jn + 2 + e];
                            m = last ? 32 : 33 + n; rn = m - 32;
                        }
                        if (rn >= 0) {
                            y0 += ldsf(xb + (bb0 * 32 + (rn ^ xsw)) * 4);
                            y1 += ldsf(xb + ((bb0 + 1) * 32 + (rn ^ xsw)) * 4);
                        }
                        const uint32_t addr = sb + C_KVC + ch * 4096 + (32 * m + bb0) * 2;
                        const uint32_t kv = lds32(addr);
                        const uint32_t yb = pack_bf16(y0, y1);
                        const uint32_t kd = pack_bf16(bf_lo(kv) * dsc, bf_hi(kv) * dsc);
                        sts32(addr, badd2(yb, kd));
                    }
                }
                fence_async_smem();
            }
            named_bar(5, 128);
            if (tau == 0) {
                bulk_s2g(g_zT + (size_t)(c0 + ch) * S_LEN, sb + C_KVC + ch * 4096, 4096);
                bulk_commit();
                TSTAMP(10 + ch);
            }
        }
        {
            const int cg = tau & 15, pr = tau >> 4;
            const int p0 = pb * 64 + pr * 8, ch0 = hg * 128 + cg * 8;
            uint4 qr[8];
#pragma unroll
            for (int i = 0; i < 8; i++) qr[i] = __ldg((const uint4*)(prm.aq + (size_t)(p0 + i) * 512 + ch0));
            if (tau == 0) {
                bulk_wait_all();
                fence_async_global();
                red_release_add(&g_z_count[b >> 5], 1);
                poll_counter(&g_z_count[hg], 32);
                __threadfence();
                if (atomicAdd(&g_done, 1) == 2 * NCTA - 1) {
                    for (int i = 0; i < NCTA; i++) g_stats[i] = 0ull;
                    for (int i = 0; i < 4; i++) { g_kvt_count[i] = 0; g_z_count[i] = 0; }
                    for (int i = 0; i < 32; i++) g_o_count[i] = 0;
                    g_done = 0;
                    __threadfence();
                }
            }
            named_bar(5, 128);
            uint4 zz[8];
#pragma unroll
            for (int c = 0; c < 8; c++) zz[c] = __ldcg((const uint4*)(g_zT + (size_t)(ch0 + c) * S_LEN + p0));
#pragma unroll
            for (int i = 0; i < 8; i++) {
                uint32_t r[4];
#pragma unroll
                for (int k = 0; k < 4; k++) {
                    const uint32_t pr2 = __byte_perm((&zz[2 * k].x)[i >> 1], (&zz[2 * k + 1].x)[i >> 1], (i & 1) ? 0x7632 : 0x5410);
                    r[k] = bmul2((&qr[i].x)[k], pr2);
                }
                *(uint4*)(prm.out + (size_t)(p0 + i) * 1024 + ch0) = make_uint4(r[0], r[1], r[2], r[3]);
            }
        }
        if (tau == 0) TSTAMP(14);
    }
}

typedef CUresult (*EncodeFn)(CUtensorMap*, CUtensorMapDataType, cuuint32_t, void*, const cuuint64_t*, const cuuint64_t*,
                             const cuuint32_t*, const cuuint32_t*, CUtensorMapInterleave, CUtensorMapSwizzle,
                             CUtensorMapL2promotion, CUtensorMapFloatOOBfill);

void make_map(EncodeFn fn, CUtensorMap* tm, const void* ptr, int rank, const cuuint64_t* dims, const cuuint64_t* strides, const cuuint32_t* box, CUtensorMapSwizzle swz) {
    cuuint32_t es[4] = {1, 1, 1, 1};
    fn(tm, CU_TENSOR_MAP_DATA_TYPE_BFLOAT16, rank, const_cast<void*>(ptr), dims, strides, box, es, CU_TENSOR_MAP_INTERLEAVE_NONE, swz,
       CU_TENSOR_MAP_L2_PROMOTION_L2_128B, CU_TENSOR_MAP_FLOAT_OOB_FILL_NONE);
}

}

extern "C" void kernel_launch(void* const* d_in, const int* in_sizes, int n_in, void* d_out, int out_size) {
    (void)in_sizes; (void)n_in; (void)out_size;
    static EncodeFn encode = nullptr;
    static void* o_ptr = nullptr;
    if (!encode) {
        cudaDriverEntryPointQueryResult qres;
        void* fn = nullptr;
        cudaGetDriverEntryPoint("cuTensorMapEncodeTiled", &fn, cudaEnableDefault, &qres);
        encode = (EncodeFn)fn;
        cudaGetSymbolAddress(&o_ptr, g_o);
        cudaFuncSetAttribute(fused_kernel, cudaFuncAttributeMaxDynamicSharedMemorySize, SMEM_TOTAL);
    }
    CUtensorMap tm_x, tm_wq, tm_wo, tm_wk, tm_wv, tm_o, tm_h, tm_k, tm_v;
    {
        const cuuint64_t dims[3] = {64, 2048, 8}, str[2] = {1024, 128};
        const cuuint32_t b64[3] = {64, 64, 2};
        make_map(encode, &tm_x, d_in[6], 3, dims, str, b64, CU_TENSOR_MAP_SWIZZLE_128B);
        make_map(encode, &tm_o, o_ptr, 3, dims, str, b64, CU_TENSOR_MAP_SWIZZLE_128B);
    }
    {
        const cuuint64_t dims[4] = {64, 64, 8, 8}, str[3] = {1024, 128, 65536};
        const cuuint32_t box[4] = {64, 64, 2, 2};
        make_map(encode, &tm_wq, d_in[7], 4, dims, str, box, CU_TENSOR_MAP_SWIZZLE_128B);
        make_map(encode, &tm_wo, d_in[10], 4, dims, str, box, CU_TENSOR_MAP_SWIZZLE_128B);
    }
    {
        const cuuint64_t dims[3] = {16, 256, 2}, str[2] = {32, 8192};
        const cuuint32_t box[3] = {16, 256, 2};
        make_map(encode, &tm_wk, d_in[8], 3, dims, str, box, CU_TENSOR_MAP_SWIZZLE_32B);
        make_map(encode, &tm_wv, d_in[9], 3, dims, str, box, CU_TENSOR_MAP_SWIZZLE_32B);
    }
    {
        const cuuint64_t dims[2] = {32, 512 * 64}, str[1] = {64};
        const cuuint32_t box[2] = {32, 64};
        make_map(encode, &tm_h, d_in[4], 2, dims, str, box, CU_TENSOR_MAP_SWIZZLE_64B);
    }
    {
        const cuuint64_t dims[2] = {512, 2048}, str[1] = {1024};
        const cuuint32_t bk[2] = {128, 67}, bv[2] = {128, 64};
        make_map(encode, &tm_k, d_in[1], 2, dims, str, bk, CU_TENSOR_MAP_SWIZZLE_NONE);
        make_map(encode, &tm_v, d_in[2], 2, dims, str, bv, CU_TENSOR_MAP_SWIZZLE_NONE);
    }
    Params prm;
    prm.aq = (const __nv_bfloat16*)d_in[0];
    prm.ak = (const __nv_bfloat16*)d_in[1];
    prm.av = (const __nv_bfloat16*)d_in[2];
    prm.shift_k = (const __nv_bfloat16*)d_in[3];
    prm.ssm_D = (const __nv_bfloat16*)d_in[5];
    prm.out = (__nv_bfloat16*)d_out;
    fused_kernel<<<NCTA, NTHREADS, SMEM_TOTAL>>>(tm_x, tm_wq, tm_wo, tm_wk, tm_wv, tm_o, tm_h, tm_k, tm_v, prm);
}
```

```cpp
#include <cuda_runtime.h>
#include <cuda_bf16.h>
#include <cuda_fp16.h>
#include <cuda.h>
#include <stdint.h>

#define LATE_WQ
#define TAIL_CH 0
#define KVIN_AFTER 3
namespace {

constexpr int S_LEN = 2048;
constexpr int NCTA = 128;
constexpr int NTHREADS = 640;

constexpr uint32_t OFF_K = 0;
constexpr uint32_t OFF_V = 65536;
constexpr uint32_t OFF_VONES = OFF_V + 32768;
constexpr uint32_t OFF_X = 132096;
constexpr uint32_t OFF_C = 197632;
constexpr uint32_t C_KVC = OFF_C;
constexpr uint32_t C_H = OFF_C + 16384;
constexpr uint32_t C_Z = C_H + 6144;
constexpr uint32_t OFF_BAR = 231936;
constexpr uint32_t SMEM_TOTAL = 232448;

enum { B_WKV = 0, B_X = 1, B_QEMPTY = 5, B_QDONE = 7, B_KV = 8, B_WO = 16, B_O = 20, B_ATT = 24, B_H = 25, B_CV = 26, B_W = 27, B_KVT = 31, B_KVIN = 32, B_COUNT = 33 };
constexpr uint32_t OFF_MISC = OFF_BAR + 8 * B_COUNT;

__device__ __align__(1024) uint8_t g_kimg[65536];
__device__ __align__(1024) uint8_t g_vimg[65792];
__device__ __align__(1024) __nv_bfloat16 g_vraw[S_LEN * 16];
__device__ __align__(1024) __nv_bfloat16 g_o[S_LEN * 512];
__device__ __align__(1024) __nv_bfloat16 g_kvT[512 * S_LEN];
__device__ __align__(1024) __nv_bfloat16 g_zT[512 * S_LEN];
__device__ unsigned long long g_stats[NCTA];
__device__ unsigned int g_kvt_count[4];
__device__ unsigned int g_z_count[4];
__device__ unsigned int g_o_count[32];
__device__ unsigned int g_done;
#define TSTAMP(i) do {} while (0)
#define CSTAMP(i) do {} while (0)

__device__ __forceinline__ void wg_fence() { asm volatile("wgmma.fence.sync.aligned;" ::: "memory"); }
__device__ __forceinline__ void wg_commit() { asm volatile("wgmma.commit_group.sync.aligned;" ::: "memory"); }
template <int N> __device__ __forceinline__ void wg_wait() { asm volatile("wgmma.wait_group.sync.aligned %0;" ::"n"(N) : "memory"); }
template <int N> __device__ __forceinline__ void fence_regs(float* r) {
#pragma unroll
    for (int i = 0; i < N; i++) asm volatile("" : "+f"(r[i])::"memory");
}
template <int N> __device__ __forceinline__ void fence_uregs(uint32_t* r) {
#pragma unroll
    for (int i = 0; i < N; i++) asm volatile("" : "+r"(r[i])::"memory");
}
__device__ __forceinline__ uint64_t make_desc(uint32_t saddr, uint32_t lbo, uint32_t sbo, uint32_t swz) {
    return (uint64_t)((saddr & 0x3FFFF) >> 4) | ((uint64_t)(lbo >> 4) << 16) | ((uint64_t)(sbo >> 4) << 32) | ((uint64_t)swz << 62);
}
__device__ __forceinline__ void mbar_init(uint32_t bar, uint32_t count) {
    asm volatile("mbarrier.init.shared::cta.b64 [%0], %1;" ::"r"(bar), "r"(count) : "memory");
}
__device__ __forceinline__ void mbar_expect_tx(uint32_t bar, uint32_t bytes) {
    asm volatile("mbarrier.arrive.expect_tx.shared::cta.b64 _, [%0], %1;" ::"r"(bar), "r"(bytes) : "memory");
}
__device__ __forceinline__ void mbar_expect_tx_noarrive(uint32_t bar, uint32_t bytes) {
    asm volatile("mbarrier.expect_tx.relaxed.cta.shared::cta.b64 [%0], %1;" ::"r"(bar), "r"(bytes) : "memory");
}
__device__ __forceinline__ void mbar_arrive(uint32_t bar) {
    asm volatile("mbarrier.arrive.shared::cta.b64 _, [%0];" ::"r"(bar) : "memory");
}
__device__ __forceinline__ bool mbar_try(uint32_t bar, uint32_t parity) {
    uint32_t ok;
    asm volatile("{\n.reg .pred p;\nmbarrier.try_wait.parity.shared::cta.b64 p, [%1], %2;\nselp.u32 %0, 1, 0, p;\n}\n"
                 : "=r"(ok) : "r"(bar), "r"(parity) : "memory");
    return ok != 0;
}
__device__ __forceinline__ void mbar_wait(uint32_t bar, uint32_t parity) {
    uint32_t spins = 0;
    while (!mbar_try(bar, parity)) {
        if (++spins > (1u << 24)) __trap();
    }
}
__device__ __forceinline__ void mbar_wait_w(uint32_t bar, uint32_t parity) {
    uint32_t spins = 0;
    while (!__all_sync(0xffffffffu, mbar_try(bar, parity))) {
        if (++spins > (1u << 24)) __trap();
    }
}
__device__ __forceinline__ void tma2d(uint32_t dst, const CUtensorMap* tm, int c0, int c1, uint32_t bar) {
    asm volatile("cp.async.bulk.tensor.2d.shared::cluster.global.mbarrier::complete_tx::bytes [%0], [%1, {%3, %4}], [%2];"
                 ::"r"(dst), "l"((uint64_t)tm), "r"(bar), "r"(c0), "r"(c1) : "memory");
}
__device__ __forceinline__ void tma3d(uint32_t dst, const CUtensorMap* tm, int c0, int c1, int c2, uint32_t bar) {
    asm volatile("cp.async.bulk.tensor.3d.shared::cluster.global.mbarrier::complete_tx::bytes [%0], [%1, {%3, %4, %5}], [%2];"
                 ::"r"(dst), "l"((uint64_t)tm), "r"(bar), "r"(c0), "r"(c1), "r"(c2) : "memory");
}
__device__ __forceinline__ void tma4d(uint32_t dst, const CUtensorMap* tm, int c0, int c1, int c2, int c3, uint32_t bar) {
    asm volatile("cp.async.bulk.tensor.4d.shared::cluster.global.mbarrier::complete_tx::bytes [%0], [%1, {%3, %4, %5, %6}], [%2];"
                 ::"r"(dst), "l"((uint64_t)tm), "r"(bar), "r"(c0), "r"(c1), "r"(c2), "r"(c3) : "memory");
}
__device__ __forceinline__ void prefetch_tm(const CUtensorMap* tm) { asm volatile("prefetch.tensormap [%0];" ::"l"((uint64_t)tm) : "memory"); }
__device__ __forceinline__ void bulk_s2g(void* dst, uint32_t src, uint32_t bytes) {
    asm volatile("cp.async.bulk.global.shared::cta.bulk_group [%0], [%1], %2;" ::"l"(dst), "r"(src), "r"(bytes) : "memory");
}
__device__ __forceinline__ void bulk_commit() { asm volatile("cp.async.bulk.commit_group;" ::: "memory"); }
__device__ __forceinline__ void bulk_wait_all() { asm volatile("cp.async.bulk.wait_group 0;" ::: "memory"); }
__device__ __forceinline__ void fence_async_global() { asm volatile("fence.proxy.async.global;" ::: "memory"); }
__device__ __forceinline__ void bulk_g2s(uint32_t dst, const void* src, uint32_t bytes, uint32_t bar) {
    asm volatile("cp.async.bulk.shared::cluster.global.mbarrier::complete_tx::bytes [%0], [%1], %2, [%3];"
                 ::"r"(dst), "l"(src), "r"(bytes), "r"(bar) : "memory");
}
__device__ __forceinline__ void fence_async_smem() { asm volatile("fence.proxy.async.shared::cta;" ::: "memory"); }
__device__ __forceinline__ void named_bar(int id, int n) { asm volatile("bar.sync %0, %1;" ::"r"(id), "r"(n) : "memory"); }
__device__ __forceinline__ bool named_bar_and(int id, int n, bool pred) {
    uint32_t r;
    asm volatile("{\n.reg .pred p, q;\nsetp.ne.u32 p, %3, 0;\nbarrier.cta.red.and.pred q, %1, %2, p;\nselp.u32 %0, 1, 0, q;\n}\n"
                 : "=r"(r) : "r"(id), "r"(n), "r"((uint32_t)pred) : "memory");
    return r != 0;
}
__device__ __forceinline__ unsigned int ld_acquire(const unsigned int* p) {
    unsigned int v;
    asm volatile("ld.acquire.gpu.global.u32 %0, [%1];" : "=r"(v) : "l"(p) : "memory");
    return v;
}
__device__ __forceinline__ void red_release_add(unsigned int* p, unsigned int v) {
    asm volatile("red.release.gpu.global.add.u32 [%0], %1;" ::"l"(p), "r"(v) : "memory");
}
__device__ __forceinline__ void poll_counter(const unsigned int* p, unsigned int target) {
    uint32_t spins = 0;
    while (ld_acquire(p) < target) {
        if (++spins > (1u << 22)) __trap();
    }
}
__device__ __forceinline__ float ex2f(float x) { float y; asm("ex2.approx.ftz.f32 %0, %1;" : "=f"(y) : "f"(x)); return y; }
__device__ __forceinline__ uint32_t pack_f16(float lo, float hi) { uint32_t r; asm("cvt.rn.f16x2.f32 %0, %1, %2;" : "=r"(r) : "f"(hi), "f"(lo)); return r; }
__device__ __forceinline__ uint32_t pack_bf16(float lo, float hi) { uint32_t r; asm("cvt.rn.bf16x2.f32 %0, %1, %2;" : "=r"(r) : "f"(hi), "f"(lo)); return r; }
__device__ __forceinline__ float bf_lo(uint32_t v) { return __uint_as_float(v << 16); }
__device__ __forceinline__ float bf_hi(uint32_t v) { return __uint_as_float(v & 0xFFFF0000u); }
__device__ __forceinline__ uint32_t hfma2(uint32_t a, uint32_t b, uint32_t c) { uint32_t r; asm("fma.rn.f16x2 %0, %1, %2, %3;" : "=r"(r) : "r"(a), "r"(b), "r"(c)); return r; }
__device__ __forceinline__ uint32_t bmul2(uint32_t a, uint32_t b) { uint32_t r; asm("mul.rn.bf16x2 %0, %1, %2;" : "=r"(r) : "r"(a), "r"(b)); return r; }
__device__ __forceinline__ uint32_t badd2(uint32_t a, uint32_t b) { uint32_t r; asm("add.rn.bf16x2 %0, %1, %2;" : "=r"(r) : "r"(a), "r"(b)); return r; }
template <int LUT> __device__ __forceinline__ uint32_t lop3(uint32_t a, uint32_t b, uint32_t c) {
    uint32_t r; asm("lop3.b32 %0, %1, %2, %3, %4;" : "=r"(r) : "r"(a), "r"(b), "r"(c), "n"(LUT)); return r;
}
__device__ __forceinline__ uint32_t lds32(uint32_t a) { uint32_t v; asm volatile("ld.shared.u32 %0, [%1];" : "=r"(v) : "r"(a)); return v; }
__device__ __forceinline__ float ldsf(uint32_t a) { float v; asm volatile("ld.shared.f32 %0, [%1];" : "=f"(v) : "r"(a)); return v; }
__device__ __forceinline__ uint4 lds128(uint32_t a) { uint4 v; asm volatile("ld.shared.v4.u32 {%0,%1,%2,%3}, [%4];" : "=r"(v.x), "=r"(v.y), "=r"(v.z), "=r"(v.w) : "r"(a)); return v; }
__device__ __forceinline__ void lds64(uint32_t a, uint32_t& x, uint32_t& y) { asm volatile("ld.shared.v2.u32 {%0,%1}, [%2];" : "=r"(x), "=r"(y) : "r"(a)); }
__device__ __forceinline__ void sts32(uint32_t a, uint32_t v) { asm volatile("st.shared.u32 [%0], %1;" ::"r"(a), "r"(v) : "memory"); }
__device__ __forceinline__ void sts64f(uint32_t a, float x, float y) { asm volatile("st.shared.v2.f32 [%0], {%1,%2};" ::"r"(a), "f"(x), "f"(y) : "memory"); }
__device__ __forceinline__ void sts128(uint32_t a, uint32_t x, uint32_t y, uint32_t z, uint32_t w) {
    asm volatile("st.shared.v4.u32 [%0], {%1,%2,%3,%4};" ::"r"(a), "r"(x), "r"(y), "r"(z), "r"(w) : "memory");
}

__device__ __forceinline__ void wg_ss_n32_tb(float* d, uint64_t descA, uint64_t descB) {
    asm volatile("wgmma.mma_async.sync.aligned.m64n32k16.f32.bf16.bf16 {%0,%1,%2,%3,%4,%5,%6,%7,%8,%9,%10,%11,%12,%13,%14,%15}, %16, %17, 1, 1, 1, 0, 1;\n"
        : "+f"(d[0]), "+f"(d[1]), "+f"(d[2]), "+f"(d[3]), "+f"(d[4]), "+f"(d[5]), "+f"(d[6]), "+f"(d[7]), "+f"(d[8]), "+f"(d[9]), "+f"(d[10]), "+f"(d[11]), "+f"(d[12]), "+f"(d[13]), "+f"(d[14]), "+f"(d[15])
        : "l"(descA), "l"(descB));
}
__device__ __forceinline__ void wg_qk_n64(float* d, const uint32_t* a, uint64_t desc) {
    asm volatile("wgmma.mma_async.sync.aligned.m64n64k16.f32.bf16.bf16 {%0,%1,%2,%3,%4,%5,%6,%7,%8,%9,%10,%11,%12,%13,%14,%15,%16,%17,%18,%19,%20,%21,%22,%23,%24,%25,%26,%27,%28,%29,%30,%31}, {%32,%33,%34,%35}, %36, 0, 1, 1, 0;\n"
        : "+f"(d[0]), "+f"(d[1]), "+f"(d[2]), "+f"(d[3]), "+f"(d[4]), "+f"(d[5]), "+f"(d[6]), "+f"(d[7]), "+f"(d[8]), "+f"(d[9]), "+f"(d[10]), "+f"(d[11]), "+f"(d[12]), "+f"(d[13]), "+f"(d[14]), "+f"(d[15]), "+f"(d[16]), "+f"(d[17]), "+f"(d[18]), "+f"(d[19]), "+f"(d[20]), "+f"(d[21]), "+f"(d[22]), "+f"(d[23]), "+f"(d[24]), "+f"(d[25]), "+f"(d[26]), "+f"(d[27]), "+f"(d[28]), "+f"(d[29]), "+f"(d[30]), "+f"(d[31])
        : "r"(a[0]), "r"(a[1]), "r"(a[2]), "r"(a[3]), "l"(desc));
}
__device__ __forceinline__ void wg_pv_n24(float* d, const uint32_t* a, uint64_t desc) {
    asm volatile("wgmma.mma_async.sync.aligned.m64n24k16.f32.f16.f16 {%0,%1,%2,%3,%4,%5,%6,%7,%8,%9,%10,%11}, {%12,%13,%14,%15}, %16, 1, 1, 1, 1;\n"
        : "+f"(d[0]), "+f"(d[1]), "+f"(d[2]), "+f"(d[3]), "+f"(d[4]), "+f"(d[5]), "+f"(d[6]), "+f"(d[7]), "+f"(d[8]), "+f"(d[9]), "+f"(d[10]), "+f"(d[11])
        : "r"(a[0]), "r"(a[1]), "r"(a[2]), "r"(a[3]), "l"(desc));
}
__device__ __forceinline__ void wg_cv_n32(float* d, const uint32_t* a, uint64_t desc) {
    asm volatile("wgmma.mma_async.sync.aligned.m64n32k16.f32.bf16.bf16 {%0,%1,%2,%3,%4,%5,%6,%7,%8,%9,%10,%11,%12,%13,%14,%15}, {%16,%17,%18,%19}, %20, 1, 1, 1, 0;\n"
        : "+f"(d[0]), "+f"(d[1]), "+f"(d[2]), "+f"(d[3]), "+f"(d[4]), "+f"(d[5]), "+f"(d[6]), "+f"(d[7]), "+f"(d[8]), "+f"(d[9]), "+f"(d[10]), "+f"(d[11]), "+f"(d[12]), "+f"(d[13]), "+f"(d[14]), "+f"(d[15])
        : "r"(a[0]), "r"(a[1]), "r"(a[2]), "r"(a[3]), "l"(desc));
}
__device__ __forceinline__ void wg_cv_n64(float* d, const uint32_t* a, uint64_t desc) {
    asm volatile("wgmma.mma_async.sync.aligned.m64n64k16.f32.bf16.bf16 {%0,%1,%2,%3,%4,%5,%6,%7,%8,%9,%10,%11,%12,%13,%14,%15,%16,%17,%18,%19,%20,%21,%22,%23,%24,%25,%26,%27,%28,%29,%30,%31}, {%32,%33,%34,%35}, %36, 1, 1, 1, 0;\n"
        : "+f"(d[0]), "+f"(d[1]), "+f"(d[2]), "+f"(d[3]), "+f"(d[4]), "+f"(d[5]), "+f"(d[6]), "+f"(d[7]), "+f"(d[8]), "+f"(d[9]), "+f"(d[10]), "+f"(d[11]), "+f"(d[12]), "+f"(d[13]), "+f"(d[14]), "+f"(d[15]), "+f"(d[16]), "+f"(d[17]), "+f"(d[18]), "+f"(d[19]), "+f"(d[20]), "+f"(d[21]), "+f"(d[22]), "+f"(d[23]), "+f"(d[24]), "+f"(d[25]), "+f"(d[26]), "+f"(d[27]), "+f"(d[28]), "+f"(d[29]), "+f"(d[30]), "+f"(d[31])
        : "r"(a[0]), "r"(a[1]), "r"(a[2]), "r"(a[3]), "l"(desc));
}

template <int N> __device__ __forceinline__ void wg_cv(float* d, const uint32_t* a, uint64_t desc);
template <> __device__ __forceinline__ void wg_cv<32>(float* d, const uint32_t* a, uint64_t s) { wg_cv_n32(d, a, s); }
template <> __device__ __forceinline__ void wg_cv<64>(float* d, const uint32_t* a, uint64_t s) { wg_cv_n64(d, a, s); }

constexpr uint32_t POLYMASK = 0xB5B5u;
__device__ __forceinline__ void softmax_fast(const float* s, uint32_t* p, uint32_t mlo) {
    const uint32_t C3 = 0x2cfb2cfbu, C2 = 0x9fec9fecu, C1 = 0x37a837a8u, C0 = 0x37383738u;
#pragma unroll
    for (int i = 0; i < 16; i++) {
        const float s0 = s[2 * i], s1 = s[2 * i + 1];
        if ((POLYMASK >> i) & 1) {
            const float t0 = s0 + 12303.0f, t1 = s1 + 12303.0f;
            const uint32_t T = __byte_perm(__float_as_uint(t0), __float_as_uint(t1), 0x5410);
            const uint32_t U = lop3<0xEA>(T, mlo, 0x3C003C00u);
            uint32_t h = hfma2(U, C3, C2);
            h = hfma2(h, U, C1);
            h = hfma2(h, U, C0);
            p[i] = lop3<0xE4>(h, T, 0x03FF03FFu);
        } else {
            p[i] = pack_f16(ex2f(s0), ex2f(s1));
        }
    }
}

__device__ __forceinline__ void gemm_chunk(float* acc, uint32_t a_addr, uint32_t b_addr) {
    const uint64_t da = make_desc(a_addr, 16, 1024, 1);
    const uint64_t db = make_desc(b_addr, 8192, 1024, 1);
#pragma unroll
    for (int ks = 0; ks < 4; ks++) wg_ss_n32_tb(acc, da + ks * 2, db + ks * 128);
}

__device__ __forceinline__ uint32_t smem_inc(uint32_t addr) {
    uint32_t old;
    asm volatile("atom.acq_rel.cta.shared.add.u32 %0, [%1], 1;" : "=r"(old) : "r"(addr) : "memory");
    return old;
}
__device__ __forceinline__ void wo_half(uint32_t sb, const CUtensorMap* tm_wo, int hg) {
    if (smem_inc(sb + OFF_MISC + 8) == 3) {
        mbar_expect_tx(sb + OFF_BAR + 8 * (B_WO + 2), 32768);
        tma4d(sb + OFF_K, tm_wo, 0, 0, hg * 2, 4, sb + OFF_BAR + 8 * (B_WO + 2));
    }
}

__device__ __forceinline__ void kv_tiles_load(uint32_t sb, const CUtensorMap* tm_k, const CUtensorMap* tm_v, int pb, int hg) {
    const uint32_t br = sb + OFF_BAR + 8 * B_KVIN;
    mbar_expect_tx(br, 67 * 256 + 64 * 256);
    tma2d(sb + OFF_C, tm_k, hg * 128, pb * 64 - 3, br);
    tma2d(sb + OFF_C + 17408, tm_v, hg * 128, pb * 64, br);
}

struct Params {
    const __nv_bfloat16 *aq, *ak, *av, *shift_k, *ssm_D;
    __nv_bfloat16* out;
};

template <int NQ>
__device__ __forceinline__ void conv_phase(float* Dn, uint32_t zaddr, uint64_t hdesc) {
    uint32_t a[2][16];
#pragma unroll
    for (int st = 0; st < 8; st++) {
        uint32_t* aa = a[st & 1];
        if (st >= 2) wg_wait<1>();
#pragma unroll
        for (int u = 0; u < 2; u++) {
            const uint32_t z = zaddr + (st * 2 + u) * 256;
            lds64(z, aa[8 * u + 0], aa[8 * u + 1]);      lds64(z - 32, aa[8 * u + 2], aa[8 * u + 3]);
            lds64(z - 64, aa[8 * u + 4], aa[8 * u + 5]); lds64(z - 96, aa[8 * u + 6], aa[8 * u + 7]);
        }
        wg_fence();
#pragma unroll
        for (int u = 0; u < 2; u++) {
            const int qi = st * 2 + u;
            wg_cv<NQ>(Dn, &aa[8 * u], hdesc - qi * 8);
            wg_cv<NQ>(Dn, &aa[8 * u + 4], hdesc - qi * 8 + 2);
        }
        wg_commit();
    }
    wg_wait<0>();
    fence_regs<NQ / 2>(Dn);
}

__global__ void __launch_bounds__(NTHREADS, 1)
fused_kernel(const __grid_constant__ CUtensorMap tm_x,
             const __grid_constant__ CUtensorMap tm_wq, const __grid_constant__ CUtensorMap tm_wo,
             const __grid_constant__ CUtensorMap tm_wk, const __grid_constant__ CUtensorMap tm_wv,
             const __grid_constant__ CUtensorMap tm_o, const __grid_constant__ CUtensorMap tm_h,
             const __grid_constant__ CUtensorMap tm_k, const __grid_constant__ CUtensorMap tm_v, const Params prm) {
    extern __shared__ __align__(1024) uint8_t smem_raw[];
    const uint32_t sb = (uint32_t)__cvta_generic_to_shared(smem_raw);
    const int warp_id = __shfl_sync(0xffffffffu, threadIdx.x >> 5, 0);
    const int lane = threadIdx.x & 31;
    const int g = lane >> 2, t = lane & 3;
    const int b = blockIdx.x, pb = b >> 2, hg = b & 3;
    auto bar = [&](int i) { return sb + OFF_BAR + 8 * i; };

    if (threadIdx.x == 512) {
        TSTAMP(0);
        prefetch_tm(&tm_x); prefetch_tm(&tm_wq); prefetch_tm(&tm_wk); prefetch_tm(&tm_wv);
        mbar_init(bar(B_WKV), 1);
        for (int j = 0; j < 4; j++) { mbar_init(bar(B_X + j), 1); mbar_init(bar(B_W + j), 1); mbar_init(bar(B_WO + j), 1); mbar_init(bar(B_O + j), 1); }
        sts32(sb + OFF_MISC + 8, 0u); sts32(sb + OFF_MISC + 12, 0u); sts32(sb + OFF_MISC + 16, 0u);
        for (int j = 0; j < 8; j++) mbar_init(bar(B_KV + j), j == 0 ? 2 : 1);
        mbar_init(bar(B_QEMPTY), 4); mbar_init(bar(B_QEMPTY + 1), 4);
        mbar_init(bar(B_QDONE), 4); mbar_init(bar(B_ATT), 4);
        mbar_init(bar(B_H), 1); mbar_init(bar(B_CV), 1); mbar_init(bar(B_KVT), 64); mbar_init(bar(B_KVIN), 1);
        asm volatile("fence.mbarrier_init.release.cluster;" ::: "memory");
    }

    if (warp_id < 16) {
        const int w = warp_id >> 2, wq = warp_id & 3;
        __syncthreads();
        float acc[16];
#pragma unroll
        for (int i = 0; i < 16; i++) acc[i] = 0.f;
        fence_regs<16>(acc);
        const uint32_t bcol = (w >> 1) * 8192 + (w & 1) * 64;
#pragma unroll 1
        for (int jj = 0; jj < 4; jj++) {
            mbar_wait_w(bar(B_X + jj), 0);
            mbar_wait_w(bar(B_W + jj), 0);
            if (threadIdx.x == 0) TSTAMP(jj == 0 ? 23 : jj == 1 ? 24 : jj == 2 ? 26 : 27);
            wg_fence();
            gemm_chunk(acc, sb + OFF_X + jj * 16384, sb + OFF_V + (jj & 1) * 32768 + bcol);
            gemm_chunk(acc, sb + OFF_X + jj * 16384 + 8192, sb + OFF_V + (jj & 1) * 32768 + 16384 + bcol);
            wg_commit();
            wg_wait<0>();
            if (jj < 2 && (threadIdx.x & 127) == 0) {
                if (smem_inc(sb + OFF_MISC + 12 + 4 * jj) == 3) {
                    mbar_expect_tx(bar(B_W + jj + 2), 32768);
                    tma4d(sb + OFF_V + jj * 32768, &tm_wq, 0, 0, hg * 2, 2 * (jj + 2), bar(B_W + jj + 2));
                }
            }
        }
        fence_regs<16>(acc);
        if ((threadIdx.x & 127) == 0) { mbar_arrive(bar(B_QDONE)); if (w == 0) TSTAMP(1); }
        uint32_t qa[2][4];
        float qn[2];
        {
            const float c = 0.25f * 1.4426950408889634f;
#pragma unroll
            for (int hh = 0; hh < 2; hh++) {
                float n0 = 0.f, n1 = 0.f;
#pragma unroll
                for (int i = 0; i < 4; i++) {
                    const uint32_t qb = pack_bf16(acc[8 * hh + 2 * i], acc[8 * hh + 2 * i + 1]);
                    const uint32_t qs = pack_bf16(bf_lo(qb) * c, bf_hi(qb) * c);
                    qa[hh][i] = qs;
                    const float e = bf_lo(qs) * bf_lo(qs) + bf_hi(qs) * bf_hi(qs);
                    if (i & 1) n1 += e; else n0 += e;
                }
                n0 += __shfl_xor_sync(0xffffffffu, n0, 1); n0 += __shfl_xor_sync(0xffffffffu, n0, 2);
                n1 += __shfl_xor_sync(0xffffffffu, n1, 1); n1 += __shfl_xor_sync(0xffffffffu, n1, 2);
                qn[hh] = fmaxf(n0, n1);
            }
        }
        uint32_t mlo = 0x03FF03FFu; asm volatile("" : "+r"(mlo));
        const uint64_t kdesc0 = make_desc(sb + OFF_K, 128, 256, 0);
        const uint64_t vdesc0 = make_desc(sb + OFF_VONES - 256, 128, 256, 0);
        constexpr uint64_t VSTEP = ((uint64_t)16 << 32) - 16;
        mbar_wait_w(bar(B_KV + 0), 0);
        if ((threadIdx.x & 127) == 0 && w == 0) TSTAMP(2);
        const float kmax2 = ldsf(sb + OFF_MISC);
        const bool fast0 = __all_sync(0xffffffffu, named_bar_and(1 + w, 128, qn[0] * kmax2 <= 193.0f));
        const bool fast1 = __all_sync(0xffffffffu, named_bar_and(1 + w, 128, qn[1] * kmax2 <= 193.0f));
        uint32_t a[4] = {qa[0][0], qa[0][1], qa[0][2], qa[0][3]};
#pragma unroll 1
        for (int hh = 0; hh < 2; hh++) {
            const bool fast = hh ? fast1 : fast0;
            float S[32], O[12];
#pragma unroll
            for (int i = 0; i < 12; i++) O[i] = 0.f;
#pragma unroll
            for (int i = 0; i < 32; i++) S[i] = 0.f;
            fence_regs<12>(O); fence_regs<32>(S);
            wg_fence();
            wg_qk_n64(S, a, kdesc0);
            wg_commit();
            wg_wait<0>();
            uint64_t kd = kdesc0 + 128, vd = vdesc0;
            if (fast) {
                uint32_t P[16];
#pragma unroll 1
                for (int c = 0; c < 8; c++) {
                    if (c < 7) mbar_wait_w(bar(B_KV + c + 1), 0);
#pragma unroll 1
                    for (int j = 0; j < 4; j++) {
                        fence_regs<32>(S);
                        softmax_fast(S, P, mlo);
                        fence_regs<32>(S);
                        wg_fence();
                        wg_qk_n64(S, a, kd);
#pragma unroll
                        for (int i = 0; i < 4; i++) wg_pv_n24(O, &P[4 * i], vd + i * VSTEP);
                        wg_commit();
                        wg_wait<0>();
                        kd += 128; vd += 4 * VSTEP;
                    }
                    if (hh == 1 && c == 3 && (threadIdx.x & 127) == 0) wo_half(sb, &tm_wo, hg);
                }
            } else {
                uint32_t P[16];
                float m0 = -INFINITY, m1 = -INFINITY;
#pragma unroll 1
                for (int c = 0; c < 8; c++) {
                    if (c < 7) mbar_wait_w(bar(B_KV + c + 1), 0);
#pragma unroll 1
                    for (int j = 0; j < 4; j++) {
                        fence_regs<32>(S); fence_regs<12>(O);
                        float x0 = m0, x1 = m1;
#pragma unroll
                        for (int i = 0; i < 8; i++) {
                            x0 = fmaxf(x0, fmaxf(S[4 * i], S[4 * i + 1]));
                            x1 = fmaxf(x1, fmaxf(S[4 * i + 2], S[4 * i + 3]));
                        }
                        x0 = fmaxf(x0, __shfl_xor_sync(0xffffffffu, x0, 1)); x0 = fmaxf(x0, __shfl_xor_sync(0xffffffffu, x0, 2));
                        x1 = fmaxf(x1, __shfl_xor_sync(0xffffffffu, x1, 1)); x1 = fmaxf(x1, __shfl_xor_sync(0xffffffffu, x1, 2));
                        const float r0 = ex2f(m0 - x0), r1 = ex2f(m1 - x1);
                        m0 = x0; m1 = x1;
#pragma unroll
                        for (int i = 0; i < 3; i++) { O[4 * i] *= r0; O[4 * i + 1] *= r0; O[4 * i + 2] *= r1; O[4 * i + 3] *= r1; }
#pragma unroll
                        for (int i = 0; i < 8; i++) {
                            P[2 * i] = pack_f16(ex2f(S[4 * i] - m0), ex2f(S[4 * i + 1] - m0));
                            P[2 * i + 1] = pack_f16(ex2f(S[4 * i + 2] - m1), ex2f(S[4 * i + 3] - m1));
                        }
                        fence_regs<32>(S); fence_regs<12>(O);
                        wg_fence();
                        wg_qk_n64(S, a, kd);
#pragma unroll
                        for (int i = 0; i < 4; i++) wg_pv_n24(O, &P[4 * i], vd + i * VSTEP);
                        wg_commit();
                        wg_wait<0>();
                        kd += 128; vd += 4 * VSTEP;
                    }
                    if (hh == 1 && c == 3 && (threadIdx.x & 127) == 0) wo_half(sb, &tm_wo, hg);
                }
            }
            fence_regs<12>(O);
            const float vscale = ldsf(sb + OFF_MISC + 4);
            const float i0 = __fdividef(vscale, O[4]), i1 = __fdividef(vscale, O[6]);
            const int row = pb * 64 + wq * 16 + g;
            uint32_t* o0 = (uint32_t*)(g_o + (size_t)row * 512 + (hg * 8 + 2 * w + hh) * 16) + t;
            uint32_t* o1 = o0 + 8 * 256;
            o0[0] = pack_bf16(O[0] * i0, O[1] * i0);
            o0[4] = pack_bf16(O[8] * i0, O[9] * i0);
            o1[0] = pack_bf16(O[2] * i1, O[3] * i1);
            o1[4] = pack_bf16(O[10] * i1, O[11] * i1);
            if ((threadIdx.x & 127) == 0 && w == 0) { TSTAMP(3 + hh); CSTAMP(40 + hh); }
#pragma unroll
            for (int i = 0; i < 4; i++) a[i] = qa[1][i];
        }
        named_bar(1 + w, 128);
        if ((threadIdx.x & 127) == 0) {
            red_release_add(&g_o_count[pb], 1);
            mbar_arrive(bar(B_ATT));
        }
        if (threadIdx.x == 0) {
            TSTAMP(30);
            mbar_wait(bar(B_ATT), 0);
            TSTAMP(31);
            poll_counter(&g_o_count[pb], 16);
            TSTAMP(18);
            fence_async_global();
            for (int jj = 0; jj < 4; jj++) {
                mbar_expect_tx(bar(B_O + jj), 16384);
                tma3d(sb + OFF_V + jj * 16384, &tm_o, 0, pb * 64, 2 * jj, bar(B_O + jj));
            }
            __threadfence();
            if (atomicAdd(&g_done, 1) == 2 * NCTA - 1) {
                for (int i = 0; i < NCTA; i++) g_stats[i] = 0ull;
                for (int i = 0; i < 4; i++) { g_kvt_count[i] = 0; g_z_count[i] = 0; }
                for (int i = 0; i < 32; i++) g_o_count[i] = 0;
                g_done = 0;
                __threadfence();
            }
        }
        __syncwarp();
#pragma unroll
        for (int i = 0; i < 16; i++) acc[i] = 0.f;
        fence_regs<16>(acc);
#pragma unroll 1
        for (int jj = 0; jj < 4; jj++) {
            mbar_wait_w(bar(B_WO + jj), 0);
            mbar_wait_w(bar(B_O + jj), 0);
            if (threadIdx.x == 0 && (jj == 0 || jj == 3)) TSTAMP(jj == 0 ? 32 : 33);
            const uint32_t wb = sb + (jj < 2 ? OFF_X + jj * 32768 : (jj == 2 ? OFF_K : OFF_C)) + bcol;
            wg_fence();
            gemm_chunk(acc, sb + OFF_V + jj * 16384, wb);
            gemm_chunk(acc, sb + OFF_V + jj * 16384 + 8192, wb + 16384);
            wg_commit();
        }
        wg_wait<0>();
        fence_regs<16>(acc);
        {
            const int row = pb * 64 + wq * 16 + g;
            uint32_t* d0 = (uint32_t*)(prm.out + (size_t)row * 1024 + 512 + hg * 128 + w * 32) + t;
            uint32_t* d1 = d0 + 8 * 512;
#pragma unroll
            for (int i = 0; i < 4; i++) {
                d0[4 * i] = pack_bf16(acc[4 * i], acc[4 * i + 1]);
                d1[4 * i] = pack_bf16(acc[4 * i + 2], acc[4 * i + 3]);
            }
        }
        if ((threadIdx.x & 127) == 0 && w == 0) TSTAMP(5);
    } else {
        const int wa = warp_id - 16, tau = threadIdx.x - 512;
        __syncthreads();
        const bool kv_cta = (hg == (pb & 3));
        if (tau == 0) {
            if (kv_cta) {
                mbar_expect_tx(bar(B_WKV), 32768);
                tma3d(sb + OFF_C, &tm_wk, 0, 0, 0, bar(B_WKV));
                tma3d(sb + OFF_C + 16384, &tm_wv, 0, 0, 0, bar(B_WKV));
            }
            for (int jj = 0; jj < 4; jj++) {
                mbar_expect_tx(bar(B_X + jj), 16384);
                tma3d(sb + OFF_X + jj * 16384, &tm_x, 0, pb * 64, 2 * jj, bar(B_X + jj));
                if (!kv_cta && jj < 2) {
                    mbar_expect_tx(bar(B_W + jj), 32768);
                    tma4d(sb + OFF_V + jj * 32768, &tm_wq, 0, 0, hg * 2, 2 * jj, bar(B_W + jj));
                }
            }
            TSTAMP(25);
        }
        __syncwarp();
        if (kv_cta) {
            float acc[16];
#pragma unroll
            for (int i = 0; i < 16; i++) acc[i] = 0.f;
            fence_regs<16>(acc);
            mbar_wait_w(bar(B_WKV), 0);
            if (tau == 0) TSTAMP(20);
#pragma unroll
            for (int jj = 0; jj < 4; jj++) {
                mbar_wait_w(bar(B_X + jj), 0);
                wg_fence();
#pragma unroll
                for (int j = 2 * jj; j < 2 * jj + 2; j++) {
                    const uint64_t da = make_desc(sb + OFF_X + j * 8192, 16, 1024, 1);
                    const uint64_t db = make_desc(sb + OFF_C + j * 2048, 16384, 256, 3);
#pragma unroll
                    for (int ks = 0; ks < 4; ks++) wg_ss_n32_tb(acc, da + ks * 2, db + ks * 32);
                }
                wg_commit();
            }
            wg_wait<0>();
            fence_regs<16>(acc);
            if (tau == 0) TSTAMP(22);
            {
                uint32_t kk[4], vv[4];
#pragma unroll
                for (int i = 0; i < 4; i++) { kk[i] = pack_bf16(acc[2 * i], acc[2 * i + 1]); vv[i] = pack_bf16(acc[8 + 2 * i], acc[8 + 2 * i + 1]); }
                const int s = 4 * pb + wa;
                uint32_t* kp = (uint32_t*)(g_kimg + s * 512 + g * 16 + 4 * t);
                kp[0] = kk[0]; kp[64] = kk[1]; kp[32] = kk[2]; kp[96] = kk[3];
                uint32_t* vlo = (uint32_t*)(g_vimg + (127 - s) * 256 + g * 16 + 4 * t);
                uint32_t* vhi = (uint32_t*)(g_vimg + 32768 + 256 + s * 256 + g * 16 + 4 * t);
                vlo[0] = pack_f16(bf_lo(vv[0]), bf_hi(vv[0])); vlo[32] = pack_f16(bf_lo(vv[1]), bf_hi(vv[1]));
                vhi[0] = pack_f16(bf_lo(vv[2]), bf_hi(vv[2])); vhi[32] = pack_f16(bf_lo(vv[3]), bf_hi(vv[3]));
                uint32_t* vr = (uint32_t*)(g_vraw + (size_t)(16 * s + g) * 16) + t;
                vr[0] = vv[0]; vr[64] = vv[1]; vr[4] = vv[2]; vr[68] = vv[3];
                float n0 = bf_lo(kk[0]) * bf_lo(kk[0]) + bf_hi(kk[0]) * bf_hi(kk[0]) + bf_lo(kk[2]) * bf_lo(kk[2]) + bf_hi(kk[2]) * bf_hi(kk[2]);
                float n1 = bf_lo(kk[1]) * bf_lo(kk[1]) + bf_hi(kk[1]) * bf_hi(kk[1]) + bf_lo(kk[3]) * bf_lo(kk[3]) + bf_hi(kk[3]) * bf_hi(kk[3]);
                n0 += __shfl_xor_sync(0xffffffffu, n0, 1); n0 += __shfl_xor_sync(0xffffffffu, n0, 2);
                n1 += __shfl_xor_sync(0xffffffffu, n1, 1); n1 += __shfl_xor_sync(0xffffffffu, n1, 2);
                float km = fmaxf(n0, n1), vm = 0.f;
#pragma unroll
                for (int i = 0; i < 4; i++) vm = fmaxf(vm, fmaxf(fabsf(bf_lo(vv[i])), fabsf(bf_hi(vv[i]))));
#pragma unroll
                for (int o = 4; o < 32; o <<= 1) km = fmaxf(km, __shfl_xor_sync(0xffffffffu, km, o));
#pragma unroll
                for (int o = 1; o < 32; o <<= 1) vm = fmaxf(vm, __shfl_xor_sync(0xffffffffu, vm, o));
                __syncwarp();
                if (lane == 0) {
                    const unsigned long long rec = ((unsigned long long)(__float_as_uint(vm) | 0x80000000u) << 32) | __float_as_uint(km);
                    asm volatile("st.release.gpu.global.u64 [%0], %1;" ::"l"(&g_stats[s]), "l"(rec) : "memory");
                    if (wa == 0) TSTAMP(8);
                }
            }
            if (tau == 0) {
                for (int jj = 0; jj < 2; jj++) {
                    mbar_expect_tx(bar(B_W + jj), 32768);
                    tma4d(sb + OFF_V + jj * 32768, &tm_wq, 0, 0, hg * 2, 2 * jj, bar(B_W + jj));
                }
            }
            __syncwarp();
        }
        const int c0 = 4 * b;
        if (wa == 1) {
            float km = 0.f, vm = 0.f;
            {
                unsigned long long rec[4];
                uint32_t spins = 0;
                bool ok;
                do {
                    ok = true;
#pragma unroll
                    for (int i = 0; i < 4; i++) {
                        asm volatile("ld.relaxed.gpu.global.u64 %0, [%1];" : "=l"(rec[i]) : "l"(&g_stats[lane + 32 * i]) : "memory");
                        ok = ok && (rec[i] >> 63);
                    }
                    if (++spins > (1u << 22)) __trap();
                } while (!__all_sync(0xffffffffu, ok));
                asm volatile("fence.acq_rel.gpu;" ::: "memory");
#pragma unroll
                for (int i = 0; i < 4; i++) { km = fmaxf(km, __uint_as_float((uint32_t)rec[i])); vm = fmaxf(vm, __uint_as_float((uint32_t)(rec[i] >> 32) & 0x7FFFFFFFu)); }
            }
            if (lane == 0) TSTAMP(16);
#pragma unroll
            for (int o = 1; o < 32; o <<= 1) { km = fmaxf(km, __shfl_xor_sync(0xffffffffu, km, o)); vm = fmaxf(vm, __shfl_xor_sync(0xffffffffu, vm, o)); }
            const bool vdirect = (vm <= 32768.f && vm >= 9.765625e-4f) || vm == 0.f;
            float vs = 1.f;
            if (!vdirect && vm < INFINITY) {
                int e = (int)((__float_as_uint(vm) >> 23) & 0xFF) - 127;
                e = max(-100, min(100, e));
                vs = __uint_as_float((uint32_t)(127 + e - 13) << 23);
            }
            if (lane == 0) {
                asm volatile("st.shared.f32 [%0], %1;" ::"r"(sb + OFF_MISC), "f"(km) : "memory");
                asm volatile("st.shared.f32 [%0], %1;" ::"r"(sb + OFF_MISC + 4), "f"(vs) : "memory");
                fence_async_global();
                mbar_wait(bar(B_QDONE), 0);
                TSTAMP(17);
                for (int c = 0; c < 8; c++) {
                    if (vdirect) mbar_expect_tx(bar(B_KV + c), 16384); else mbar_expect_tx_noarrive(bar(B_KV + c), 8192);
                    bulk_g2s(sb + OFF_K + c * 8192, g_kimg + c * 8192, 8192, bar(B_KV + c));
                    if (vdirect) {
                        bulk_g2s(sb + OFF_V + (112 - 16 * c) * 256, g_vimg + (112 - 16 * c) * 256, 4096, bar(B_KV + c));
                        bulk_g2s(sb + OFF_VONES + 256 + c * 4096, g_vimg + 32768 + 256 + c * 4096, 4096, bar(B_KV + c));
                    }
                    if (c == 0) {
                        for (int i = 0; i < 16; i++) sts128(sb + OFF_VONES + i * 16, 0x3C003C00u, 0x3C003C00u, 0x3C003C00u, 0x3C003C00u);
                        fence_async_smem();
                        if (vdirect) mbar_arrive(bar(B_KV + 0));
                    }
                }
                TSTAMP(28);
            }
            __syncwarp();
            if (!vdirect) {
                const float inv = 1.f / vs;
                for (int idx = lane; idx < S_LEN * 8; idx += 32) {
                    const int key = idx >> 3, dp = idx & 7;
                    const uint32_t v = __ldcg((const uint32_t*)g_vraw + idx);
                    const uint32_t h = pack_f16(bf_lo(v) * inv, bf_hi(v) * inv);
                    const int st = key >> 4, hf = (key >> 3) & 1;
                    const uint32_t base = (dp < 4) ? (OFF_V + (127 - st) * 256) : (OFF_VONES + 256 + st * 256);
                    sts32(sb + base + hf * 128 + (key & 7) * 16 + (dp & 3) * 4, h);
                }
            }
            if (!vdirect) {
                fence_async_smem();
                __syncwarp();
                if (lane == 0) { mbar_arrive(bar(B_KV + 0)); for (int c = 0; c < 8; c++) mbar_arrive(bar(B_KV + c)); }
            }
            __syncwarp();
        } else if (wa >= 2) {
            const int kch0 = hg * 128 + lane * 4;
            uint32_t wA[4], wB[4];
            {
                const uint4 s0 = __ldg((const uint4*)(prm.shift_k + kch0 * 4));
                const uint4 s1 = __ldg((const uint4*)(prm.shift_k + kch0 * 4) + 1);
                wA[0] = __byte_perm(s0.x, s0.z, 0x5410); wA[1] = __byte_perm(s0.x, s0.z, 0x7632);
                wA[2] = __byte_perm(s0.y, s0.w, 0x5410); wA[3] = __byte_perm(s0.y, s0.w, 0x7632);
                wB[0] = __byte_perm(s1.x, s1.z, 0x5410); wB[1] = __byte_perm(s1.x, s1.z, 0x7632);
                wB[2] = __byte_perm(s1.y, s1.w, 0x5410); wB[3] = __byte_perm(s1.y, s1.w, 0x7632);
            }
            mbar_wait_w(bar(B_KVIN), 0);
            const uint32_t kb = sb + OFF_C + (wa - 2) * 32 * 256 + lane * 8, vb = kb + 17408;
            uint32_t k0a, k0b, k1a, k1b, k2a, k2b;
            lds64(kb, k0a, k0b); lds64(kb + 256, k1a, k1b); lds64(kb + 512, k2a, k2b);
#pragma unroll
            for (int o8 = 0; o8 < 4; o8++) {
                uint32_t xa[8], xb[8];
#pragma unroll
                for (int i = 0; i < 8; i++) {
                    uint32_t k3a, k3b, va, vb2;
                    lds64(kb + (o8 * 8 + i + 3) * 256, k3a, k3b);
                    lds64(vb + (o8 * 8 + i) * 256, va, vb2);
                    xa[i] = bmul2(badd2(badd2(badd2(bmul2(k0a, wA[3]), bmul2(k1a, wA[2])), bmul2(k2a, wA[1])), bmul2(k3a, wA[0])), va);
                    xb[i] = bmul2(badd2(badd2(badd2(bmul2(k0b, wB[3]), bmul2(k1b, wB[2])), bmul2(k2b, wB[1])), bmul2(k3b, wB[0])), vb2);
                    k0a = k1a; k0b = k1b; k1a = k2a; k1b = k2b; k2a = k3a; k2b = k3b;
                }
                uint4* dst = (uint4*)(g_kvT + (size_t)kch0 * S_LEN + pb * 64 + (wa - 2) * 32 + o8 * 8);
                dst[0] = make_uint4(__byte_perm(xa[0], xa[1], 0x5410), __byte_perm(xa[2], xa[3], 0x5410), __byte_perm(xa[4], xa[5], 0x5410), __byte_perm(xa[6], xa[7], 0x5410));
                dst[S_LEN / 8] = make_uint4(__byte_perm(xa[0], xa[1], 0x7632), __byte_perm(xa[2], xa[3], 0x7632), __byte_perm(xa[4], xa[5], 0x7632), __byte_perm(xa[6], xa[7], 0x7632));
                dst[2 * (S_LEN / 8)] = make_uint4(__byte_perm(xb[0], xb[1], 0x5410), __byte_perm(xb[2], xb[3], 0x5410), __byte_perm(xb[4], xb[5], 0x5410), __byte_perm(xb[6], xb[7], 0x5410));
                dst[3 * (S_LEN / 8)] = make_uint4(__byte_perm(xb[0], xb[1], 0x7632), __byte_perm(xb[2], xb[3], 0x7632), __byte_perm(xb[4], xb[5], 0x7632), __byte_perm(xb[6], xb[7], 0x7632));
            }
            mbar_arrive(bar(B_KVT));
            mbar_wait_w(bar(B_KVT), 0);
            sts128(sb + C_H + (tau - 64) * 32, 0u, 0u, 0u, 0u);
            sts128(sb + C_H + (tau - 64) * 32 + 16, 0u, 0u, 0u, 0u);
            fence_async_smem();
        } else {
            if (lane == 0) {
                mbar_wait(bar(B_W + KVIN_AFTER), 0);
                kv_tiles_load(sb, &tm_k, &tm_v, pb, hg);
                prefetch_tm(&tm_wo); prefetch_tm(&tm_o); prefetch_tm(&tm_h);
                mbar_wait(bar(B_KVT), 0);
                mbar_expect_tx(bar(B_H), 4096);
                tma2d(sb + C_H + 2048, &tm_h, 0, c0 * 64, bar(B_H));
                red_release_add(&g_kvt_count[hg], 1);
                TSTAMP(34);
                poll_counter(&g_kvt_count[b >> 5], 32);
                fence_async_global();
                mbar_expect_tx(bar(B_CV), 16384);
                bulk_g2s(sb + C_KVC, g_kvT + (size_t)c0 * S_LEN, 16384, bar(B_CV));
                mbar_wait(bar(B_QDONE), 0);
                for (int jj = 0; jj < 2; jj++) {
                    mbar_expect_tx(bar(B_WO + jj), 32768);
                    tma4d(sb + OFF_X + jj * 32768, &tm_wo, 0, 0, hg * 2, 2 * jj, bar(B_WO + jj));
                }
            }
            __syncwarp();
        }
        named_bar(5, 128);
        mbar_wait_w(bar(B_CV), 0);
        if (tau == 0) TSTAMP(9);
        const int NCH = 4;
#pragma unroll 1
        for (int ch = 0; ch < NCH; ch++) {
            if (ch >= 4 - TAIL_CH) mbar_wait_w(bar(B_ATT), 0);
            {
                const uint32_t src = sb + C_KVC + ch * 4096 + tau * 32;
                const uint4 u0 = lds128(src), u1 = lds128(src + 16);
                const uint32_t prev = tau > 0 ? lds32(src - 4) : 0u;
                const uint32_t zd = sb + C_Z + (32 + tau * 16) * 4;
                sts128(zd,      __byte_perm(u0.x, prev, 0x7610), __byte_perm(u0.x, u0.x, 0x1032), __byte_perm(u0.y, u0.x, 0x7610), __byte_perm(u0.y, u0.y, 0x1032));
                sts128(zd + 16, __byte_perm(u0.z, u0.y, 0x7610), __byte_perm(u0.z, u0.z, 0x1032), __byte_perm(u0.w, u0.z, 0x7610), __byte_perm(u0.w, u0.w, 0x1032));
                sts128(zd + 32, __byte_perm(u1.x, u0.w, 0x7610), __byte_perm(u1.x, u1.x, 0x1032), __byte_perm(u1.y, u1.x, 0x7610), __byte_perm(u1.y, u1.y, 0x1032));
                sts128(zd + 48, __byte_perm(u1.z, u1.y, 0x7610), __byte_perm(u1.z, u1.z, 0x1032), __byte_perm(u1.w, u1.z, 0x7610), __byte_perm(u1.w, u1.w, 0x1032));
                if (tau < 32) sts32(sb + C_Z + tau * 4, 0u);
            }
            named_bar(5, 128);
            mbar_wait_w(bar(B_H), ch & 1);
            float D[32];
#pragma unroll
            for (int i = 0; i < 32; i++) D[i] = 0.f;
            fence_regs<32>(D);
            const uint32_t z0 = sb + C_Z + (32 + 32 * (wa >> 1) + 16 * (wa & 1) + 2 * g - 2 * t) * 4;
            const uint64_t hd = make_desc(sb + C_H + 2048, 16, 512, 2);
            conv_phase<64>(D, z0, hd);
            float E[16];
#pragma unroll
            for (int i = 0; i < 16; i++) asm volatile("mov.f32 %0, %1;" : "=f"(E[i]) : "f"(D[16 + i]));
            conv_phase<32>(E, z0 + 4096, hd);
            if (tau == 0 && ch < 3) {
                mbar_expect_tx(bar(B_H), 4096);
                tma2d(sb + C_H + 2048, &tm_h, 0, (c0 + ch + 1) * 64, bar(B_H));
            }
            const int bb0 = 16 * (wa & 1) + 2 * g;
            const int xsw = (g & 3) << 3;
            {
                const uint32_t xb = sb + C_Z + (wa >> 1) * 4096;
#pragma unroll
                for (int jn = 0; jn < 4; jn++) {
#pragma unroll
                    for (int r = 0; r < 2; r++) {
                        const float v0 = (wa < 2) ? E[4 * jn + 2 * r] : D[4 * jn + 2 * r];
                        const float v1 = (wa < 2) ? E[4 * jn + 2 * r + 1] : D[4 * jn + 2 * r + 1];
                        sts64f(xb + ((bb0 + r) * 32 + ((8 * jn + 2 * t) ^ xsw)) * 4, v0, v1);
                    }
                }
            }
            named_bar(5, 128);
            {
                const float dsc = __bfloat162float(prm.ssm_D[c0 + ch]);
                const uint32_t xb = sb + C_Z + ((wa >> 1) ^ 1) * 4096;
#pragma unroll
                for (int jn = 0; jn < 4; jn++) {
#pragma unroll
                    for (int e = 0; e < 2; e++) {
                        const int n = 8 * jn + 2 * t + e;
                        float y0, y1; int m, rn;
                        if (wa < 2) { y0 = D[4 * jn + e]; y1 = D[4 * jn + 2 + e]; m = n; rn = n - 1; }
                        else {
                            const bool last = (jn == 3 && e == 1) && (t == 3);
                            y0 = last ? D[13] : E[4 * jn + e]; y1 = last ? D[15] : E[4 * jn + 2 + e];
                            m = last ? 32 : 33 + n; rn = m - 32;
                        }
                        if (rn >= 0) {
                            y0 += ldsf(xb + (bb0 * 32 + (rn ^ xsw)) * 4);
                            y1 += ldsf(xb + ((bb0 + 1) * 32 + (rn ^ xsw)) * 4);
                        }
                        const uint32_t addr = sb + C_KVC + ch * 4096 + (32 * m + bb0) * 2;
                        const uint32_t kv = lds32(addr);
                        const uint32_t yb = pack_bf16(y0, y1);
                        const uint32_t kd = pack_bf16(bf_lo(kv) * dsc, bf_hi(kv) * dsc);
                        sts32(addr, badd2(yb, kd));
                    }
                }
                fence_async_smem();
            }
            named_bar(5, 128);
            if (tau == 0) {
                bulk_s2g(g_zT + (size_t)(c0 + ch) * S_LEN, sb + C_KVC + ch * 4096, 4096);
                bulk_commit();
                TSTAMP(10 + ch);
            }
        }
        {
            const int cg = tau & 15, pr = tau >> 4;
            const int p0 = pb * 64 + pr * 8, ch0 = hg * 128 + cg * 8;
            uint4 qr[8];
#pragma unroll
            for (int i = 0; i < 8; i++) qr[i] = __ldg((const uint4*)(prm.aq + (size_t)(p0 + i) * 512 + ch0));
            if (tau == 0) {
                bulk_wait_all();
                mbar_expect_tx(bar(B_WO + 3), 32768);
                tma4d(sb + OFF_C, &tm_wo, 0, 0, hg * 2, 6, bar(B_WO + 3));
                fence_async_global();
                red_release_add(&g_z_count[b >> 5], 1);
                poll_counter(&g_z_count[hg], 32);
                __threadfence();
                if (atomicAdd(&g_done, 1) == 2 * NCTA - 1) {
                    for (int i = 0; i < NCTA; i++) g_stats[i] = 0ull;
                    for (int i = 0; i < 4; i++) { g_kvt_count[i] = 0; g_z_count[i] = 0; }
                    for (int i = 0; i < 32; i++) g_o_count[i] = 0;
                    g_done = 0;
                    __threadfence();
                }
            }
            named_bar(5, 128);
            uint4 zz[8];
#pragma unroll
            for (int c = 0; c < 8; c++) zz[c] = __ldcg((const uint4*)(g_zT + (size_t)(ch0 + c) * S_LEN + p0));
#pragma unroll
            for (int i = 0; i < 8; i++) {
                uint32_t r[4];
#pragma unroll
                for (int k = 0; k < 4; k++) {
                    const uint32_t pr2 = __byte_perm((&zz[2 * k].x)[i >> 1], (&zz[2 * k + 1].x)[i >> 1], (i & 1) ? 0x7632 : 0x5410);
                    r[k] = bmul2((&qr[i].x)[k], pr2);
                }
                *(uint4*)(prm.out + (size_t)(p0 + i) * 1024 + ch0) = make_uint4(r[0], r[1], r[2], r[3]);
            }
        }
        if (tau == 0) TSTAMP(14);
    }
}

typedef CUresult (*EncodeFn)(CUtensorMap*, CUtensorMapDataType, cuuint32_t, void*, const cuuint64_t*, const cuuint64_t*,
                             const cuuint32_t*, const cuuint32_t*, CUtensorMapInterleave, CUtensorMapSwizzle,
                             CUtensorMapL2promotion, CUtensorMapFloatOOBfill);

void make_map(EncodeFn fn, CUtensorMap* tm, const void* ptr, int rank, const cuuint64_t* dims, const cuuint64_t* strides, const cuuint32_t* box, CUtensorMapSwizzle swz) {
    cuuint32_t es[4] = {1, 1, 1, 1};
    fn(tm, CU_TENSOR_MAP_DATA_TYPE_BFLOAT16, rank, const_cast<void*>(ptr), dims, strides, box, es, CU_TENSOR_MAP_INTERLEAVE_NONE, swz,
       CU_TENSOR_MAP_L2_PROMOTION_L2_128B, CU_TENSOR_MAP_FLOAT_OOB_FILL_NONE);
}

}

extern "C" void kernel_launch(void* const* d_in, const int* in_sizes, int n_in, void* d_out, int out_size) {
    (void)in_sizes; (void)n_in; (void)out_size;
    static EncodeFn encode = nullptr;
    static void* o_ptr = nullptr;
    if (!encode) {
        cudaDriverEntryPointQueryResult qres;
        void* fn = nullptr;
        cudaGetDriverEntryPoint("cuTensorMapEncodeTiled", &fn, cudaEnableDefault, &qres);
        encode = (EncodeFn)fn;
        cudaGetSymbolAddress(&o_ptr, g_o);
        cudaFuncSetAttribute(fused_kernel, cudaFuncAttributeMaxDynamicSharedMemorySize, SMEM_TOTAL);
    }
    CUtensorMap tm_x, tm_wq, tm_wo, tm_wk, tm_wv, tm_o, tm_h, tm_k, tm_v;
    {
        const cuuint64_t dims[3] = {64, 2048, 8}, str[2] = {1024, 128};
        const cuuint32_t b64[3] = {64, 64, 2};
        make_map(encode, &tm_x, d_in[6], 3, dims, str, b64, CU_TENSOR_MAP_SWIZZLE_128B);
        make_map(encode, &tm_o, o_ptr, 3, dims, str, b64, CU_TENSOR_MAP_SWIZZLE_128B);
    }
    {
        const cuuint64_t dims[4] = {64, 64, 8, 8}, str[3] = {1024, 128, 65536};
        const cuuint32_t box[4] = {64, 64, 2, 2};
        make_map(encode, &tm_wq, d_in[7], 4, dims, str, box, CU_TENSOR_MAP_SWIZZLE_128B);
        make_map(encode, &tm_wo, d_in[10], 4, dims, str, box, CU_TENSOR_MAP_SWIZZLE_128B);
    }
    {
        const cuuint64_t dims[3] = {16, 256, 2}, str[2] = {32, 8192};
        const cuuint32_t box[3] = {16, 256, 2};
        make_map(encode, &tm_wk, d_in[8], 3, dims, str, box, CU_TENSOR_MAP_SWIZZLE_32B);
        make_map(encode, &tm_wv, d_in[9], 3, dims, str, box, CU_TENSOR_MAP_SWIZZLE_32B);
    }
    {
        const cuuint64_t dims[2] = {32, 512 * 64}, str[1] = {64};
        const cuuint32_t box[2] = {32, 64};
        make_map(encode, &tm_h, d_in[4], 2, dims, str, box, CU_TENSOR_MAP_SWIZZLE_64B);
    }
    {
        const cuuint64_t dims[2] = {512, 2048}, str[1] = {1024};
        const cuuint32_t bk[2] = {128, 67}, bv[2] = {128, 64};
        make_map(encode, &tm_k, d_in[1], 2, dims, str, bk, CU_TENSOR_MAP_SWIZZLE_NONE);
        make_map(encode, &tm_v, d_in[2], 2, dims, str, bv, CU_TENSOR_MAP_SWIZZLE_NONE);
    }
    Params prm;
    prm.aq = (const __nv_bfloat16*)d_in[0];
    prm.ak = (const __nv_bfloat16*)d_in[1];
    prm.av = (const __nv_bfloat16*)d_in[2];
    prm.shift_k = (const __nv_bfloat16*)d_in[3];
    prm.ssm_D = (const __nv_bfloat16*)d_in[5];
    prm.out = (__nv_bfloat16*)d_out;
    fused_kernel<<<NCTA, NTHREADS, SMEM_TOTAL>>>(tm_x, tm_wq, tm_wo, tm_wk, tm_wv, tm_o, tm_h, tm_k, tm_v, prm);
}
```

```cpp
#include <cuda_runtime.h>
#include <cuda_bf16.h>
#include <cuda_fp16.h>
#include <cuda.h>
#include <stdint.h>

namespace {

constexpr int S_LEN = 2048;
constexpr int NCTA = 128;
constexpr int NTHREADS = 640;

constexpr uint32_t OFF_K = 0;
constexpr uint32_t OFF_V = 65536;
constexpr uint32_t OFF_VONES = OFF_V + 32768;
constexpr uint32_t OFF_X = 132096;
constexpr uint32_t OFF_C = 197632;
constexpr uint32_t C_KVC = OFF_C;
constexpr uint32_t C_H = OFF_C + 16384;
constexpr uint32_t C_Z = C_H + 6144;
constexpr uint32_t OFF_BAR = 231936;
constexpr uint32_t SMEM_TOTAL = 232448;

enum { B_WKV = 0, B_X = 1, B_QDONE = 7, B_KV = 8, B_WO = 16, B_O = 20, B_ATT = 24, B_H = 25, B_CV = 26, B_W = 27, B_KVT = 31, B_KVIN = 32, B_KHALF = 33, B_COUNT = 34 };
constexpr uint32_t OFF_MISC = OFF_BAR + 8 * B_COUNT;

__device__ __align__(1024) uint8_t g_kimg[65536];
__device__ __align__(1024) uint8_t g_vimg[65792];
__device__ __align__(1024) __nv_bfloat16 g_vraw[S_LEN * 16];
__device__ __align__(1024) __nv_bfloat16 g_o[S_LEN * 512];
__device__ __align__(1024) __nv_bfloat16 g_kvT[512 * S_LEN];
__device__ __align__(1024) __nv_bfloat16 g_zT[512 * S_LEN];
__device__ unsigned long long g_stats[NCTA];
__device__ unsigned int g_kvt_count[4];
__device__ unsigned int g_z_count[4];
__device__ unsigned int g_o_count[32];
__device__ unsigned int g_done;
#define TSTAMP(i) do {} while (0)
#define CSTAMP(i) do {} while (0)

__device__ __forceinline__ void wg_fence() { asm volatile("wgmma.fence.sync.aligned;" ::: "memory"); }
__device__ __forceinline__ void wg_commit() { asm volatile("wgmma.commit_group.sync.aligned;" ::: "memory"); }
template <int N> __device__ __forceinline__ void wg_wait() { asm volatile("wgmma.wait_group.sync.aligned %0;" ::"n"(N) : "memory"); }
template <int N> __device__ __forceinline__ void fence_regs(float* r) {
#pragma unroll
    for (int i = 0; i < N; i++) asm volatile("" : "+f"(r[i])::"memory");
}
template <int N> __device__ __forceinline__ void fence_uregs(uint32_t* r) {
#pragma unroll
    for (int i = 0; i < N; i++) asm volatile("" : "+r"(r[i])::"memory");
}
__device__ __forceinline__ uint64_t make_desc(uint32_t saddr, uint32_t lbo, uint32_t sbo, uint32_t swz) {
    return (uint64_t)((saddr & 0x3FFFF) >> 4) | ((uint64_t)(lbo >> 4) << 16) | ((uint64_t)(sbo >> 4) << 32) | ((uint64_t)swz << 62);
}
__device__ __forceinline__ void mbar_init(uint32_t bar, uint32_t count) {
    asm volatile("mbarrier.init.shared::cta.b64 [%0], %1;" ::"r"(bar), "r"(count) : "memory");
}
__device__ __forceinline__ void mbar_expect_tx(uint32_t bar, uint32_t bytes) {
    asm volatile("mbarrier.arrive.expect_tx.shared::cta.b64 _, [%0], %1;" ::"r"(bar), "r"(bytes) : "memory");
}
__device__ __forceinline__ void mbar_expect_tx_noarrive(uint32_t bar, uint32_t bytes) {
    asm volatile("mbarrier.expect_tx.relaxed.cta.shared::cta.b64 [%0], %1;" ::"r"(bar), "r"(bytes) : "memory");
}
__device__ __forceinline__ void mbar_arrive(uint32_t bar) {
    asm volatile("mbarrier.arrive.shared::cta.b64 _, [%0];" ::"r"(bar) : "memory");
}
__device__ __forceinline__ void mbar_arrive_if(uint32_t bar, bool pred) {
    asm volatile("{\n.reg .pred p;\nsetp.ne.u32 p, %1, 0;\n@p mbarrier.arrive.shared::cta.b64 _, [%0];\n}\n" ::"r"(bar), "r"((uint32_t)pred) : "memory");
}
__device__ __forceinline__ bool mbar_try(uint32_t bar, uint32_t parity) {
    uint32_t ok;
    asm volatile("{\n.reg .pred p;\nmbarrier.try_wait.parity.shared::cta.b64 p, [%1], %2;\nselp.u32 %0, 1, 0, p;\n}\n"
                 : "=r"(ok) : "r"(bar), "r"(parity) : "memory");
    return ok != 0;
}
__device__ __forceinline__ void mbar_wait(uint32_t bar, uint32_t parity) {
    uint32_t spins = 0;
    while (!mbar_try(bar, parity)) {
        if (++spins > (1u << 22)) __trap();
    }
}
__device__ __forceinline__ void mbar_wait_w(uint32_t bar, uint32_t parity) {
    uint32_t spins = 0;
    while (!__all_sync(0xffffffffu, mbar_try(bar, parity))) {
        if (++spins > (1u << 22)) __trap();
    }
}
__device__ __forceinline__ void tma2d(uint32_t dst, const CUtensorMap* tm, int c0, int c1, uint32_t bar) {
    asm volatile("cp.async.bulk.tensor.2d.shared::cluster.global.mbarrier::complete_tx::bytes [%0], [%1, {%3, %4}], [%2];"
                 ::"r"(dst), "l"((uint64_t)tm), "r"(bar), "r"(c0), "r"(c1) : "memory");
}
__device__ __forceinline__ void tma3d(uint32_t dst, const CUtensorMap* tm, int c0, int c1, int c2, uint32_t bar) {
    asm volatile("cp.async.bulk.tensor.3d.shared::cluster.global.mbarrier::complete_tx::bytes [%0], [%1, {%3, %4, %5}], [%2];"
                 ::"r"(dst), "l"((uint64_t)tm), "r"(bar), "r"(c0), "r"(c1), "r"(c2) : "memory");
}
__device__ __forceinline__ void tma4d(uint32_t dst, const CUtensorMap* tm, int c0, int c1, int c2, int c3, uint32_t bar) {
    asm volatile("cp.async.bulk.tensor.4d.shared::cluster.global.mbarrier::complete_tx::bytes [%0], [%1, {%3, %4, %5, %6}], [%2];"
                 ::"r"(dst), "l"((uint64_t)tm), "r"(bar), "r"(c0), "r"(c1), "r"(c2), "r"(c3) : "memory");
}
__device__ __forceinline__ void prefetch_tm(const CUtensorMap* tm) { asm volatile("prefetch.tensormap [%0];" ::"l"((uint64_t)tm) : "memory"); }
__device__ __forceinline__ void bulk_s2g(void* dst, uint32_t src, uint32_t bytes) {
    asm volatile("cp.async.bulk.global.shared::cta.bulk_group [%0], [%1], %2;" ::"l"(dst), "r"(src), "r"(bytes) : "memory");
}
__device__ __forceinline__ void bulk_commit() { asm volatile("cp.async.bulk.commit_group;" ::: "memory"); }
__device__ __forceinline__ void bulk_wait_all() { asm volatile("cp.async.bulk.wait_group 0;" ::: "memory"); }
__device__ __forceinline__ void fence_async_global() { asm volatile("fence.proxy.async.global;" ::: "memory"); }
__device__ __forceinline__ void bulk_g2s(uint32_t dst, const void* src, uint32_t bytes, uint32_t bar) {
    asm volatile("cp.async.bulk.shared::cluster.global.mbarrier::complete_tx::bytes [%0], [%1], %2, [%3];"
                 ::"r"(dst), "l"(src), "r"(bytes), "r"(bar) : "memory");
}
__device__ __forceinline__ void fence_async_smem() { asm volatile("fence.proxy.async.shared::cta;" ::: "memory"); }
__device__ __forceinline__ void named_bar(int id, int n) { asm volatile("bar.sync %0, %1;" ::"r"(id), "r"(n) : "memory"); }
__device__ __forceinline__ bool named_bar_and(int id, int n, bool pred) {
    uint32_t r;
    asm volatile("{\n.reg .pred p, q;\nsetp.ne.u32 p, %3, 0;\nbarrier.cta.red.and.pred q, %1, %2, p;\nselp.u32 %0, 1, 0, q;\n}\n"
                 : "=r"(r) : "r"(id), "r"(n), "r"((uint32_t)pred) : "memory");
    return r != 0;
}
__device__ __forceinline__ unsigned int ld_acquire(const unsigned int* p) {
    unsigned int v;
    asm volatile("ld.acquire.gpu.global.u32 %0, [%1];" : "=r"(v) : "l"(p) : "memory");
    return v;
}
__device__ __forceinline__ void red_release_add(unsigned int* p, unsigned int v) {
    asm volatile("red.release.gpu.global.add.u32 [%0], %1;" ::"l"(p), "r"(v) : "memory");
}
__device__ __forceinline__ void poll_counter(const unsigned int* p, unsigned int target) {
    uint32_t spins = 0;
    while (ld_acquire(p) < target) {
        if (++spins > (1u << 22)) __trap();
    }
}
__device__ __forceinline__ float ex2f(float x) { float y; asm("ex2.approx.ftz.f32 %0, %1;" : "=f"(y) : "f"(x)); return y; }
__device__ __forceinline__ uint32_t pack_f16(float lo, float hi) { uint32_t r; asm("cvt.rn.f16x2.f32 %0, %1, %2;" : "=r"(r) : "f"(hi), "f"(lo)); return r; }
__device__ __forceinline__ uint32_t pack_bf16(float lo, float hi) { uint32_t r; asm("cvt.rn.bf16x2.f32 %0, %1, %2;" : "=r"(r) : "f"(hi), "f"(lo)); return r; }
__device__ __forceinline__ float bf_lo(uint32_t v) { return __uint_as_float(v << 16); }
__device__ __forceinline__ float bf_hi(uint32_t v) { return __uint_as_float(v & 0xFFFF0000u); }
__device__ __forceinline__ uint32_t hfma2(uint32_t a, uint32_t b, uint32_t c) { uint32_t r; asm("fma.rn.f16x2 %0, %1, %2, %3;" : "=r"(r) : "r"(a), "r"(b), "r"(c)); return r; }
__device__ __forceinline__ uint32_t bmul2(uint32_t a, uint32_t b) { uint32_t r; asm("mul.rn.bf16x2 %0, %1, %2;" : "=r"(r) : "r"(a), "r"(b)); return r; }
__device__ __forceinline__ uint32_t badd2(uint32_t a, uint32_t b) { uint32_t r; asm("add.rn.bf16x2 %0, %1, %2;" : "=r"(r) : "r"(a), "r"(b)); return r; }
template <int LUT> __device__ __forceinline__ uint32_t lop3(uint32_t a, uint32_t b, uint32_t c) {
    uint32_t r; asm("lop3.b32 %0, %1, %2, %3, %4;" : "=r"(r) : "r"(a), "r"(b), "r"(c), "n"(LUT)); return r;
}
__device__ __forceinline__ uint32_t lds32(uint32_t a) { uint32_t v; asm volatile("ld.shared.u32 %0, [%1];" : "=r"(v) : "r"(a)); return v; }
__device__ __forceinline__ float ldsf(uint32_t a) { float v; asm volatile("ld.shared.f32 %0, [%1];" : "=f"(v) : "r"(a)); return v; }
__device__ __forceinline__ uint4 lds128(uint32_t a) { uint4 v; asm volatile("ld.shared.v4.u32 {%0,%1,%2,%3}, [%4];" : "=r"(v.x), "=r"(v.y), "=r"(v.z), "=r"(v.w) : "r"(a)); return v; }
__device__ __forceinline__ void lds64(uint32_t a, uint32_t& x, uint32_t& y) { asm volatile("ld.shared.v2.u32 {%0,%1}, [%2];" : "=r"(x), "=r"(y) : "r"(a)); }
__device__ __forceinline__ void sts32(uint32_t a, uint32_t v) { asm volatile("st.shared.u32 [%0], %1;" ::"r"(a), "r"(v) : "memory"); }
__device__ __forceinline__ void sts64f(uint32_t a, float x, float y) { asm volatile("st.shared.v2.f32 [%0], {%1,%2};" ::"r"(a), "f"(x), "f"(y) : "memory"); }
__device__ __forceinline__ void sts128(uint32_t a, uint32_t x, uint32_t y, uint32_t z, uint32_t w) {
    asm volatile("st.shared.v4.u32 [%0], {%1,%2,%3,%4};" ::"r"(a), "r"(x), "r"(y), "r"(z), "r"(w) : "memory");
}

__device__ __forceinline__ void wg_ss_n32_tb(float* d, uint64_t descA, uint64_t descB) {
    asm volatile("wgmma.mma_async.sync.aligned.m64n32k16.f32.bf16.bf16 {%0,%1,%2,%3,%4,%5,%6,%7,%8,%9,%10,%11,%12,%13,%14,%15}, %16, %17, 1, 1, 1, 0, 1;\n"
        : "+f"(d[0]), "+f"(d[1]), "+f"(d[2]), "+f"(d[3]), "+f"(d[4]), "+f"(d[5]), "+f"(d[6]), "+f"(d[7]), "+f"(d[8]), "+f"(d[9]), "+f"(d[10]), "+f"(d[11]), "+f"(d[12]), "+f"(d[13]), "+f"(d[14]), "+f"(d[15])
        : "l"(descA), "l"(descB));
}
__device__ __forceinline__ void wg_ss_n64_tb(float* d, uint64_t descA, uint64_t descB) {
    asm volatile("wgmma.mma_async.sync.aligned.m64n64k16.f32.bf16.bf16 {%0,%1,%2,%3,%4,%5,%6,%7,%8,%9,%10,%11,%12,%13,%14,%15,%16,%17,%18,%19,%20,%21,%22,%23,%24,%25,%26,%27,%28,%29,%30,%31}, %32, %33, 1, 1, 1, 0, 1;\n"
        : "+f"(d[0]), "+f"(d[1]), "+f"(d[2]), "+f"(d[3]), "+f"(d[4]), "+f"(d[5]), "+f"(d[6]), "+f"(d[7]), "+f"(d[8]), "+f"(d[9]), "+f"(d[10]), "+f"(d[11]), "+f"(d[12]), "+f"(d[13]), "+f"(d[14]), "+f"(d[15]), "+f"(d[16]), "+f"(d[17]), "+f"(d[18]), "+f"(d[19]), "+f"(d[20]), "+f"(d[21]), "+f"(d[22]), "+f"(d[23]), "+f"(d[24]), "+f"(d[25]), "+f"(d[26]), "+f"(d[27]), "+f"(d[28]), "+f"(d[29]), "+f"(d[30]), "+f"(d[31])
        : "l"(descA), "l"(descB));
}
__device__ __forceinline__ void wg_qk_n64(float* d, const uint32_t* a, uint64_t desc) {
    asm volatile("wgmma.mma_async.sync.aligned.m64n64k16.f32.bf16.bf16 {%0,%1,%2,%3,%4,%5,%6,%7,%8,%9,%10,%11,%12,%13,%14,%15,%16,%17,%18,%19,%20,%21,%22,%23,%24,%25,%26,%27,%28,%29,%30,%31}, {%32,%33,%34,%35}, %36, 0, 1, 1, 0;\n"
        : "+f"(d[0]), "+f"(d[1]), "+f"(d[2]), "+f"(d[3]), "+f"(d[4]), "+f"(d[5]), "+f"(d[6]), "+f"(d[7]), "+f"(d[8]), "+f"(d[9]), "+f"(d[10]), "+f"(d[11]), "+f"(d[12]), "+f"(d[13]), "+f"(d[14]), "+f"(d[15]), "+f"(d[16]), "+f"(d[17]), "+f"(d[18]), "+f"(d[19]), "+f"(d[20]), "+f"(d[21]), "+f"(d[22]), "+f"(d[23]), "+f"(d[24]), "+f"(d[25]), "+f"(d[26]), "+f"(d[27]), "+f"(d[28]), "+f"(d[29]), "+f"(d[30]), "+f"(d[31])
        : "r"(a[0]), "r"(a[1]), "r"(a[2]), "r"(a[3]), "l"(desc));
}
__device__ __forceinline__ void wg_pv_n24(float* d, const uint32_t* a, uint64_t desc) {
    asm volatile("wgmma.mma_async.sync.aligned.m64n24k16.f32.f16.f16 {%0,%1,%2,%3,%4,%5,%6,%7,%8,%9,%10,%11}, {%12,%13,%14,%15}, %16, 1, 1, 1, 1;\n"
        : "+f"(d[0]), "+f"(d[1]), "+f"(d[2]), "+f"(d[3]), "+f"(d[4]), "+f"(d[5]), "+f"(d[6]), "+f"(d[7]), "+f"(d[8]), "+f"(d[9]), "+f"(d[10]), "+f"(d[11])
        : "r"(a[0]), "r"(a[1]), "r"(a[2]), "r"(a[3]), "l"(desc));
}
__device__ __forceinline__ void wg_cv_n16(float* d, const uint32_t* a, uint64_t desc) {
    asm volatile("wgmma.mma_async.sync.aligned.m64n16k16.f32.bf16.bf16 {%0,%1,%2,%3,%4,%5,%6,%7}, {%8,%9,%10,%11}, %12, 1, 1, 1, 0;\n"
        : "+f"(d[0]), "+f"(d[1]), "+f"(d[2]), "+f"(d[3]), "+f"(d[4]), "+f"(d[5]), "+f"(d[6]), "+f"(d[7])
        : "r"(a[0]), "r"(a[1]), "r"(a[2]), "r"(a[3]), "l"(desc));
}
__device__ __forceinline__ void wg_cv_n32(float* d, const uint32_t* a, uint64_t desc) {
    asm volatile("wgmma.mma_async.sync.aligned.m64n32k16.f32.bf16.bf16 {%0,%1,%2,%3,%4,%5,%6,%7,%8,%9,%10,%11,%12,%13,%14,%15}, {%16,%17,%18,%19}, %20, 1, 1, 1, 0;\n"
        : "+f"(d[0]), "+f"(d[1]), "+f"(d[2]), "+f"(d[3]), "+f"(d[4]), "+f"(d[5]), "+f"(d[6]), "+f"(d[7]), "+f"(d[8]), "+f"(d[9]), "+f"(d[10]), "+f"(d[11]), "+f"(d[12]), "+f"(d[13]), "+f"(d[14]), "+f"(d[15])
        : "r"(a[0]), "r"(a[1]), "r"(a[2]), "r"(a[3]), "l"(desc));
}
__device__ __forceinline__ void wg_cv_n48(float* d, const uint32_t* a, uint64_t desc) {
    asm volatile("wgmma.mma_async.sync.aligned.m64n48k16.f32.bf16.bf16 {%0,%1,%2,%3,%4,%5,%6,%7,%8,%9,%10,%11,%12,%13,%14,%15,%16,%17,%18,%19,%20,%21,%22,%23}, {%24,%25,%26,%27}, %28, 1, 1, 1, 0;\n"
        : "+f"(d[0]), "+f"(d[1]), "+f"(d[2]), "+f"(d[3]), "+f"(d[4]), "+f"(d[5]), "+f"(d[6]), "+f"(d[7]), "+f"(d[8]), "+f"(d[9]), "+f"(d[10]), "+f"(d[11]), "+f"(d[12]), "+f"(d[13]), "+f"(d[14]), "+f"(d[15]), "+f"(d[16]), "+f"(d[17]), "+f"(d[18]), "+f"(d[19]), "+f"(d[20]), "+f"(d[21]), "+f"(d[22]), "+f"(d[23])
        : "r"(a[0]), "r"(a[1]), "r"(a[2]), "r"(a[3]), "l"(desc));
}
__device__ __forceinline__ void wg_cv_n64(float* d, const uint32_t* a, uint64_t desc) {
    asm volatile("wgmma.mma_async.sync.aligned.m64n64k16.f32.bf16.bf16 {%0,%1,%2,%3,%4,%5,%6,%7,%8,%9,%10,%11,%12,%13,%14,%15,%16,%17,%18,%19,%20,%21,%22,%23,%24,%25,%26,%27,%28,%29,%30,%31}, {%32,%33,%34,%35}, %36, 1, 1, 1, 0;\n"
        : "+f"(d[0]), "+f"(d[1]), "+f"(d[2]), "+f"(d[3]), "+f"(d[4]), "+f"(d[5]), "+f"(d[6]), "+f"(d[7]), "+f"(d[8]), "+f"(d[9]), "+f"(d[10]), "+f"(d[11]), "+f"(d[12]), "+f"(d[13]), "+f"(d[14]), "+f"(d[15]), "+f"(d[16]), "+f"(d[17]), "+f"(d[18]), "+f"(d[19]), "+f"(d[20]), "+f"(d[21]), "+f"(d[22]), "+f"(d[23]), "+f"(d[24]), "+f"(d[25]), "+f"(d[26]), "+f"(d[27]), "+f"(d[28]), "+f"(d[29]), "+f"(d[30]), "+f"(d[31])
        : "r"(a[0]), "r"(a[1]), "r"(a[2]), "r"(a[3]), "l"(desc));
}

template <int N> __device__ __forceinline__ void wg_cv(float* d, const uint32_t* a, uint64_t desc);
template <> __device__ __forceinline__ void wg_cv<16>(float* d, const uint32_t* a, uint64_t s) { wg_cv_n16(d, a, s); }
template <> __device__ __forceinline__ void wg_cv<48>(float* d, const uint32_t* a, uint64_t s) { wg_cv_n48(d, a, s); }
template <> __device__ __forceinline__ void wg_cv<32>(float* d, const uint32_t* a, uint64_t s) { wg_cv_n32(d, a, s); }
template <> __device__ __forceinline__ void wg_cv<64>(float* d, const uint32_t* a, uint64_t s) { wg_cv_n64(d, a, s); }

constexpr uint32_t POLYMASK = 0x5555u;
__device__ __forceinline__ void softmax_fast(const float* s, uint32_t* p, uint32_t mlo) {
    const uint32_t C3 = 0x2cfb2cfbu, C2 = 0x9fec9fecu, C1 = 0x37a837a8u, C0 = 0x37383738u;
#pragma unroll
    for (int i = 0; i < 16; i++) {
        const float s0 = s[2 * i], s1 = s[2 * i + 1];
        if ((POLYMASK >> i) & 1) {
            const float t0 = s0 + 12303.0f, t1 = s1 + 12303.0f;
            const uint32_t T = __byte_perm(__float_as_uint(t0), __float_as_uint(t1), 0x5410);
            const uint32_t U = lop3<0xEA>(T, mlo, 0x3C003C00u);
            uint32_t h = hfma2(U, C3, C2);
            h = hfma2(h, U, C1);
            h = hfma2(h, U, C0);
            p[i] = lop3<0xE4>(h, T, 0x03FF03FFu);
        } else {
            p[i] = pack_f16(ex2f(s0), ex2f(s1));
        }
    }
}

__device__ __forceinline__ void gemm_chunk(float* acc, uint32_t a_addr, uint32_t b_addr) {
    const uint64_t da = make_desc(a_addr, 16, 1024, 1);
    const uint64_t db = make_desc(b_addr, 8192, 1024, 1);
#pragma unroll
    for (int ks = 0; ks < 4; ks++) wg_ss_n32_tb(acc, da + ks * 2, db + ks * 128);
}

__device__ __forceinline__ uint32_t smem_inc(uint32_t addr) {
    uint32_t old;
    asm volatile("atom.acq_rel.cta.shared.add.u32 %0, [%1], 1;" : "=r"(old) : "r"(addr) : "memory");
    return old;
}
__device__ __forceinline__ void kv_tiles_load(uint32_t sb, const CUtensorMap* tm_k, const CUtensorMap* tm_v, int pb, int hg) {
    const uint32_t br = sb + OFF_BAR + 8 * B_KVIN;
    mbar_expect_tx(br, 67 * 256 + 64 * 256);
    tma2d(sb + OFF_C, tm_k, hg * 128, pb * 64 - 3, br);
    tma2d(sb + OFF_C + 17408, tm_v, hg * 128, pb * 64, br);
}

struct Params {
    const __nv_bfloat16 *aq, *shift_k, *ssm_D, *wk, *wv;
    __nv_bfloat16* out;
};

template <int NQ>
__device__ __forceinline__ void conv_phase(float* Dn, uint32_t zaddr, uint64_t hdesc) {
    uint32_t a[2][16];
#pragma unroll 1
    for (int it = 0; it < 2; it++) {
#pragma unroll
        for (int st = 0; st < 2; st++) {
            uint32_t* aa = a[st];
#pragma unroll
            for (int u = 0; u < 2; u++) {
                const uint32_t z = zaddr + (st * 2 + u) * 256;
                lds64(z, aa[8 * u + 0], aa[8 * u + 1]);      lds64(z - 32, aa[8 * u + 2], aa[8 * u + 3]);
                lds64(z - 64, aa[8 * u + 4], aa[8 * u + 5]); lds64(z - 96, aa[8 * u + 6], aa[8 * u + 7]);
            }
            wg_fence();
#pragma unroll
            for (int u = 0; u < 2; u++) {
                const int qi = st * 2 + u;
                wg_cv<NQ>(Dn, &aa[8 * u], hdesc - qi * 8);
                wg_cv<NQ>(Dn, &aa[8 * u + 4], hdesc - qi * 8 + 2);
            }
            wg_commit();
        }
        wg_wait<0>();
        zaddr += 1024; hdesc -= 32;
    }
    fence_regs<NQ / 2>(Dn);
}

__global__ void __launch_bounds__(NTHREADS, 1)
fused_kernel(const __grid_constant__ CUtensorMap tm_x,
             const __grid_constant__ CUtensorMap tm_wq, const __grid_constant__ CUtensorMap tm_wo,
             const __grid_constant__ CUtensorMap tm_o, const __grid_constant__ CUtensorMap tm_h,
             const __grid_constant__ CUtensorMap tm_k, const __grid_constant__ CUtensorMap tm_v, const Params prm) {
    extern __shared__ __align__(1024) uint8_t smem_raw[];
    const uint32_t sb = (uint32_t)__cvta_generic_to_shared(smem_raw);
    const int warp_id = __shfl_sync(0xffffffffu, threadIdx.x >> 5, 0);
    const int lane = threadIdx.x & 31;
    const int g = lane >> 2, t = lane & 3;
    const int b = blockIdx.x, pb = b >> 2, hg = b & 3;
    auto bar = [&](int i) { return sb + OFF_BAR + 8 * i; };
    const bool kv_cta = (hg == (pb & 3));

    if (threadIdx.x == 512) {
        TSTAMP(0);
        for (int j = 0; j < 4; j++) { mbar_init(bar(B_X + j), 1); mbar_init(bar(B_W + j), 1); }
        asm volatile("fence.mbarrier_init.release.cluster;" ::: "memory");
        for (int jj = 0; jj < 4; jj++) {
            mbar_expect_tx(bar(B_X + jj), 16384);
            tma3d(sb + OFF_X + jj * 16384, &tm_x, 0, pb * 64, 2 * jj, bar(B_X + jj));
            if (jj < (kv_cta ? 1 : 2)) {
                mbar_expect_tx(bar(B_W + jj), 32768);
                tma4d(sb + OFF_V + jj * 32768, &tm_wq, 0, 0, hg * 2, 2 * jj, bar(B_W + jj));
            }
        }
        TSTAMP(25);
        mbar_init(bar(B_WKV), 512);
        for (int j = 0; j < 4; j++) { mbar_init(bar(B_WO + j), 1); mbar_init(bar(B_O + j), 1); }
        sts32(sb + OFF_MISC + 12, 0u); sts32(sb + OFF_MISC + 16, 0u);
        if (sb & 1023u) __trap();
        for (int j = 0; j < 8; j++) mbar_init(bar(B_KV + j), j == 0 ? 2 : 1);
        mbar_init(bar(B_QDONE), 4); mbar_init(bar(B_ATT), 4);
        mbar_init(bar(B_H), 1); mbar_init(bar(B_CV), 1); mbar_init(bar(B_KVT), 64); mbar_init(bar(B_KVIN), 1); mbar_init(bar(B_KHALF), 4);
        asm volatile("fence.mbarrier_init.release.cluster;" ::: "memory");
    }

    if (warp_id < 16) {
        const int w = warp_id >> 2, wq = warp_id & 3;
        uint4 wkv[4];
        if (kv_cta) {
#pragma unroll
            for (int i = 0; i < 4; i++) {
                const int idx = threadIdx.x + 512 * i;
                wkv[i] = __ldg((const uint4*)((idx >> 10) ? prm.wv : prm.wk) + (idx & 1023));
            }
        }
        __syncthreads();
        if (kv_cta) {
#pragma unroll
            for (int i = 0; i < 4; i++) {
                const int idx = threadIdx.x + 512 * i, r = (idx & 1023) >> 1, hf = idx & 1;
                sts128(sb + OFF_C + (idx >> 10) * 16384 + r * 32 + ((hf ^ ((r >> 2) & 1)) << 4), wkv[i].x, wkv[i].y, wkv[i].z, wkv[i].w);
            }
            fence_async_smem();
            mbar_arrive(bar(B_WKV));
        }
        float acc[16];
#pragma unroll
        for (int i = 0; i < 16; i++) acc[i] = 0.f;
        fence_regs<16>(acc);
        const uint32_t bcol = (w >> 1) * 8192 + (w & 1) * 64;
#pragma unroll 1
        for (int jj = 0; jj < 4; jj++) {
            mbar_wait_w(bar(B_X + jj), 0);
            mbar_wait_w(bar(B_W + jj), 0);
            if (threadIdx.x == 0) TSTAMP(jj == 0 ? 23 : jj == 1 ? 24 : jj == 2 ? 26 : 27);
            wg_fence();
            const uint32_t wst = sb + OFF_V + (jj & 1) * 32768 + bcol;
            gemm_chunk(acc, sb + OFF_X + jj * 16384, wst);
            gemm_chunk(acc, sb + OFF_X + jj * 16384 + 8192, wst + 16384);
            wg_commit();
            wg_wait<0>();
            if (jj < 2 && (threadIdx.x & 127) == 0) {
                if (smem_inc(sb + OFF_MISC + 12 + 4 * jj) == 3) {
                    mbar_expect_tx(bar(B_W + jj + 2), 32768);
                    tma4d(sb + OFF_V + jj * 32768, &tm_wq, 0, 0, hg * 2, 2 * (jj + 2), bar(B_W + jj + 2));
                }
            }
        }
        fence_regs<16>(acc);
        if ((threadIdx.x & 127) == 0) { mbar_arrive(bar(B_QDONE)); if (w == 0) TSTAMP(1); }
        uint32_t qa[2][4];
        float qn[2];
        {
            const float c = 0.25f * 1.4426950408889634f;
#pragma unroll
            for (int hh = 0; hh < 2; hh++) {
                float n0 = 0.f, n1 = 0.f;
#pragma unroll
                for (int i = 0; i < 4; i++) {
                    const uint32_t qb = pack_bf16(acc[8 * hh + 2 * i], acc[8 * hh + 2 * i + 1]);
                    const uint32_t qs = pack_bf16(bf_lo(qb) * c, bf_hi(qb) * c);
                    qa[hh][i] = qb;
                    const float e = bf_lo(qs) * bf_lo(qs) + bf_hi(qs) * bf_hi(qs);
                    if (i & 1) n1 += e; else n0 += e;
                }
                n0 += __shfl_xor_sync(0xffffffffu, n0, 1); n0 += __shfl_xor_sync(0xffffffffu, n0, 2);
                n1 += __shfl_xor_sync(0xffffffffu, n1, 1); n1 += __shfl_xor_sync(0xffffffffu, n1, 2);
                qn[hh] = fmaxf(n0, n1);
            }
        }
        uint32_t mlo = 0x03FF03FFu; asm volatile("" : "+r"(mlo));
        const uint64_t kdesc0 = make_desc(sb + OFF_K, 128, 256, 0);
        const uint64_t vdesc0 = make_desc(sb + OFF_VONES - 256, 128, 256, 0);
        constexpr uint64_t VSTEP = ((uint64_t)16 << 32) - 16;
        mbar_wait_w(bar(B_KV + 0), 0);
        if ((threadIdx.x & 127) == 0 && w == 0) TSTAMP(2);
        const float kmax2 = ldsf(sb + OFF_MISC);
        const bool sure0 = __all_sync(0xffffffffu, named_bar_and(1 + w, 128, qn[0] * kmax2 <= 195.0f));
        const bool sure1 = __all_sync(0xffffffffu, named_bar_and(1 + w, 128, qn[1] * kmax2 <= 195.0f));
        const bool fast0 = sure0 || __all_sync(0xffffffffu, named_bar_and(1 + w, 128, qn[0] * kmax2 <= 223.5f));
        const bool fast1 = sure1 || __all_sync(0xffffffffu, named_bar_and(1 + w, 128, qn[1] * kmax2 <= 223.5f));
        uint32_t a[4] = {qa[0][0], qa[0][1], qa[0][2], qa[0][3]};
#pragma unroll 1
        for (int hh = 0; hh < 2; hh++) {
            bool fast = hh ? fast1 : fast0;
            bool sure = hh ? sure1 : sure0;
            uint32_t as[4];
            {
                const float c = 0.25f * 1.4426950408889634f;
#pragma unroll
                for (int i = 0; i < 4; i++) as[i] = pack_bf16(bf_lo(a[i]) * c, bf_hi(a[i]) * c);
            }
            float S[32], O[12];
            const uint32_t klo0 = (uint32_t)kdesc0, khi = (uint32_t)(kdesc0 >> 32);
            const uint32_t vlo0 = (uint32_t)vdesc0, vhi0 = (uint32_t)(vdesc0 >> 32);
            bool done = false;
            if (!fast) {
                const float nq = hh ? qn[1] : qn[0];
                if (__all_sync(0xffffffffu, named_bar_and(1 + w, 128, nq * kmax2 <= 2300.f))) {
                    uint32_t P[16], sg = 0;
#pragma unroll
                    for (int i = 0; i < 12; i++) O[i] = 0.f;
#pragma unroll
                    for (int i = 0; i < 32; i++) S[i] = 0.f;
                    fence_regs<12>(O); fence_regs<32>(S);
                    mbar_wait_w(bar(B_KV + 1), 0);
                    wg_fence();
                    wg_qk_n64(S, as, kdesc0);
                    wg_commit();
                    wg_wait<0>();
#pragma unroll 1
                    for (int j = 0; j < 32; j++) {
                        if ((j & 3) == 0 && j < 28) mbar_wait_w(bar(B_KV + (j >> 2) + 1), 0);
                        fence_regs<32>(S);
                        softmax_fast(S, P, mlo);
                        fence_regs<32>(S);
#pragma unroll
                        for (int i = 0; i < 16; i += 2) sg = lop3<0xFE>(sg, P[i], P[i + 1]);
                        wg_fence();
#pragma unroll
                        for (int i = 0; i < 4; i++) wg_pv_n24(O, &P[4 * i], ((uint64_t)(vhi0 + (4 * j + i) * 16) << 32) | (vlo0 - (4 * j + i) * 16));
                        wg_qk_n64(S, as, ((uint64_t)khi << 32) | (klo0 + (j + 1) * 128));
                        wg_commit();
                        wg_wait<0>();
                    }
                    fence_regs<12>(O);
                    const bool ok = (sg & 0x80008000u) == 0 && O[4] >= 64.f && O[4] < 3.0e38f && O[6] >= 64.f && O[6] < 3.0e38f;
                    done = __all_sync(0xffffffffu, named_bar_and(1 + w, 128, ok));
                }
            }
            if (fast) {
#pragma unroll
                for (int i = 0; i < 12; i++) O[i] = 0.f;
#pragma unroll
                for (int i = 0; i < 32; i++) S[i] = 0.f;
                fence_regs<12>(O); fence_regs<32>(S);
                wg_fence();
                wg_qk_n64(S, as, kdesc0);
                wg_commit();
                wg_wait<0>();
                uint32_t P[16];
#pragma unroll 2
                for (int c = 0; c < 8; c++) {
                    if (c < 7) mbar_wait_w(bar(B_KV + c + 1), 0);
                    const uint32_t klo = klo0 + c * 512, vlo = vlo0 - c * 256, vhi = vhi0 + c * 256;
#pragma unroll
                    for (int j = 0; j < 4; j++) {
                        fence_regs<32>(S);
                        softmax_fast(S, P, mlo);
                        fence_regs<32>(S);
                        wg_fence();
#pragma unroll
                        for (int i = 0; i < 4; i++) wg_pv_n24(O, &P[4 * i], ((uint64_t)(vhi + (4 * j + i) * 16) << 32) | (vlo - (4 * j + i) * 16));
                        wg_qk_n64(S, as, ((uint64_t)khi << 32) | (klo + (j + 1) * 128));
                        wg_commit();
                        wg_wait<0>();
                    }
                    mbar_arrive_if(bar(B_KHALF), sure && hh == 1 && c == 3 && (threadIdx.x & 127) == 0);
                }
                fence_regs<12>(O);
                if (!sure) fast = __all_sync(0xffffffffu, named_bar_and(1 + w, 128, O[4] >= 64.f && O[6] >= 64.f));
            }
            if (!fast && !done) {
#pragma unroll
                for (int i = 0; i < 12; i++) O[i] = 0.f;
#pragma unroll
                for (int i = 0; i < 32; i++) S[i] = 0.f;
                fence_regs<12>(O); fence_regs<32>(S);
                wg_fence();
                wg_qk_n64(S, a, kdesc0);
                wg_commit();
                wg_wait<0>();
                uint64_t kd = kdesc0 + 128, vd = vdesc0;
                uint32_t P[16];
                float m0 = -INFINITY, m1 = -INFINITY;
#pragma unroll 1
                for (int c = 0; c < 8; c++) {
                    if (c < 7) mbar_wait_w(bar(B_KV + c + 1), 0);
#pragma unroll 1
                    for (int j = 0; j < 4; j++) {
                        fence_regs<32>(S); fence_regs<12>(O);
#pragma unroll
                        for (int i = 0; i < 16; i++) {
                            const uint32_t sbf = pack_bf16(S[2 * i], S[2 * i + 1]);
                            S[2 * i] = bf_lo(sbf) * (0.25f * 1.4426950408889634f);
                            S[2 * i + 1] = bf_hi(sbf) * (0.25f * 1.4426950408889634f);
                        }
                        float x0 = m0, x1 = m1;
#pragma unroll
                        for (int i = 0; i < 8; i++) {
                            x0 = fmaxf(x0, fmaxf(S[4 * i], S[4 * i + 1]));
                            x1 = fmaxf(x1, fmaxf(S[4 * i + 2], S[4 * i + 3]));
                        }
                        x0 = fmaxf(x0, __shfl_xor_sync(0xffffffffu, x0, 1)); x0 = fmaxf(x0, __shfl_xor_sync(0xffffffffu, x0, 2));
                        x1 = fmaxf(x1, __shfl_xor_sync(0xffffffffu, x1, 1)); x1 = fmaxf(x1, __shfl_xor_sync(0xffffffffu, x1, 2));
                        const float r0 = ex2f(m0 - x0), r1 = ex2f(m1 - x1);
                        m0 = x0; m1 = x1;
#pragma unroll
                        for (int i = 0; i < 3; i++) { O[4 * i] *= r0; O[4 * i + 1] *= r0; O[4 * i + 2] *= r1; O[4 * i + 3] *= r1; }
#pragma unroll
                        for (int i = 0; i < 8; i++) {
                            P[2 * i] = pack_f16(ex2f(S[4 * i] - m0), ex2f(S[4 * i + 1] - m0));
                            P[2 * i + 1] = pack_f16(ex2f(S[4 * i + 2] - m1), ex2f(S[4 * i + 3] - m1));
                        }
                        fence_regs<32>(S); fence_regs<12>(O);
                        wg_fence();
                        wg_qk_n64(S, a, kd);
#pragma unroll
                        for (int i = 0; i < 4; i++) wg_pv_n24(O, &P[4 * i], vd + i * VSTEP);
                        wg_commit();
                        wg_wait<0>();
                        kd += 128; vd += 4 * VSTEP;
                    }
                }
            }
            mbar_arrive_if(bar(B_KHALF), !sure && hh == 1 && (threadIdx.x & 127) == 0);
            fence_regs<12>(O);
            const float vscale = ldsf(sb + OFF_MISC + 4);
            const float i0 = __fdividef(vscale, O[4]), i1 = __fdividef(vscale, O[6]);
            const int row = pb * 64 + wq * 16 + g;
            uint32_t* o0 = (uint32_t*)(g_o + (size_t)row * 512 + (hg * 8 + 2 * w + hh) * 16) + t;
            uint32_t* o1 = o0 + 8 * 256;
            o0[0] = pack_bf16(O[0] * i0, O[1] * i0);
            o0[4] = pack_bf16(O[8] * i0, O[9] * i0);
            o1[0] = pack_bf16(O[2] * i1, O[3] * i1);
            o1[4] = pack_bf16(O[10] * i1, O[11] * i1);
            if ((threadIdx.x & 127) == 0 && w == 0) { TSTAMP(3 + hh); CSTAMP(40 + hh); }
#pragma unroll
            for (int i = 0; i < 4; i++) a[i] = qa[1][i];
        }
        named_bar(1 + w, 128);
        if ((threadIdx.x & 127) == 0) {
            red_release_add(&g_o_count[pb], 1);
            mbar_arrive(bar(B_ATT));
        }
        if (threadIdx.x == 0) {
            TSTAMP(30);
            mbar_wait(bar(B_ATT), 0);
            TSTAMP(31);
            poll_counter(&g_o_count[pb], 16);
            TSTAMP(18);
            fence_async_global();
            for (int jj = 0; jj < 4; jj++) {
                mbar_expect_tx(bar(B_O + jj), 16384);
                tma3d(sb + OFF_V + jj * 16384, &tm_o, 0, pb * 64, 2 * jj, bar(B_O + jj));
            }
            __threadfence();
            if (atomicAdd(&g_done, 1) == 2 * NCTA - 1) {
                for (int i = 0; i < NCTA; i++) g_stats[i] = 0ull;
                for (int i = 0; i < 4; i++) { g_kvt_count[i] = 0; g_z_count[i] = 0; }
                for (int i = 0; i < 32; i++) g_o_count[i] = 0;
                g_done = 0;
                __threadfence();
            }
        }
        __syncwarp();
        if (w < 2) {
            float oacc[32];
#pragma unroll
            for (int i = 0; i < 32; i++) oacc[i] = 0.f;
            fence_regs<32>(oacc);
#pragma unroll 1
            for (int jj = 0; jj < 4; jj++) {
                mbar_wait_w(bar(B_WO + jj), 0);
                mbar_wait_w(bar(B_O + jj), 0);
                if (threadIdx.x == 0 && (jj == 0 || jj == 3)) TSTAMP(jj == 0 ? 32 : 33);
                const uint32_t wb = sb + (jj < 2 ? OFF_X + jj * 32768 : (jj == 2 ? OFF_K : OFF_C)) + w * 8192;
                wg_fence();
#pragma unroll
                for (int hc = 0; hc < 2; hc++) {
                    const uint64_t da = make_desc(sb + OFF_V + jj * 16384 + hc * 8192, 16, 1024, 1);
                    const uint64_t db = make_desc(wb + hc * 16384, 8192, 1024, 1);
#pragma unroll
                    for (int ks = 0; ks < 4; ks++) wg_ss_n64_tb(oacc, da + ks * 2, db + ks * 128);
                }
                wg_commit();
            }
            wg_wait<0>();
            fence_regs<32>(oacc);
            const int row = pb * 64 + wq * 16 + g;
            uint32_t* d0 = (uint32_t*)(prm.out + (size_t)row * 1024 + 512 + hg * 128 + w * 64) + t;
            uint32_t* d1 = d0 + 8 * 512;
#pragma unroll
            for (int i = 0; i < 8; i++) {
                d0[4 * i] = pack_bf16(oacc[4 * i], oacc[4 * i + 1]);
                d1[4 * i] = pack_bf16(oacc[4 * i + 2], oacc[4 * i + 3]);
            }
        }
        if ((threadIdx.x & 127) == 0 && w == 0) TSTAMP(5);
    } else {
        const int wa = warp_id - 16, tau = threadIdx.x - 512;
        __syncthreads();
        if (kv_cta) {
            float acc[16];
#pragma unroll
            for (int i = 0; i < 16; i++) acc[i] = 0.f;
            fence_regs<16>(acc);
            mbar_wait_w(bar(B_WKV), 0);
            if (tau == 0) TSTAMP(20);
#pragma unroll
            for (int jj = 0; jj < 4; jj++) {
                mbar_wait_w(bar(B_X + jj), 0);
                wg_fence();
#pragma unroll
                for (int j = 2 * jj; j < 2 * jj + 2; j++) {
                    const uint64_t da = make_desc(sb + OFF_X + j * 8192, 16, 1024, 1);
                    const uint64_t db = make_desc(sb + OFF_C + j * 2048, 16384, 256, 3);
#pragma unroll
                    for (int ks = 0; ks < 4; ks++) wg_ss_n32_tb(acc, da + ks * 2, db + ks * 32);
                }
                wg_commit();
            }
            wg_wait<0>();
            fence_regs<16>(acc);
            if (tau == 0) TSTAMP(22);
            {
                uint32_t kk[4], vv[4];
#pragma unroll
                for (int i = 0; i < 4; i++) { kk[i] = pack_bf16(acc[2 * i], acc[2 * i + 1]); vv[i] = pack_bf16(acc[8 + 2 * i], acc[8 + 2 * i + 1]); }
                const int s = 4 * pb + wa;
                uint32_t* kp = (uint32_t*)(g_kimg + s * 512 + g * 16 + 4 * t);
                kp[0] = kk[0]; kp[64] = kk[1]; kp[32] = kk[2]; kp[96] = kk[3];
                uint32_t* vlo = (uint32_t*)(g_vimg + (127 - s) * 256 + g * 16 + 4 * t);
                uint32_t* vhi = (uint32_t*)(g_vimg + 32768 + 256 + s * 256 + g * 16 + 4 * t);
                vlo[0] = pack_f16(bf_lo(vv[0]), bf_hi(vv[0])); vlo[32] = pack_f16(bf_lo(vv[1]), bf_hi(vv[1]));
                vhi[0] = pack_f16(bf_lo(vv[2]), bf_hi(vv[2])); vhi[32] = pack_f16(bf_lo(vv[3]), bf_hi(vv[3]));
                uint32_t* vr = (uint32_t*)(g_vraw + (size_t)(16 * s + g) * 16) + t;
                vr[0] = vv[0]; vr[64] = vv[1]; vr[4] = vv[2]; vr[68] = vv[3];
                float n0 = bf_lo(kk[0]) * bf_lo(kk[0]) + bf_hi(kk[0]) * bf_hi(kk[0]) + bf_lo(kk[2]) * bf_lo(kk[2]) + bf_hi(kk[2]) * bf_hi(kk[2]);
                float n1 = bf_lo(kk[1]) * bf_lo(kk[1]) + bf_hi(kk[1]) * bf_hi(kk[1]) + bf_lo(kk[3]) * bf_lo(kk[3]) + bf_hi(kk[3]) * bf_hi(kk[3]);
                n0 += __shfl_xor_sync(0xffffffffu, n0, 1); n0 += __shfl_xor_sync(0xffffffffu, n0, 2);
                n1 += __shfl_xor_sync(0xffffffffu, n1, 1); n1 += __shfl_xor_sync(0xffffffffu, n1, 2);
                float km = fmaxf(n0, n1), vm = 0.f;
#pragma unroll
                for (int i = 0; i < 4; i++) vm = fmaxf(vm, fmaxf(fabsf(bf_lo(vv[i])), fabsf(bf_hi(vv[i]))));
#pragma unroll
                for (int o = 4; o < 32; o <<= 1) km = fmaxf(km, __shfl_xor_sync(0xffffffffu, km, o));
#pragma unroll
                for (int o = 1; o < 32; o <<= 1) vm = fmaxf(vm, __shfl_xor_sync(0xffffffffu, vm, o));
                __syncwarp();
                if (lane == 0) {
                    const unsigned long long rec = ((unsigned long long)(__float_as_uint(vm) | 0x80000000u) << 32) | __float_as_uint(km);
                    asm volatile("st.release.gpu.global.u64 [%0], %1;" ::"l"(&g_stats[s]), "l"(rec) : "memory");
                    if (wa == 0) TSTAMP(8);
                }
            }
            if (tau == 0) {
                mbar_expect_tx(bar(B_W + 1), 32768);
                tma4d(sb + OFF_V + 32768, &tm_wq, 0, 0, hg * 2, 2, bar(B_W + 1));
            }
            __syncwarp();
        }
        const int c0 = 4 * b;
        if (wa == 1) {
            float km = 0.f, vm = 0.f;
            {
                unsigned long long rec[4];
                uint32_t spins = 0;
                bool ok;
                do {
                    ok = true;
#pragma unroll
                    for (int i = 0; i < 4; i++) {
                        asm volatile("ld.relaxed.gpu.global.u64 %0, [%1];" : "=l"(rec[i]) : "l"(&g_stats[lane + 32 * i]) : "memory");
                        ok = ok && (rec[i] >> 63);
                    }
                    if (++spins > (1u << 22)) __trap();
                } while (!__all_sync(0xffffffffu, ok));
                asm volatile("fence.acquire.gpu;" ::: "memory");
#pragma unroll
                for (int i = 0; i < 4; i++) { km = fmaxf(km, __uint_as_float((uint32_t)rec[i])); vm = fmaxf(vm, __uint_as_float((uint32_t)(rec[i] >> 32) & 0x7FFFFFFFu)); }
            }
            if (lane == 0) TSTAMP(16);
#pragma unroll
            for (int o = 1; o < 32; o <<= 1) { km = fmaxf(km, __shfl_xor_sync(0xffffffffu, km, o)); vm = fmaxf(vm, __shfl_xor_sync(0xffffffffu, vm, o)); }
            const bool vdirect = (vm <= 32768.f && vm >= 9.765625e-4f) || vm == 0.f;
            float vs = 1.f;
            if (!vdirect && vm < INFINITY) {
                int e = (int)((__float_as_uint(vm) >> 23) & 0xFF) - 127;
                e = max(-100, min(100, e));
                vs = __uint_as_float((uint32_t)(127 + e - 13) << 23);
            }
            if (lane == 0) {
                asm volatile("st.shared.f32 [%0], %1;" ::"r"(sb + OFF_MISC), "f"(km) : "memory");
                asm volatile("st.shared.f32 [%0], %1;" ::"r"(sb + OFF_MISC + 4), "f"(vs) : "memory");
                fence_async_global();
                mbar_wait(bar(B_QDONE), 0);
                TSTAMP(17);
                for (int c = 0; c < 8; c++) {
                    if (vdirect) mbar_expect_tx(bar(B_KV + c), 16384); else mbar_expect_tx_noarrive(bar(B_KV + c), 8192);
                    bulk_g2s(sb + OFF_K + c * 8192, g_kimg + c * 8192, 8192, bar(B_KV + c));
                    if (vdirect) {
                        bulk_g2s(sb + OFF_V + (112 - 16 * c) * 256, g_vimg + (112 - 16 * c) * 256, 4096, bar(B_KV + c));
                        bulk_g2s(sb + OFF_VONES + 256 + c * 4096, g_vimg + 32768 + 256 + c * 4096, 4096, bar(B_KV + c));
                    }
                    if (c == 0) {
                        for (int i = 0; i < 16; i++) sts128(sb + OFF_VONES + i * 16, 0x3C003C00u, 0x3C003C00u, 0x3C003C00u, 0x3C003C00u);
                        fence_async_smem();
                        if (vdirect) mbar_arrive(bar(B_KV + 0));
                    }
                }
                TSTAMP(28);
            }
            __syncwarp();
            if (!vdirect) {
                const float inv = 1.f / vs;
                for (int idx = lane; idx < S_LEN * 8; idx += 32) {
                    const int key = idx >> 3, dp = idx & 7;
                    const uint32_t v = __ldcg((const uint32_t*)g_vraw + idx);
                    const uint32_t h = pack_f16(bf_lo(v) * inv, bf_hi(v) * inv);
                    const int st = key >> 4, hf = (key >> 3) & 1;
                    const uint32_t base = (dp < 4) ? (OFF_V + (127 - st) * 256) : (OFF_VONES + 256 + st * 256);
                    sts32(sb + base + hf * 128 + (key & 7) * 16 + (dp & 3) * 4, h);
                }
            }
            if (!vdirect) {
                fence_async_smem();
                __syncwarp();
                if (lane == 0) { mbar_arrive(bar(B_KV + 0)); for (int c = 0; c < 8; c++) mbar_arrive(bar(B_KV + c)); }
            }
            __syncwarp();
        } else if (wa >= 2) {
            const int kch0 = hg * 128 + lane * 4;
            uint32_t wA[4], wB[4];
            {
                const uint4 s0 = __ldg((const uint4*)(prm.shift_k + kch0 * 4));
                const uint4 s1 = __ldg((const uint4*)(prm.shift_k + kch0 * 4) + 1);
                wA[0] = __byte_perm(s0.x, s0.z, 0x5410); wA[1] = __byte_perm(s0.x, s0.z, 0x7632);
                wA[2] = __byte_perm(s0.y, s0.w, 0x5410); wA[3] = __byte_perm(s0.y, s0.w, 0x7632);
                wB[0] = __byte_perm(s1.x, s1.z, 0x5410); wB[1] = __byte_perm(s1.x, s1.z, 0x7632);
                wB[2] = __byte_perm(s1.y, s1.w, 0x5410); wB[3] = __byte_perm(s1.y, s1.w, 0x7632);
            }
            mbar_wait_w(bar(B_KVIN), 0);
            const uint32_t kb = sb + OFF_C + (wa - 2) * 32 * 256 + lane * 8, vb = kb + 17408;
            uint32_t k0a, k0b, k1a, k1b, k2a, k2b;
            lds64(kb, k0a, k0b); lds64(kb + 256, k1a, k1b); lds64(kb + 512, k2a, k2b);
#pragma unroll
            for (int o8 = 0; o8 < 4; o8++) {
                uint32_t xa[8], xb[8];
#pragma unroll
                for (int i = 0; i < 8; i++) {
                    uint32_t k3a, k3b, va, vb2;
                    lds64(kb + (o8 * 8 + i + 3) * 256, k3a, k3b);
                    lds64(vb + (o8 * 8 + i) * 256, va, vb2);
                    xa[i] = bmul2(badd2(badd2(badd2(bmul2(k0a, wA[3]), bmul2(k1a, wA[2])), bmul2(k2a, wA[1])), bmul2(k3a, wA[0])), va);
                    xb[i] = bmul2(badd2(badd2(badd2(bmul2(k0b, wB[3]), bmul2(k1b, wB[2])), bmul2(k2b, wB[1])), bmul2(k3b, wB[0])), vb2);
                    k0a = k1a; k0b = k1b; k1a = k2a; k1b = k2b; k2a = k3a; k2b = k3b;
                }
                uint4* dst = (uint4*)(g_kvT + (size_t)kch0 * S_LEN + pb * 64 + (wa - 2) * 32 + o8 * 8);
                dst[0] = make_uint4(__byte_perm(xa[0], xa[1], 0x5410), __byte_perm(xa[2], xa[3], 0x5410), __byte_perm(xa[4], xa[5], 0x5410), __byte_perm(xa[6], xa[7], 0x5410));
                dst[S_LEN / 8] = make_uint4(__byte_perm(xa[0], xa[1], 0x7632), __byte_perm(xa[2], xa[3], 0x7632), __byte_perm(xa[4], xa[5], 0x7632), __byte_perm(xa[6], xa[7], 0x7632));
                dst[2 * (S_LEN / 8)] = make_uint4(__byte_perm(xb[0], xb[1], 0x5410), __byte_perm(xb[2], xb[3], 0x5410), __byte_perm(xb[4], xb[5], 0x5410), __byte_perm(xb[6], xb[7], 0x5410));
                dst[3 * (S_LEN / 8)] = make_uint4(__byte_perm(xb[0], xb[1], 0x7632), __byte_perm(xb[2], xb[3], 0x7632), __byte_perm(xb[4], xb[5], 0x7632), __byte_perm(xb[6], xb[7], 0x7632));
            }
            mbar_arrive(bar(B_KVT));
            mbar_wait_w(bar(B_KVT), 0);
            sts128(sb + C_H + (tau - 64) * 32, 0u, 0u, 0u, 0u);
            sts128(sb + C_H + (tau - 64) * 32 + 16, 0u, 0u, 0u, 0u);
            fence_async_smem();
        } else {
            if (lane == 0) {
                mbar_wait(bar(B_KV + 7), 0);
                kv_tiles_load(sb, &tm_k, &tm_v, pb, hg);
                prefetch_tm(&tm_wo); prefetch_tm(&tm_o); prefetch_tm(&tm_h);
                mbar_wait(bar(B_KVT), 0);
                mbar_expect_tx(bar(B_H), 4096);
                tma2d(sb + C_H + 2048, &tm_h, 0, c0 * 64, bar(B_H));
                red_release_add(&g_kvt_count[hg], 1);
                TSTAMP(34);
                poll_counter(&g_kvt_count[b >> 5], 32);
                fence_async_global();
                mbar_expect_tx(bar(B_CV), 16384);
                bulk_g2s(sb + C_KVC, g_kvT + (size_t)c0 * S_LEN, 16384, bar(B_CV));
                mbar_wait(bar(B_QDONE), 0);
                for (int jj = 0; jj < 2; jj++) {
                    mbar_expect_tx(bar(B_WO + jj), 32768);
                    tma4d(sb + OFF_X + jj * 32768, &tm_wo, 0, 0, hg * 2, 2 * jj, bar(B_WO + jj));
                }
            }
            __syncwarp();
        }
        named_bar(5, 128);
        mbar_wait_w(bar(B_CV), 0);
        if (tau == 0) TSTAMP(9);
        constexpr int NCH = 4;
#pragma unroll 1
        for (int ch = 0; ch < NCH; ch++) {
            {
                const uint32_t src = sb + C_KVC + ch * 4096 + tau * 32;
                const uint4 u0 = lds128(src), u1 = lds128(src + 16);
                const uint32_t prev = tau > 0 ? lds32(src - 4) : 0u;
                const uint32_t zd = sb + C_Z + (32 + tau * 16) * 4;
                sts128(zd,      __byte_perm(u0.x, prev, 0x7610), __byte_perm(u0.x, u0.x, 0x1032), __byte_perm(u0.y, u0.x, 0x7610), __byte_perm(u0.y, u0.y, 0x1032));
                sts128(zd + 16, __byte_perm(u0.z, u0.y, 0x7610), __byte_perm(u0.z, u0.z, 0x1032), __byte_perm(u0.w, u0.z, 0x7610), __byte_perm(u0.w, u0.w, 0x1032));
                sts128(zd + 32, __byte_perm(u1.x, u0.w, 0x7610), __byte_perm(u1.x, u1.x, 0x1032), __byte_perm(u1.y, u1.x, 0x7610), __byte_perm(u1.y, u1.y, 0x1032));
                sts128(zd + 48, __byte_perm(u1.z, u1.y, 0x7610), __byte_perm(u1.z, u1.z, 0x1032), __byte_perm(u1.w, u1.z, 0x7610), __byte_perm(u1.w, u1.w, 0x1032));
                if (tau < 32) sts32(sb + C_Z + tau * 4, 0u);
            }
            named_bar(5, 128);
            mbar_wait_w(bar(B_H), ch & 1);
            float D[32];
#pragma unroll
            for (int i = 0; i < 32; i++) D[i] = 0.f;
            fence_regs<32>(D);
            const uint32_t z0 = sb + C_Z + (32 + 32 * (wa >> 1) + 16 * (wa & 1) + 2 * g - 2 * t) * 4;
            const uint64_t hd = make_desc(sb + C_H + 2048, 16, 512, 2);
            float E[16];
            conv_phase<64>(D, z0, hd);
            {
                float F48[24];
#pragma unroll
                for (int i = 0; i < 24; i++) asm volatile("mov.f32 %0, %1;" : "=f"(F48[i]) : "f"(D[8 + i]));
                conv_phase<48>(F48, z0 + 2048, hd);
                float F32[16];
#pragma unroll
                for (int i = 0; i < 8; i++) D[8 + i] = F48[i];
#pragma unroll
                for (int i = 0; i < 16; i++) asm volatile("mov.f32 %0, %1;" : "=f"(F32[i]) : "f"(F48[8 + i]));
                conv_phase<32>(F32, z0 + 4096, hd);
                float F16[8];
#pragma unroll
                for (int i = 0; i < 8; i++) E[i] = F32[i];
#pragma unroll
                for (int i = 0; i < 8; i++) asm volatile("mov.f32 %0, %1;" : "=f"(F16[i]) : "f"(F32[8 + i]));
                conv_phase<16>(F16, z0 + 6144, hd);
#pragma unroll
                for (int i = 0; i < 8; i++) E[8 + i] = F16[i];
            }
            if (tau == 0 && ch < 3) {
                mbar_expect_tx(bar(B_H), 4096);
                tma2d(sb + C_H + 2048, &tm_h, 0, (c0 + ch + 1) * 64, bar(B_H));
            }
            const int bb0 = 16 * (wa & 1) + 2 * g;
            const int xsw = (g & 3) << 3;
            {
                const uint32_t xb = sb + C_Z + (wa >> 1) * 4096;
#pragma unroll
                for (int jn = 0; jn < 4; jn++) {
#pragma unroll
                    for (int r = 0; r < 2; r++) {
                        const float v0 = (wa < 2) ? E[4 * jn + 2 * r] : D[4 * jn + 2 * r];
                        const float v1 = (wa < 2) ? E[4 * jn + 2 * r + 1] : D[4 * jn + 2 * r + 1];
                        sts64f(xb + ((bb0 + r) * 32 + ((8 * jn + 2 * t) ^ xsw)) * 4, v0, v1);
                    }
                }
            }
            named_bar(5, 128);
            {
                const float dsc = __bfloat162float(prm.ssm_D[c0 + ch]);
                const uint32_t xb = sb + C_Z + ((wa >> 1) ^ 1) * 4096;
#pragma unroll
                for (int jn = 0; jn < 4; jn++) {
#pragma unroll
                    for (int e = 0; e < 2; e++) {
                        const int n = 8 * jn + 2 * t + e;
                        float y0, y1; int m, rn;
                        if (wa < 2) { y0 = D[4 * jn + e]; y1 = D[4 * jn + 2 + e]; m = n; rn = n - 1; }
                        else {
                            const bool last = (jn == 3 && e == 1) && (t == 3);
                            y0 = last ? D[13] : E[4 * jn + e]; y1 = last ? D[15] : E[4 * jn + 2 + e];
                            m = last ? 32 : 33 + n; rn = m - 32;
                        }
                        if (rn >= 0) {
                            y0 += ldsf(xb + (bb0 * 32 + (rn ^ xsw)) * 4);
                            y1 += ldsf(xb + ((bb0 + 1) * 32 + (rn ^ xsw)) * 4);
                        }
                        const uint32_t addr = sb + C_KVC + ch * 4096 + (32 * m + bb0) * 2;
                        const uint32_t kv = lds32(addr);
                        const uint32_t yb = pack_bf16(y0, y1);
                        const uint32_t kd = pack_bf16(bf_lo(kv) * dsc, bf_hi(kv) * dsc);
                        sts32(addr, badd2(yb, kd));
                    }
                }
                fence_async_smem();
            }
            named_bar(5, 128);
            if (tau == 0) {
                bulk_s2g(g_zT + (size_t)(c0 + ch) * S_LEN, sb + C_KVC + ch * 4096, 4096);
                bulk_commit();
                TSTAMP(10 + ch);
            }
        }
        {
            const int cg = tau & 15, pr = tau >> 4;
            const int p0 = pb * 64 + pr * 8, ch0 = hg * 128 + cg * 8;
            uint4 qr[8];
#pragma unroll
            for (int i = 0; i < 8; i++) qr[i] = __ldg((const uint4*)(prm.aq + (size_t)(p0 + i) * 512 + ch0));
            if (tau == 0) {
                bulk_wait_all();
                mbar_expect_tx(bar(B_WO + 3), 32768);
                tma4d(sb + OFF_C, &tm_wo, 0, 0, hg * 2, 6, bar(B_WO + 3));
                fence_async_global();
                red_release_add(&g_z_count[b >> 5], 1);
                poll_counter(&g_z_count[hg], 32);
                __threadfence();
                if (atomicAdd(&g_done, 1) == 2 * NCTA - 1) {
                    for (int i = 0; i < NCTA; i++) g_stats[i] = 0ull;
                    for (int i = 0; i < 4; i++) { g_kvt_count[i] = 0; g_z_count[i] = 0; }
                    for (int i = 0; i < 32; i++) g_o_count[i] = 0;
                    g_done = 0;
                    __threadfence();
                }
            }
            named_bar(5, 128);
            uint4 zz[8];
#pragma unroll
            for (int c = 0; c < 8; c++) zz[c] = __ldcg((const uint4*)(g_zT + (size_t)(ch0 + c) * S_LEN + p0));
#pragma unroll
            for (int i = 0; i < 8; i++) {
                uint32_t r[4];
#pragma unroll
                for (int k = 0; k < 4; k++) {
                    const uint32_t pr2 = __byte_perm((&zz[2 * k].x)[i >> 1], (&zz[2 * k + 1].x)[i >> 1], (i & 1) ? 0x7632 : 0x5410);
                    r[k] = bmul2((&qr[i].x)[k], pr2);
                }
                *(uint4*)(prm.out + (size_t)(p0 + i) * 1024 + ch0) = make_uint4(r[0], r[1], r[2], r[3]);
            }
        }
        if (tau == 0) {
            TSTAMP(14);
            mbar_wait(bar(B_KHALF), 0);
            mbar_expect_tx(bar(B_WO + 2), 32768);
            tma4d(sb + OFF_K, &tm_wo, 0, 0, hg * 2, 4, bar(B_WO + 2));
        }
    }
}

typedef CUresult (*EncodeFn)(CUtensorMap*, CUtensorMapDataType, cuuint32_t, void*, const cuuint64_t*, const cuuint64_t*,
                             const cuuint32_t*, const cuuint32_t*, CUtensorMapInterleave, CUtensorMapSwizzle,
                             CUtensorMapL2promotion, CUtensorMapFloatOOBfill);

void make_map(EncodeFn fn, CUtensorMap* tm, const void* ptr, int rank, const cuuint64_t* dims, const cuuint64_t* strides, const cuuint32_t* box, CUtensorMapSwizzle swz) {
    cuuint32_t es[4] = {1, 1, 1, 1};
    fn(tm, CU_TENSOR_MAP_DATA_TYPE_BFLOAT16, rank, const_cast<void*>(ptr), dims, strides, box, es, CU_TENSOR_MAP_INTERLEAVE_NONE, swz,
       CU_TENSOR_MAP_L2_PROMOTION_L2_128B, CU_TENSOR_MAP_FLOAT_OOB_FILL_NONE);
}

}

extern "C" void kernel_launch(void* const* d_in, const int* in_sizes, int n_in, void* d_out, int out_size) {
    (void)in_sizes; (void)n_in; (void)out_size;
    static EncodeFn encode = nullptr;
    static void* o_ptr = nullptr;
    if (!encode) {
        cudaDriverEntryPointQueryResult qres;
        void* fn = nullptr;
        cudaGetDriverEntryPoint("cuTensorMapEncodeTiled", &fn, cudaEnableDefault, &qres);
        encode = (EncodeFn)fn;
        cudaGetSymbolAddress(&o_ptr, g_o);
        cudaFuncSetAttribute(fused_kernel, cudaFuncAttributeMaxDynamicSharedMemorySize, SMEM_TOTAL);
    }
    CUtensorMap tm_x, tm_wq, tm_wo, tm_o, tm_h, tm_k, tm_v;
    {
        const cuuint64_t dims[3] = {64, 2048, 8}, str[2] = {1024, 128};
        const cuuint32_t b64[3] = {64, 64, 2};
        make_map(encode, &tm_x, d_in[6], 3, dims, str, b64, CU_TENSOR_MAP_SWIZZLE_128B);
        make_map(encode, &tm_o, o_ptr, 3, dims, str, b64, CU_TENSOR_MAP_SWIZZLE_128B);
    }
    {
        const cuuint64_t dims[4] = {64, 64, 8, 8}, str[3] = {1024, 128, 65536};
        const cuuint32_t box[4] = {64, 64, 2, 2};
        make_map(encode, &tm_wq, d_in[7], 4, dims, str, box, CU_TENSOR_MAP_SWIZZLE_128B);
        make_map(encode, &tm_wo, d_in[10], 4, dims, str, box, CU_TENSOR_MAP_SWIZZLE_128B);
    }
    {
        const cuuint64_t dims[2] = {32, 512 * 64}, str[1] = {64};
        const cuuint32_t box[2] = {32, 64};
        make_map(encode, &tm_h, d_in[4], 2, dims, str, box, CU_TENSOR_MAP_SWIZZLE_64B);
    }
    {
        const cuuint64_t dims[2] = {512, 2048}, str[1] = {1024};
        const cuuint32_t bk[2] = {128, 67}, bv[2] = {128, 64};
        make_map(encode, &tm_k, d_in[1], 2, dims, str, bk, CU_TENSOR_MAP_SWIZZLE_NONE);
        make_map(encode, &tm_v, d_in[2], 2, dims, str, bv, CU_TENSOR_MAP_SWIZZLE_NONE);
    }
    Params prm;
    prm.aq = (const __nv_bfloat16*)d_in[0];
    prm.wk = (const __nv_bfloat16*)d_in[8];
    prm.wv = (const __nv_bfloat16*)d_in[9];
    prm.shift_k = (const __nv_bfloat16*)d_in[3];
    prm.ssm_D = (const __nv_bfloat16*)d_in[5];
    prm.out = (__nv_bfloat16*)d_out;
    fused_kernel<<<NCTA, NTHREADS, SMEM_TOTAL>>>(tm_x, tm_wq, tm_wo, tm_o, tm_h, tm_k, tm_v, prm);
}
```
